```python
import torch

def _softmax(x, axis=-1):
    return torch.softmax(x, dim=axis)

def _gelu(x):
    return torch.nn.functional.gelu(x, approximate='tanh')

def _silu(x):
    return torch.nn.functional.silu(x)

def _sigmoid(x):
    return torch.sigmoid(x)

def _layernorm(x, axis=-1, eps=1e-05):
    m = x.mean(dim=axis, keepdim=True)
    v = x.var(dim=axis, keepdim=True, unbiased=False)
    return (x - m) / torch.sqrt(v + eps)

def _scatter_add(tgt, idx, src, axis=0):
    return tgt.clone().index_add_(axis, idx, src)

def _segment_sum(src, seg, n):
    out = torch.zeros((n,) + src.shape[1:], dtype=src.dtype)
    return out.index_add_(0, seg, src)

def _pad(x, pw):
    flat = tuple((v for pair in reversed(pw) for v in pair))
    return torch.nn.functional.pad(x, flat)
kernel_name = 'gather_scatter__tensor_product_equiv_tfn__graph'

def setup_inputs():

    _w = lambda a: (lambda t: t.to(torch.bfloat16) if t.is_floating_point() else t)(torch.as_tensor(a))
    N, deg, C, L, DE = (10000, 32, 128, 1, 4)
    E = N * deg
    M = (L + 1) ** 2
    src = (lambda lo, hi, *s: torch.randint(lo, hi, s))(0, N, E).to(torch.int64)
    dst = (lambda lo, hi, *s: torch.randint(lo, hi, s))(0, N, E).to(torch.int64)
    r = (lambda *s: torch.randn(*s, dtype=torch.bfloat16) * 0.05)(E, 3)
    r = r / (torch.linalg.norm(r, dim=-1, keepdim=True) + 1e-09)
    rx, ry, rz = (r[:, 0].clone(), r[:, 1].clone(), r[:, 2].clone())
    Ys = [torch.ones((E, 1), dtype=float)]
    if L >= 1:
        Ys.append(r.to(float))
    if L >= 2:
        Ys.append(torch.stack([2 * rx * ry, 2 * ry * rz, (3 * rz * rz - 1.0) / (lambda _x: torch.sqrt(torch.as_tensor(_x)))(3.0), 2 * rx * rz, rx * rx - ry * ry], dim=-1).to(float))
    for _l in range(3, L + 1):
        Ys.append(((lambda *s: torch.randn(*s, dtype=torch.bfloat16) * 0.05)(E, 2 * _l + 1) * 0.3).to(float))
    Y = torch.cat(Ys, dim=-1)
    cg = torch.zeros((M, M, M), dtype=float)
    off = [_l * _l for _l in range(L + 2)]
    for l1 in range(L + 1):
        for l2 in range(L + 1):
            for l3 in range(abs(l1 - l2), min(L, l1 + l2) + 1):
                d1, d2, d3 = (2 * l1 + 1, 2 * l2 + 1, 2 * l3 + 1)
                cg[off[l1]:off[l1 + 1], off[l2]:off[l2 + 1], off[l3]:off[l3 + 1]] = (lambda *s: torch.randn(*s, dtype=torch.bfloat16) * 0.05)(d1, d2, d3) / (lambda _x: torch.sqrt(torch.as_tensor(_x)))(float(d1 * d2))
    return {'x': _w((lambda *s: torch.randn(*s, dtype=torch.bfloat16) * 0.05)(N, C, M) * 0.2), 'src': _w(src), 'dst': _w(dst), 'Y': _w(Y), 'edge_feat': _w((lambda *s: torch.randn(*s, dtype=torch.bfloat16) * 0.05)(E, DE)), 'w_rad': _w((lambda *s: torch.randn(*s, dtype=torch.bfloat16) * 0.05)(DE, C) * (1.0 / max(1.0, DE) ** 0.5)), 'cg': _w(cg), 'w_mix': _w((lambda *s: torch.randn(*s, dtype=torch.bfloat16) * 0.05)(C, C) * (1.0 / max(1.0, C) ** 0.5))}

def reference(x, src, dst, Y, edge_feat, w_rad, cg, w_mix):
    N, C, M = (x.shape[0], x.shape[1], x.shape[2])
    R = _silu(edge_feat @ w_rad)
    xs = x[src]
    tp = torch.einsum('eci,ef,ifo->eco', xs, Y, cg)
    msg = R[:, :, None] * tp
    agg = _segment_sum(msg.reshape(-1, C * M), dst, N).reshape(N, C, M)
    return torch.einsum('ncm,cd->ndm', agg, w_mix)
```

```cpp
#include <cuda_runtime.h>
#include <cuda_bf16.h>
#include <stdint.h>

namespace {

constexpr int NN = 10000;
constexpr int NE = 320000;
constexpr int NB = 132;
constexpr int NW = 20;
constexpr int NT = NW * 32;
constexpr int NPB = 76;
constexpr int CELL = 48;
constexpr int CAP = 19;
constexpr int DS = 3;
constexpr int WSTEPS = CAP + DS;
constexpr int NE4 = NE / 4;
constexpr uint32_t KEY_NONE = 0xFFFFFFFFu;
constexpr uint32_t KEY_OVF = 0xFFFFFFFEu;
constexpr uint32_t F_PAD = 256, F_WRAP = 128;

constexpr int SM_RING = 0;
constexpr int SM_WMIX = SM_RING + NW * DS * 2048;
constexpr int SM_REC = SM_WMIX + 32768;
constexpr int SM_SRC = SM_REC + NW * CAP * 128;
constexpr int SM_AZ = SM_SRC + NW * WSTEPS * 32;
constexpr int SM_MISC = SM_AZ + 2048;
constexpr int SM_TOTAL = SM_MISC + 2048;
constexpr int SM_STAGE = SM_RING;
constexpr int SM_HIST = SM_RING + 32768;
static_assert(SM_TOTAL <= 232448, "smem");

__device__ uint4 g_cells[NB * NB * CELL / 4];
__device__ uint4 g_stash[NB * NW * 6 * 32];
__device__ unsigned g_bar;
#define TSTAMP(i)

__device__ __forceinline__ void mma16816(float* d, uint32_t a0, uint32_t a1, uint32_t a2, uint32_t a3, uint32_t b0, uint32_t b1) {
    asm("mma.sync.aligned.m16n8k16.row.col.f32.bf16.bf16.f32 {%0,%1,%2,%3}, {%4,%5,%6,%7}, {%8,%9}, {%0,%1,%2,%3};"
        : "+f"(d[0]), "+f"(d[1]), "+f"(d[2]), "+f"(d[3]) : "r"(a0), "r"(a1), "r"(a2), "r"(a3), "r"(b0), "r"(b1));
}
__device__ __forceinline__ void mma1688z(float* d, uint32_t a0, uint32_t a1, uint32_t b0) {
    asm("mma.sync.aligned.m16n8k8.row.col.f32.bf16.bf16.f32 {%0,%1,%2,%3}, {%4,%5}, {%6}, {%7,%7,%7,%7};"
        : "=f"(d[0]), "=f"(d[1]), "=f"(d[2]), "=f"(d[3]) : "r"(a0), "r"(a1), "r"(b0), "f"(0.f));
}
__device__ __forceinline__ uint32_t pack2(float lo, float hi) {
    uint32_t r; asm("cvt.rn.bf16x2.f32 %0, %1, %2;" : "=r"(r) : "f"(hi), "f"(lo)); return r;
}
__device__ __forceinline__ float silu_h(float h) {
    float t; asm("tanh.approx.f32 %0, %1;" : "=f"(t) : "f"(h)); return fmaf(h, t, h);
}
__device__ __forceinline__ uint32_t mul_lo(uint32_t v, uint32_t r) {
    __nv_bfloat162 a = *(__nv_bfloat162*)&v, b = *(__nv_bfloat162*)&r; __nv_bfloat162 c = __hmul2(a, __low2bfloat162(b)); return *(uint32_t*)&c;
}
__device__ __forceinline__ uint32_t mul_hi(uint32_t v, uint32_t r) {
    __nv_bfloat162 a = *(__nv_bfloat162*)&v, b = *(__nv_bfloat162*)&r; __nv_bfloat162 c = __hmul2(a, __high2bfloat162(b)); return *(uint32_t*)&c;
}
__device__ __forceinline__ uint2 lds64(uint32_t a) {
    uint2 r; asm volatile("ld.shared.v2.u32 {%0,%1}, [%2];" : "=r"(r.x), "=r"(r.y) : "r"(a)); return r;
}
__device__ __forceinline__ uint4 lds128(uint32_t a) {
    uint4 r; asm volatile("ld.shared.v4.u32 {%0,%1,%2,%3}, [%4];" : "=r"(r.x), "=r"(r.y), "=r"(r.z), "=r"(r.w) : "r"(a) : "memory"); return r;
}
__device__ __forceinline__ int bin_start(int b) { return (b * NN + NB - 1) / NB; }
__device__ __forceinline__ int chunk_start4(int c) { return (c * NE4) / NB; }
__device__ __forceinline__ float bf2f(uint32_t h) { return __uint_as_float(h << 16); }

__device__ __noinline__ void slow_path(unsigned char* smem, int n0, int nn, const uint16_t* x, const int* src, const int* dst,
                                       const uint16_t* Y, const uint16_t* ef, const uint16_t* w_rad, const uint16_t* cg,
                                       const uint16_t* w_mix, __nv_bfloat16* out) {
    float* agg = (float*)smem;
    const int tid = threadIdx.x, lane = tid & 31, w = tid >> 5;
    __syncthreads();
    for (int i = tid; i < NPB * 512; i += NT) agg[i] = 0.f;
    __syncthreads();
    for (int e0 = w * 32; e0 < NE; e0 += NT) {
        int dl = dst[e0 + lane] - n0;
        unsigned m = __ballot_sync(0xffffffff, dl >= 0 && dl < nn);
        while (m) {
            int l = __ffs(m) - 1; m &= m - 1;
            int e = e0 + l, d = __shfl_sync(0xffffffff, dl, l), s = src[e];
            float T[16];
            for (int i = 0; i < 4; i++) for (int o = 0; o < 4; o++) {
                float a = 0.f;
                for (int f = 0; f < 4; f++) a += bf2f(Y[e * 4 + f]) * bf2f(cg[i * 16 + f * 4 + o]);
                T[i * 4 + o] = a;
            }
            for (int k = 0; k < 4; k++) {
                int c = lane + 32 * k;
                float z = 0.f;
                for (int j = 0; j < 4; j++) z += bf2f(ef[e * 4 + j]) * bf2f(w_rad[j * 128 + c]);
                float R = z / (1.f + __expf(-z));
                for (int o = 0; o < 4; o++) {
                    float a = 0.f;
                    for (int i = 0; i < 4; i++) a += bf2f(x[(size_t)s * 512 + c * 4 + i]) * T[i * 4 + o];
                    atomicAdd(&agg[d * 512 + c * 4 + o], R * a);
                }
            }
        }
    }
    __syncthreads();
    for (int i = tid; i < nn * 512; i += NT) {
        int n = i >> 9, d = (i >> 2) & 127, o = i & 3;
        float a = 0.f;
        for (int c = 0; c < 128; c++) a += agg[n * 512 + c * 4 + o] * bf2f(w_mix[c * 128 + d]);
        out[(size_t)(n0 + n) * 512 + (i & 511)] = __float2bfloat16(a);
    }
}

__global__ void __launch_bounds__(NT, 1)
tfn_kernel(const unsigned char* __restrict__ x, const int4* __restrict__ src4, const int4* __restrict__ dst4,
           const uint2* __restrict__ Y, const uint2* __restrict__ ef, const uint16_t* __restrict__ w_rad,
           const uint16_t* __restrict__ cg, const uint4* __restrict__ w_mix, uint32_t* __restrict__ out) {
    extern __shared__ __align__(1024) unsigned char smem[];
    const uint32_t sb = (uint32_t)__cvta_generic_to_shared(smem);
    const int b = blockIdx.x, tid = threadIdx.x, lane = tid & 31, g = lane >> 2, t = lane & 3;
    const int w = __shfl_sync(0xffffffff, tid >> 5, 0);
    uint32_t* stage = (uint32_t*)(smem + SM_STAGE);
    uint32_t* hist = (uint32_t*)(smem + SM_HIST);
    uint32_t* cnt = (uint32_t*)(smem + SM_MISC);
    uint32_t* deg = cnt + 160;
    uint32_t* order = deg + 80;
    uint32_t* flag = order + 80;
    TSTAMP(0);

    const int c0 = chunk_start4(b), c1 = chunk_start4(b + 1);
    const int n0 = bin_start(b), nn = bin_start(b + 1) - n0;
    const bool has4 = c0 + tid < c1;
    int4 d4 = make_int4(0, 0, 0, 0), s4 = d4;
    if (has4) { d4 = __ldg(dst4 + c0 + tid); s4 = __ldg(src4 + c0 + tid); }
    if (tid == NT - 32) {
        asm volatile("cp.async.bulk.prefetch.L2.global [%0], %1;" :: "l"(ef + c0 * 4), "r"((c1 - c0) * 32));
        asm volatile("cp.async.bulk.prefetch.L2.global [%0], %1;" :: "l"(Y + c0 * 4), "r"((c1 - c0) * 32));
        for (int i = 0; i < nn; i += 19)
            asm volatile("cp.async.bulk.prefetch.L2.global [%0], %1;" :: "l"(x + (size_t)(n0 + i) * 1024), "r"(min(19, nn - i) * 1024));
    }
    for (int i = tid; i < 2048; i += NT) {
        int c = i >> 4, db = i & 15;
        int k = (c & 0x70) | ((c & 1) << 3) | ((c & 15) >> 1);
        uint32_t dstp = sb + SM_WMIX + (k >> 3) * 2048 + db * 128 + (k & 7) * 16;
        asm volatile("cp.async.cg.shared.global [%0], [%1], 16;" :: "r"(dstp), "l"(w_mix + i) : "memory");
    }
    asm volatile("cp.async.commit_group;" ::: "memory");
    for (int i = tid; i < NB * CELL / 4; i += NT) ((uint4*)stage)[i] = make_uint4(KEY_NONE, KEY_NONE, KEY_NONE, KEY_NONE);
    ((uint4*)hist)[tid] = make_uint4(0, 0, 0, 0);
    if (tid < 160) cnt[tid] = 0;
    if (tid == 0) *flag = 0;
    for (int i = tid; i < NW * CAP * 8; i += NT) ((uint4*)(smem + SM_REC))[i] = make_uint4(0, 0, 0, 0);
    for (int i = tid; i < NW * WSTEPS * 2; i += NT) ((uint4*)(smem + SM_SRC))[i] = make_uint4(F_PAD, F_PAD, F_PAD, F_PAD);
    if (tid < 256) {
        int j = tid >> 5;
        uint32_t v0 = 0, v1 = 0;
        if (t < 2) {
            int cc = 16 * j + 2 * g;
            uint32_t r0 = *(const uint32_t*)(w_rad + (2 * t) * 128 + cc), r1 = *(const uint32_t*)(w_rad + (2 * t + 1) * 128 + cc);
            v0 = pack2(0.5f * bf2f(r0 & 0xFFFF), 0.5f * bf2f(r1 & 0xFFFF));
            v1 = pack2(0.5f * bf2f(r0 >> 16), 0.5f * bf2f(r1 >> 16));
        }
        *(uint2*)(smem + SM_AZ + (j >> 1) * 512 + lane * 16 + (j & 1) * 8) = make_uint2(v0, v1);
    }
    uint32_t at[4];
    {
        const int o = g & 3, f = 2 * (t & 1);
#pragma unroll
        for (int i = 0; i < 4; i++) {
            uint32_t lo = cg[i * 16 + f * 4 + o], hi = cg[i * 16 + (f + 1) * 4 + o];
            at[i] = (t >> 1) == (g >> 2) ? (lo | (hi << 16)) : 0;
        }
    }
    __syncthreads();

    if (has4) {
        const int dd[4] = {d4.x, d4.y, d4.z, d4.w}, ss[4] = {s4.x, s4.y, s4.z, s4.w};
        uint32_t bin[4], slot[4];
#pragma unroll
        for (int k = 0; k < 4; k++) { bin[k] = (uint32_t)(dd[k] * NB) / NN; slot[k] = atomicAdd(&cnt[bin[k]], 1); }
#pragma unroll
        for (int k = 0; k < 4; k++) {
            uint32_t key = (uint32_t)ss[k] | (((tid * 4 + k) * NPB + (dd[k] - bin_start(bin[k]))) << 14);
            if (slot[k] < CELL - 1) stage[bin[k] * CELL + slot[k]] = key;
            else stage[bin[k] * CELL + CELL - 1] = KEY_OVF;
        }
    }
    __syncthreads();
    TSTAMP(1);
    for (int i = tid; i < NB * CELL / 4; i += NT) {
        int bn = i / (CELL / 4), r = i - bn * (CELL / 4);
        g_cells[(bn * NB + b) * (CELL / 4) + r] = ((uint4*)stage)[i];
    }
    __syncthreads();
    if (tid == 0) {
        __threadfence();
        unsigned old = atomicAdd(&g_bar, 1);
        unsigned target = (old / NB + 1) * NB;
        unsigned v; int spins = 0;
        do { asm volatile("ld.acquire.gpu.global.u32 %0, [%1];" : "=r"(v) : "l"(&g_bar) : "memory"); } while ((int)(v - target) < 0 && ++spins < (1 << 24));
    }
    __syncthreads();
    TSTAMP(2);

    uint32_t key[12]; uint2 rY[12], rE[12]; uint32_t rk[12];
#pragma unroll
    for (int j = 0; j < 3; j++) {
        int i = tid + j * NT;
        uint4 v = make_uint4(KEY_NONE, KEY_NONE, KEY_NONE, KEY_NONE);
        if (i < NB * CELL / 4) v = __ldcg(&g_cells[b * NB * (CELL / 4) + i]);
        key[4 * j] = v.x; key[4 * j + 1] = v.y; key[4 * j + 2] = v.z; key[4 * j + 3] = v.w;
    }
#pragma unroll
    for (int j = 0; j < 3; j++) {
        const int eb = 4 * chunk_start4((tid + j * NT) / (CELL / 4));
#pragma unroll
        for (int k = 0; k < 4; k++) {
            const int u = 4 * j + k;
            if (key[u] < KEY_OVF) {
                uint32_t v = key[u] >> 14, s = key[u] & 0x3FFF;
                uint32_t el = v / NPB, dl = v - el * NPB;
                rY[u] = __ldg(Y + eb + el); rE[u] = __ldg(ef + eb + el);
                uint32_t hidx = dl * 32 + ((s * 209) >> 16);
                rk[u] = atomicAdd(&hist[hidx], 1);
                key[u] = s | (hidx << 14);
            } else if (key[u] == KEY_OVF) *flag = 1;
        }
    }
    __syncthreads();
    TSTAMP(3);
#pragma unroll
    for (int k = 0; k < 4; k++) {
        uint32_t dsum = __reduce_add_sync(0xffffffff, hist[(w * 4 + k) * 32 + lane]);
        if (lane == 0) deg[w * 4 + k] = dsum * 128 + (127 - (w * 4 + k));
    }
    __syncthreads();
    {
        const int n = tid >> 3, sub = tid & 7;
        const uint32_t me = deg[n];
        int r = 0;
#pragma unroll
        for (int k = 0; k < 10; k++) r += deg[sub * 10 + k] > me;
        r += __shfl_xor_sync(0xffffffff, r, 1); r += __shfl_xor_sync(0xffffffff, r, 2); r += __shfl_xor_sync(0xffffffff, r, 4);
        if (sub == 0) order[r] = n;
    }
    __syncthreads();
    int S = 0;
#pragma unroll
    for (int p = 0; p < 2; p++) {
        const int l = 2 * w + p, na = order[l], nb = order[79 - l];
        const uint32_t ca = hist[na * 32 + lane], cb = hist[nb * 32 + lane];
        uint32_t inc = ca + cb;
#pragma unroll
        for (int o = 1; o < 32; o <<= 1) { uint32_t u = __shfl_up_sync(0xffffffff, inc, o); if (lane >= o) inc += u; }
        const uint32_t ex = inc - ca - cb;
        hist[na * 32 + lane] = (ex << 8) | (w << 2) | (p << 1);
        hist[nb * 32 + lane] = ((ex + ca) << 8) | (w << 2) | (p << 1) | 1;
        S = max(S, (int)(__shfl_sync(0xffffffff, inc, 31) + 3) >> 2);
    }
    if (S > CAP && lane == 0) *flag = 1;
    S = max(S, DS);
    __syncthreads();
    if (*flag) {
        asm volatile("cp.async.wait_all;" ::: "memory");
        slow_path(smem, n0, nn, (const uint16_t*)x, (const int*)src4, (const int*)dst4, (const uint16_t*)Y, (const uint16_t*)ef, w_rad, cg,
                  (const uint16_t*)w_mix, (__nv_bfloat16*)out);
        return;
    }
#pragma unroll
    for (int u = 0; u < 12; u++) {
        if (key[u] < KEY_OVF) {
            const uint32_t h = hist[key[u] >> 14];
            const uint32_t pos = (h >> 8) + rk[u], ww = (h >> 2) & 63, sl = pos * 2 + ((h >> 1) & 1);
            *(uint4*)(smem + SM_REC + ww * (CAP * 128) + sl * 16) = make_uint4(rY[u].x, rE[u].x, rY[u].y, rE[u].y);
            *(uint32_t*)(smem + SM_SRC + ww * (WSTEPS * 32) + sl * 4) = ((key[u] & 0x3FFF) << 9) | (h & 1);
        }
    }
    __syncthreads();
    TSTAMP(4);
    uint32_t bits0 = 0;
    {
        uint32_t* sp = (uint32_t*)(smem + SM_SRC + w * (WSTEPS * 32));
#pragma unroll
        for (int k = 0; k < (CAP + 3) / 4; k++) {
            uint32_t v = (k * 32 + lane < CAP * 8) ? sp[k * 32 + lane] : 0;
            uint32_t m = (__ballot_sync(0xffffffff, v & 1) >> g) & 0x01010101u;
            bits0 |= ((m * 0x10204080u) >> 28) << (4 * k);
            if (v & 1) sp[k * 32 + lane] = v ^ 1;
        }
        __syncwarp();
        if (lane < DS * 8) sp[S * 8 + lane] = sp[lane] + F_WRAP;
        if (t < 2) bits0 = ~bits0;
        __syncwarp();
    }

    const int q = lane >> 3, c = lane & 7;
    const uint32_t ring0 = sb + SM_RING + w * (DS * 2048);
    const uint32_t wdst = ring0 + q * 128 + ((c + 2 * q) & 7) * 16;
    const uint32_t rsrc = ring0 + t * 128 + ((g + 2 * t) & 7) * 16;
    const uint32_t recl = sb + SM_REC + w * (CAP * 128) + g * 16 + (t & 1) * 8;
    const uint32_t srcl = sb + SM_SRC + w * (WSTEPS * 32) + q * 8;
    const uint16_t* pbase = (const uint16_t*)(x + c * 16);
    uint32_t pmask = F_PAD;
    auto cpa2 = [&](uint32_t dstp, uint32_t sv) {
        asm volatile("{.reg .pred p; .reg .b32 m; and.b32 m, %2, %3; setp.ne.u32 p, m, 0;\n"
                     "cp.async.cg.shared.global [%0], [%1], 16, p; cp.async.cg.shared.global [%0+1024], [%1+128], 16, p;}"
                     :: "r"(dstp), "l"(pbase + sv), "r"(sv), "r"(pmask) : "memory");
    };
#pragma unroll
    for (int i = 0; i < DS; i++) {
        uint2 s0 = lds64(srcl + i * 32);
        cpa2(wdst + i * 2048, s0.x); cpa2(wdst + i * 2048 + 512, s0.y);
        asm volatile("cp.async.commit_group;" ::: "memory");
    }
    uint4* stash = g_stash + (b * NW + w) * (6 * 32) + lane;
    uint32_t off = 0;
    uint4 pk0, pk1;
    for (int ph = 0; ph < 4; ph++) {
        if (ph == 3) pmask = F_PAD | F_WRAP;
        const uint4 az = *(const uint4*)(smem + SM_AZ + ph * 512 + lane * 16);
        float acc[4][4];
#pragma unroll
        for (int i = 0; i < 16; i++) acc[i / 4][i % 4] = 0.f;
        uint32_t bits = bits0;
#pragma unroll 1
        for (int st = 0; st < S; st++) {
            const uint2 r = lds64(recl + st * 128);
            const uint2 s0 = lds64(srcl + (st + DS) * 32);
            asm volatile("cp.async.wait_group %0;" :: "n"(DS - 1) : "memory");
            __syncwarp();
            const uint4 xa = lds128(rsrc + off), xb = lds128(rsrc + off + 512), xc = lds128(rsrc + off + 1024), xd = lds128(rsrc + off + 1536);
            __syncwarp();
            cpa2(wdst + off, s0.x); cpa2(wdst + off + 512, s0.y);
            asm volatile("cp.async.commit_group;" ::: "memory");
            float z[4], y[4], t1[4], t2[4];
            mma1688z(z, az.x, az.y, r.y);
            mma1688z(y, az.z, az.w, r.y);
            const uint32_t bt = (bits & 1) ? r.x : 0;
            mma1688z(t1, at[0], at[1], bt);
            mma1688z(t2, at[2], at[3], bt);
            const uint32_t ta0 = pack2(t1[0], t1[2]), ta1 = pack2(t2[0], t2[2]), tb0 = pack2(t1[1], t1[3]), tb1 = pack2(t2[1], t2[3]);
            const uint32_t ra = pack2(silu_h(z[0]), silu_h(z[2])), rb = pack2(silu_h(z[1]), silu_h(z[3]));
            mma16816(acc[0], mul_lo(xa.x, ra), mul_hi(xa.z, ra), mul_lo(xa.y, ra), mul_hi(xa.w, ra), ta0, ta1);
            mma16816(acc[1], mul_lo(xb.x, rb), mul_hi(xb.z, rb), mul_lo(xb.y, rb), mul_hi(xb.w, rb), tb0, tb1);
            const uint32_t rc = pack2(silu_h(y[0]), silu_h(y[2])), rd = pack2(silu_h(y[1]), silu_h(y[3]));
            mma16816(acc[2], mul_lo(xc.x, rc), mul_hi(xc.z, rc), mul_lo(xc.y, rc), mul_hi(xc.w, rc), ta0, ta1);
            mma16816(acc[3], mul_lo(xd.x, rd), mul_hi(xd.z, rd), mul_lo(xd.y, rd), mul_hi(xd.w, rd), tb0, tb1);
            bits >>= 1;
            off += 2048; if (off == DS * 2048) off = 0;
        }
        pk0.x = pack2(acc[0][0], acc[0][1]); pk0.y = pack2(acc[0][2], acc[0][3]); pk0.z = pack2(acc[2][0], acc[2][1]); pk0.w = pack2(acc[2][2], acc[2][3]);
        pk1.x = pack2(acc[1][0], acc[1][1]); pk1.y = pack2(acc[1][2], acc[1][3]); pk1.z = pack2(acc[3][0], acc[3][1]); pk1.w = pack2(acc[3][2], acc[3][3]);
        if (ph < 3) {
            stash[ph * 64] = pk0; stash[ph * 64 + 32] = pk1;
            pbase += 128;
            asm volatile("fence.proxy.async.shared::cta;" ::: "memory");
            asm volatile("bar.sync 1, %0;" :: "n"(NT) : "memory");
        }
    }
    TSTAMP(5);

    {
        uint4 sv[6];
#pragma unroll
        for (int i = 0; i < 6; i++) sv[i] = __ldcg(stash + i * 32);
        asm volatile("cp.async.wait_all;" ::: "memory");
        __syncwarp();
        uint32_t* bp = (uint32_t*)(smem + SM_RING + w * (DS * 2048)) + lane;
#pragma unroll
        for (int ph = 0; ph < 4; ph++) {
            const uint4 a = ph < 3 ? sv[2 * ph] : pk0, bb = ph < 3 ? sv[2 * ph + 1] : pk1;
            bp[(ph * 4 + 0) * 32] = a.x; bp[(ph * 4 + 1) * 32] = a.y; bp[(ph * 4 + 2) * 32] = a.z; bp[(ph * 4 + 3) * 32] = a.w;
            bp[768 + (ph * 4 + 0) * 32] = bb.x; bp[768 + (ph * 4 + 1) * 32] = bb.y; bp[768 + (ph * 4 + 2) * 32] = bb.z; bp[768 + (ph * 4 + 3) * 32] = bb.w;
        }
        asm volatile("fence.proxy.async.shared::cta;" ::: "memory");
        const int wg = w >> 2, w4 = w & 3;
        asm volatile("bar.sync %0, 128;" :: "r"(2 + wg) : "memory");
        const uint64_t descA0 = (uint64_t)(((sb + SM_WMIX) & 0x3FFFF) >> 4) | ((uint64_t)(2048 >> 4) << 16) | ((uint64_t)(128 >> 4) << 32);
        const uint64_t descB0 = (uint64_t)(((sb + SM_RING + wg * 4 * DS * 2048) & 0x3FFFF) >> 4) | ((uint64_t)(128 >> 4) << 16) | ((uint64_t)(3072 >> 4) << 32);
        float d[2][32];
        asm volatile("wgmma.fence.sync.aligned;" ::: "memory");
#pragma unroll
        for (int mt = 0; mt < 2; mt++) {
#pragma unroll
            for (int ks = 0; ks < 8; ks++) {
                const uint64_t da = descA0 + (uint64_t)((ks * 4096 + mt * 1024) >> 4), db = descB0 + (uint64_t)((ks * 256) >> 4);
                asm volatile("{.reg .pred p; setp.ne.b32 p, %34, 0;\n"
                    "wgmma.mma_async.sync.aligned.m64n64k16.f32.bf16.bf16 "
                    "{%0,%1,%2,%3,%4,%5,%6,%7,%8,%9,%10,%11,%12,%13,%14,%15,%16,%17,%18,%19,%20,%21,%22,%23,%24,%25,%26,%27,%28,%29,%30,%31}, %32, %33, p, 1, 1, 1, 1;}"
                    : "+f"(d[mt][0]), "+f"(d[mt][1]), "+f"(d[mt][2]), "+f"(d[mt][3]), "+f"(d[mt][4]), "+f"(d[mt][5]), "+f"(d[mt][6]), "+f"(d[mt][7]),
                      "+f"(d[mt][8]), "+f"(d[mt][9]), "+f"(d[mt][10]), "+f"(d[mt][11]), "+f"(d[mt][12]), "+f"(d[mt][13]), "+f"(d[mt][14]), "+f"(d[mt][15]),
                      "+f"(d[mt][16]), "+f"(d[mt][17]), "+f"(d[mt][18]), "+f"(d[mt][19]), "+f"(d[mt][20]), "+f"(d[mt][21]), "+f"(d[mt][22]), "+f"(d[mt][23]),
                      "+f"(d[mt][24]), "+f"(d[mt][25]), "+f"(d[mt][26]), "+f"(d[mt][27]), "+f"(d[mt][28]), "+f"(d[mt][29]), "+f"(d[mt][30]), "+f"(d[mt][31])
                    : "l"(da), "l"(db), "r"(ks));
            }
            asm volatile("wgmma.commit_group.sync.aligned;" ::: "memory");
        }
        int nd[8];
#pragma unroll
        for (int j = 0; j < 8; j++) { const int l = wg * 8 + j; nd[j] = order[(t >> 1) ? 79 - l : l]; }
        uint32_t* ob = out + (size_t)n0 * 256 + (w4 * 16 + g) * 2 + (t & 1);
#pragma unroll
        for (int mt = 0; mt < 2; mt++) {
            if (mt == 0) asm volatile("wgmma.wait_group.sync.aligned 1;" ::: "memory");
            else asm volatile("wgmma.wait_group.sync.aligned 0;" ::: "memory");
#pragma unroll
            for (int i = 0; i < 32; i++) asm volatile("" : "+f"(d[mt][i]) :: "memory");
#pragma unroll
            for (int j = 0; j < 8; j++) {
                if (nd[j] < nn) {
                    ob[nd[j] * 256 + mt * 128] = pack2(d[mt][4 * j], d[mt][4 * j + 1]);
                    ob[nd[j] * 256 + mt * 128 + 16] = pack2(d[mt][4 * j + 2], d[mt][4 * j + 3]);
                }
            }
        }
    }
    TSTAMP(6);
}

}

extern "C" void kernel_launch(void* const* d_in, const int* in_sizes, int n_in, void* d_out, int out_size) {
    (void)in_sizes; (void)n_in; (void)out_size;
    cudaFuncSetAttribute(tfn_kernel, cudaFuncAttributeMaxDynamicSharedMemorySize, SM_TOTAL);
    cudaLaunchConfig_t cfg = {};
    cfg.gridDim = dim3(NB); cfg.blockDim = dim3(NT); cfg.dynamicSmemBytes = SM_TOTAL; cfg.stream = cudaStreamPerThread;
    cudaLaunchAttribute at[1];
    at[0].id = cudaLaunchAttributeCooperative; at[0].val.cooperative = 1;
    cfg.attrs = at; cfg.numAttrs = 1;
    cudaLaunchKernelEx(&cfg, tfn_kernel, (const unsigned char*)d_in[0], (const int4*)d_in[1], (const int4*)d_in[2],
                       (const uint2*)d_in[3], (const uint2*)d_in[4], (const uint16_t*)d_in[5], (const uint16_t*)d_in[6],
                       (const uint4*)d_in[7], (uint32_t*)d_out);
}
```

```cpp
#include <cuda_runtime.h>
#include <cuda_bf16.h>
#include <stdint.h>

namespace {

constexpr int NN = 10000;
constexpr int NE = 320000;
constexpr int NB = 132;
constexpr int NW = 20;
constexpr int NT = NW * 32;
constexpr int CW = NW - 1;
constexpr int NPB = 76;
constexpr int CELL = 48;
constexpr int CAP = 19;
constexpr int DS = 3;
constexpr int STEPB = 160;
constexpr int NE4 = NE / 4;
constexpr int NPIECE = NB * CELL / 4;
constexpr uint32_t KEY_NONE = 0xFFFFFFFFu;
constexpr uint32_t F_PAD = 256, F_WRAP = 128;

constexpr int SLOTB = NW * 2048;
constexpr int SM_RING = 0;
constexpr int SM_WMIX = SM_RING + DS * SLOTB;
constexpr int SM_META = SM_WMIX + 32768;
constexpr int SM_AZ = SM_META + NW * CAP * STEPB;
constexpr int SM_MISC = SM_AZ + 2048;
constexpr int SM_TOTAL = SM_MISC + 2048;
constexpr int SM_KEYS = SM_RING;
constexpr int SM_HIST = SM_RING + 25600;
constexpr int SM_RECS = SM_RING + SLOTB;
constexpr int SM_RAWY = SM_META;
constexpr int SM_RAWE = SM_RAWY + 608 * 32;
constexpr int SM_ELOC = SM_RAWE + 608 * 32;
static_assert(SM_TOTAL <= 232448 && SM_ELOC + NB * CELL * 2 <= SM_AZ, "smem");
static_assert(SM_RECS + NB * CELL * 16 <= SM_META && SM_HIST + 10240 <= SM_RECS && SM_WMIX % 1024 == 0, "smem");

struct Scratch {
    uint4 keys[NB * NPIECE];
    uint4 recs[NB * NB * CELL];
    uint4 stash[NB * NW * 6 * 32];
    unsigned bar[64];
};
__device__ Scratch g_scratch;
#define TSTAMP(i)
#define TSTAMPC(i)

__device__ __forceinline__ void mma16816(float* d, uint32_t a0, uint32_t a1, uint32_t a2, uint32_t a3, uint32_t b0, uint32_t b1) {
    asm("mma.sync.aligned.m16n8k16.row.col.f32.bf16.bf16.f32 {%0,%1,%2,%3}, {%4,%5,%6,%7}, {%8,%9}, {%0,%1,%2,%3};"
        : "+f"(d[0]), "+f"(d[1]), "+f"(d[2]), "+f"(d[3]) : "r"(a0), "r"(a1), "r"(a2), "r"(a3), "r"(b0), "r"(b1));
}
__device__ __forceinline__ void mma1688z(float* d, uint32_t a0, uint32_t a1, uint32_t b0) {
    asm("mma.sync.aligned.m16n8k8.row.col.f32.bf16.bf16.f32 {%0,%1,%2,%3}, {%4,%5}, {%6}, {%7,%7,%7,%7};"
        : "=f"(d[0]), "=f"(d[1]), "=f"(d[2]), "=f"(d[3]) : "r"(a0), "r"(a1), "r"(b0), "f"(0.f));
}
__device__ __forceinline__ uint32_t pack2(float lo, float hi) {
    uint32_t r; asm("cvt.rn.bf16x2.f32 %0, %1, %2;" : "=r"(r) : "f"(hi), "f"(lo)); return r;
}
__device__ __forceinline__ float silu_h(float h) {
    float t; asm("tanh.approx.f32 %0, %1;" : "=f"(t) : "f"(h)); return fmaf(h, t, h);
}
__device__ __forceinline__ uint32_t mul_lo(uint32_t v, uint32_t r) {
    __nv_bfloat162 a = *(__nv_bfloat162*)&v, b = *(__nv_bfloat162*)&r; __nv_bfloat162 c = __hmul2(a, __low2bfloat162(b)); return *(uint32_t*)&c;
}
__device__ __forceinline__ uint32_t mul_hi(uint32_t v, uint32_t r) {
    __nv_bfloat162 a = *(__nv_bfloat162*)&v, b = *(__nv_bfloat162*)&r; __nv_bfloat162 c = __hmul2(a, __high2bfloat162(b)); return *(uint32_t*)&c;
}
__device__ __forceinline__ uint2 lds64(uint32_t a) {
    uint2 r; asm volatile("ld.shared.v2.u32 {%0,%1}, [%2];" : "=r"(r.x), "=r"(r.y) : "r"(a)); return r;
}
__device__ __forceinline__ uint4 lds128(uint32_t a) {
    uint4 r; asm volatile("ld.shared.v4.u32 {%0,%1,%2,%3}, [%4];" : "=r"(r.x), "=r"(r.y), "=r"(r.z), "=r"(r.w) : "r"(a) : "memory"); return r;
}
__device__ __forceinline__ void bar_sync(int id, int n) { asm volatile("bar.sync %0, %1;" :: "r"(id), "r"(n) : "memory"); }
__device__ __forceinline__ void bar_arrive(int id, int n) { asm volatile("bar.arrive %0, %1;" :: "r"(id), "r"(n) : "memory"); }
__device__ __forceinline__ void mbar_wait(uint32_t bar, uint32_t ph) {
    uint32_t done; int spins = 0;
    do {
        asm volatile("{.reg .pred p; mbarrier.try_wait.parity.shared.b64 p, [%1], %2; selp.u32 %0,1,0,p;}" : "=r"(done) : "r"(bar), "r"(ph) : "memory");
    } while (!done && ++spins < (1 << 22));
}
__device__ __forceinline__ unsigned gbar_read(const unsigned* ctr) {
    unsigned v; asm volatile("ld.relaxed.gpu.global.u32 %0, [%1];" : "=r"(v) : "l"(ctr) : "memory");
    return v;
}
__device__ __forceinline__ void gbar_arrive(unsigned* ctr) {
    asm volatile("red.add.release.gpu.global.u32 [%0], 1;" :: "l"(ctr) : "memory");
}
__device__ __forceinline__ void gbar_wait(const unsigned* ctr, unsigned target) {
    unsigned v; int spins = 0;
    do { asm volatile("ld.acquire.gpu.global.u32 %0, [%1];" : "=r"(v) : "l"(ctr) : "memory"); } while ((int)(v - target) < 0 && ++spins < (1 << 22));
}
__device__ __forceinline__ int bin_start(int b) { return (b * NN + NB - 1) / NB; }
__device__ __forceinline__ int chunk_start4(int c) { return (c * NE4) / NB; }
__device__ __forceinline__ float bf2f(uint32_t h) { return __uint_as_float(h << 16); }

__device__ __noinline__ void slow_path(unsigned char* smem, int n0, int nn, const uint16_t* x, const int* src, const int* dst,
                                       const uint16_t* Y, const uint16_t* ef, const uint16_t* w_rad, const uint16_t* cg,
                                       const uint16_t* w_mix, __nv_bfloat16* out) {
    float* agg = (float*)smem;
    const int tid = threadIdx.x, lane = tid & 31, w = tid >> 5;
    bar_sync(1, NT);
    for (int i = tid; i < NPB * 512; i += NT) agg[i] = 0.f;
    bar_sync(1, NT);
    for (int e0 = w * 32; e0 < NE; e0 += NT) {
        int dl = dst[e0 + lane] - n0;
        unsigned m = __ballot_sync(0xffffffff, dl >= 0 && dl < nn);
        while (m) {
            int l = __ffs(m) - 1; m &= m - 1;
            int e = e0 + l, d = __shfl_sync(0xffffffff, dl, l), s = src[e];
            float T[16];
            for (int i = 0; i < 4; i++) for (int o = 0; o < 4; o++) {
                float a = 0.f;
                for (int f = 0; f < 4; f++) a += bf2f(Y[e * 4 + f]) * bf2f(cg[i * 16 + f * 4 + o]);
                T[i * 4 + o] = a;
            }
            for (int k = 0; k < 4; k++) {
                int c = lane + 32 * k;
                float z = 0.f;
                for (int j = 0; j < 4; j++) z += bf2f(ef[e * 4 + j]) * bf2f(w_rad[j * 128 + c]);
                float R = z / (1.f + __expf(-z));
                for (int o = 0; o < 4; o++) {
                    float a = 0.f;
                    for (int i = 0; i < 4; i++) a += bf2f(x[(size_t)s * 512 + c * 4 + i]) * T[i * 4 + o];
                    atomicAdd(&agg[d * 512 + c * 4 + o], R * a);
                }
            }
        }
    }
    bar_sync(1, NT);
    for (int i = tid; i < nn * 512; i += NT) {
        int n = i >> 9, d = (i >> 2) & 127, o = i & 3;
        float a = 0.f;
        for (int c = 0; c < 128; c++) a += agg[n * 512 + c * 4 + o] * bf2f(w_mix[c * 128 + d]);
        out[(size_t)(n0 + n) * 512 + (i & 511)] = __float2bfloat16(a);
    }
}

#define PFPOS 3
#define XPREFETCH if (lane == 0 && w < 4 && w * 19 < nn) \
    asm volatile("cp.async.bulk.prefetch.L2.global [%0], %1;" :: "l"(x + (size_t)(n0 + w * 19) * 1024), "r"(min(19, nn - w * 19) * 1024));
__global__ void __launch_bounds__(NT, 1)
tfn_kernel(const unsigned char* __restrict__ x, const int4* __restrict__ src4, const int4* __restrict__ dst4,
           const uint4* __restrict__ Y, const uint4* __restrict__ ef, const uint16_t* __restrict__ w_rad,
           const uint16_t* __restrict__ cg, const uint4* __restrict__ w_mix, uint32_t* __restrict__ out, Scratch* __restrict__ gs) {
    extern __shared__ __align__(1024) unsigned char smem[];
    const uint32_t sb = (uint32_t)__cvta_generic_to_shared(smem);
    const int b = blockIdx.x, tid = threadIdx.x, lane = tid & 31, g = lane >> 2, t = lane & 3;
    const int w = __shfl_sync(0xffffffff, tid >> 5, 0);
    uint32_t* keys = (uint32_t*)(smem + SM_KEYS);
    uint32_t* hist = (uint32_t*)(smem + SM_HIST);
    uint32_t* cnt = (uint32_t*)(smem + SM_MISC);
    uint32_t* deg = cnt + 160;
    uint32_t* order = deg + 80;
    uint32_t* cnt2 = order + 80;
    volatile uint32_t* flag = cnt2 + 132;
    const uint32_t mbarK = sb + SM_MISC + 1920, mbarR = mbarK + 8;
    const int n0 = bin_start(b), nn = bin_start(b + 1) - n0;
    TSTAMP(0);

    const int c0 = chunk_start4(b), c1 = chunk_start4(b + 1);
    const bool has4 = c0 + tid < c1;
    int4 d4 = make_int4(0, 0, 0, 0), s4 = d4;
    if (has4) { d4 = __ldg(dst4 + c0 + tid); s4 = __ldg(src4 + c0 + tid); }
    unsigned tgt = 0;
    if (tid == NT - 1) tgt = gbar_read(&gs->bar[0]);
    if (tid == 32) {
        asm volatile("mbarrier.init.shared.b64 [%0], 1;" :: "r"(mbarK));
        asm volatile("mbarrier.init.shared.b64 [%0], 1;" :: "r"(mbarR));
        asm volatile("fence.mbarrier_init.release.cluster;" ::: "memory");
        asm volatile("mbarrier.arrive.expect_tx.shared.b64 _, [%0], %1;" :: "r"(mbarR), "r"((c1 - c0) * 64) : "memory");
        asm volatile("cp.async.bulk.shared::cluster.global.mbarrier::complete_tx::bytes [%0], [%1], %2, [%3];"
                     :: "r"(sb + SM_RAWY), "l"(Y + 2 * c0), "r"((c1 - c0) * 32), "r"(mbarR) : "memory");
        asm volatile("cp.async.bulk.shared::cluster.global.mbarrier::complete_tx::bytes [%0], [%1], %2, [%3];"
                     :: "r"(sb + SM_RAWE), "l"(ef + 2 * c0), "r"((c1 - c0) * 32), "r"(mbarR) : "memory");
        *flag = 0;
    }
    uint32_t wr0 = 0, wr1 = 0, cgv[1];
    if (w < 8 && t < 2) { wr0 = *(const uint32_t*)(w_rad + (2 * t) * 128 + 16 * w + 2 * g); wr1 = *(const uint32_t*)(w_rad + (2 * t + 1) * 128 + 16 * w + 2 * g); }
    cgv[0] = ((const uint32_t*)cg)[lane];
#pragma unroll
    for (int j = 0; j < 3; j++) if (tid + j * NT < NPIECE) ((uint4*)keys)[tid + j * NT] = make_uint4(KEY_NONE, KEY_NONE, KEY_NONE, KEY_NONE);
    ((uint4*)hist)[tid] = make_uint4(0, 0, 0, 0);
    if (tid < 160) cnt[tid] = 0;
    if (tid < 4) { deg[NPB + tid] = 127 - (NPB + tid); order[NPB + tid] = NPB + tid; }
    __syncthreads();
    TSTAMP(9);

    const uint32_t rot = ((b >> 1) & 3) * 4;
    if (has4) {
        const int dd[4] = {d4.x, d4.y, d4.z, d4.w}, ss[4] = {s4.x, s4.y, s4.z, s4.w};
        uint32_t bin[4], slot[4];
#pragma unroll
        for (int k = 0; k < 4; k++) { bin[k] = (uint32_t)(dd[k] * NB) / NN; slot[k] = min(atomicAdd(&cnt[bin[k]], 1), CELL - 1); }
#pragma unroll
        for (int k = 0; k < 4; k++) {
            const uint32_t key = (uint32_t)ss[k] | ((((dd[k] - bin_start(bin[k])) << 5) + ((ss[k] * 209) >> 16)) << 14);
            uint32_t sr = slot[k] + rot; if (sr >= CELL) sr -= CELL;
            keys[bin[k] * CELL + sr] = key;
            ((uint16_t*)(smem + SM_ELOC))[bin[k] * CELL + slot[k]] = tid * 4 + k;
        }
    }
    bar_sync(1, NT);
    TSTAMP(1);
    {
        const int hp = (11 + (rot >> 2)) % 12;
#pragma unroll
        for (int j = 0; j < 3; j++) {
            const int i = tid + j * NT;
            if (i < NPIECE) {
                const int bn = i / 12, r = i - bn * 12;
                uint4 v = ((uint4*)keys)[i];
                if (r == hp) v.w = 0xFF000000u | cnt[bn];
                gs->keys[(bn * NB + b) * 12 + r] = v;
            }
        }
    }
    uint32_t at[4];
    if (w == CW) {
        bar_sync(7, NT);
        if (tid == NT - 1) {
            TSTAMPC(10);
            gbar_arrive(&gs->bar[0]);
            TSTAMPC(11);
            tgt = (tgt / NB + 1) * NB;
            asm volatile("fence.proxy.async.shared::cta;" ::: "memory");
            asm volatile("mbarrier.arrive.expect_tx.shared.b64 _, [%0], %1;" :: "r"(mbarK), "r"(NPIECE * 16) : "memory");
            gbar_wait(&gs->bar[0], tgt);
            TSTAMPC(13);
            asm volatile("fence.proxy.async.global;" ::: "memory");
            asm volatile("cp.async.bulk.shared::cluster.global.mbarrier::complete_tx::bytes [%0], [%1], %2, [%3];"
                         :: "r"(sb + SM_KEYS), "l"(gs->keys + b * NPIECE), "r"(NPIECE * 16), "r"(mbarK) : "memory");
        }
    } else {
        bar_arrive(7, NT);
        if (w < 8) {
            *(uint2*)(smem + SM_AZ + (w >> 1) * 512 + lane * 16 + (w & 1) * 8) =
                make_uint2(pack2(0.5f * bf2f(wr0 & 0xFFFF), 0.5f * bf2f(wr1 & 0xFFFF)), pack2(0.5f * bf2f(wr0 >> 16), 0.5f * bf2f(wr1 >> 16)));
        }
        uint32_t el[7], cn[7];
#pragma unroll
        for (int j = 0; j < 7; j++) {
            const int cell = min(w + CW * j, NB - 1);
            cn[j] = cnt[cell];
            el[j] = ((const uint16_t*)(smem + SM_ELOC))[cell * CELL + min(lane, max((int)cn[j], 1) - 1)];
        }
        mbar_wait(mbarR, 0);
        TSTAMP(18);
#pragma unroll
        for (int j = 0; j < 7; j++) {
            const int cell = w + CW * j;
            if (cell < NB && lane < ((cn[j] + 1) & ~1u)) {
                const uint2 yy = *(const uint2*)(smem + SM_RAWY + el[j] * 8), ee = *(const uint2*)(smem + SM_RAWE + el[j] * 8);
                gs->recs[(cell * NB + b) * CELL + lane] = make_uint4(yy.x, ee.x, yy.y, ee.y);
            }
            if (cn[j] > 32 && cell < NB && lane + 32 < min(cn[j], CELL - 1)) {
                const uint32_t e2 = ((const uint16_t*)(smem + SM_ELOC))[cell * CELL + 32 + lane];
                const uint2 yy = *(const uint2*)(smem + SM_RAWY + e2 * 8), ee = *(const uint2*)(smem + SM_RAWE + e2 * 8);
                gs->recs[(cell * NB + b) * CELL + 32 + lane] = make_uint4(yy.x, ee.x, yy.y, ee.y);
            }
        }
        if (w == CW - 1) {
            bar_sync(8, NT - 32);
            if (lane == 0) { TSTAMPC(14); gbar_arrive(&gs->bar[32]); TSTAMPC(15); }
        } else bar_arrive(8, NT - 32);
    }
    __syncwarp();
    TSTAMP(2);
    {
        const int o = g & 3, f = 2 * (t & 1);
#pragma unroll
        for (int i = 0; i < 4; i++) {
            const uint32_t lo = __shfl_sync(0xffffffff, cgv[0], i * 8 + f * 2 + (o >> 1)), hi = __shfl_sync(0xffffffff, cgv[0], i * 8 + f * 2 + 2 + (o >> 1));
            at[i] = (t >> 1) == (g >> 2) ? __byte_perm(lo, hi, (o & 1) ? 0x7632 : 0x5410) : 0;
        }
    }

    uint32_t key[3][4], kidx[3];
    {
        uint32_t ka[3];
#pragma unroll
        for (int j = 0; j < 3; j++) {
            const int i = min(tid + j * NT, NPIECE - 1), r = i / NB, c = i - r * NB;
            int pr = r + ((c >> 1) & 3); if (pr >= 12) pr -= 12;
            ka[j] = sb + SM_KEYS + (c * 12 + pr) * 16;
            kidx[j] = c * CELL + r * 4;
        }
        mbar_wait(mbarK, 0);
        TSTAMP(3);
#pragma unroll
        for (int j = 0; j < 3; j++) {
            const uint4 v = lds128(ka[j]);
            key[j][0] = (tid + j * NT < NPIECE) ? v.x : KEY_NONE; key[j][1] = v.y; key[j][2] = v.z; key[j][3] = v.w;
        }
        if (tid < NB) {
            const uint32_t hc = keys[tid * CELL + (47 + ((tid >> 1) & 3) * 4) % CELL] & 0xFFFFFF;
            if (hc > CELL - 1) *flag = 1;
            cnt2[tid] = hc;
        }
#pragma unroll
        for (int j = 0; j < 3; j++) {
            if (key[j][0] != KEY_NONE) {
                uint32_t rk[4];
#pragma unroll
                for (int u = 0; u < 4; u++) rk[u] = key[j][u] < 0xFC000000u ? atomicAdd(&hist[key[j][u] >> 14], 1) : 0;
                if (max(max(rk[0], rk[1]), max(rk[2], rk[3])) > 62) *flag = 1;
#pragma unroll
                for (int u = 0; u < 4; u++) key[j][u] |= rk[u] << 26;
            }
        }
    }
    bar_sync(1, NT);
    TSTAMP(20);
    if (w == CW) {
        if (tid == NT - 1) { TSTAMPC(16); gbar_wait(&gs->bar[32], tgt); TSTAMPC(17); }
        __syncwarp();
    } else {
#pragma unroll
        for (int k = 0; k < 4; k++) {
            uint32_t dsum = __reduce_add_sync(0xffffffff, hist[(w * 4 + k) * 32 + lane]);
            if (lane == 0) deg[w * 4 + k] = dsum * 128 + (127 - (w * 4 + k));
        }
        bar_sync(9, NT - 32);
        const int n = tid >> 3, sub = tid & 7;
        const uint32_t me = deg[n];
        int r = 0;
#pragma unroll
        for (int k = 0; k < 10; k++) r += deg[sub * 10 + k] > me;
        r += __shfl_xor_sync(0xffffffff, r, 1); r += __shfl_xor_sync(0xffffffff, r, 2); r += __shfl_xor_sync(0xffffffff, r, 4);
        if (sub == 0) order[r] = n;
    }
    bar_sync(1, NT);
    TSTAMP(22);
    {
        uint32_t cn[7];
#pragma unroll
        for (int j = 0; j < 7; j++) cn[j] = w + NW * j < NB ? cnt2[w + NW * j] : 0;
        const uint4* gp = gs->recs + (b * NB + w) * CELL + lane;
        const uint32_t sp = sb + SM_RECS + (w * CELL + lane) * 16;
#pragma unroll
        for (int j = 0; j < 7; j++)
            if (lane < cn[j]) asm volatile("cp.async.cg.shared.global [%0], [%1], 16;" :: "r"(sp + j * (NW * CELL * 16)), "l"(gp + j * (NW * CELL)) : "memory");
#pragma unroll
        for (int j = 0; j < 7; j++)
            if (cn[j] > 32 && lane + 32 < min(cn[j], CELL - 1))
                asm volatile("cp.async.cg.shared.global [%0], [%1], 16;" :: "r"(sp + j * (NW * CELL * 16) + 512), "l"(gp + j * (NW * CELL) + 32) : "memory");
        asm volatile("cp.async.commit_group;" ::: "memory");
    }
    int S = 0, mylen = 0;
#pragma unroll
    for (int p = 0; p < 2; p++) {
        const int l = 2 * w + p, na = order[l], nb = order[79 - l];
        const uint32_t ca = hist[na * 32 + lane], cb = hist[nb * 32 + lane];
        uint32_t inc = ca + cb;
#pragma unroll
        for (int o = 1; o < 32; o <<= 1) { uint32_t u = __shfl_up_sync(0xffffffff, inc, o); if (lane >= o) inc += u; }
        const uint32_t base = w * (CAP * STEPB / 4) + p + 2 * (inc - ca - cb);
        hist[na * 32 + lane] = base;
        hist[nb * 32 + lane] = (base + 2 * ca) | 0x4000;
        const int len = __shfl_sync(0xffffffff, inc, 31);
        S = max(S, (len + 3) >> 2);
        if ((lane & 1) == p) mylen = len;
    }
    if (S > CAP) *flag = 1;
    S = max(S, DS);
    bar_sync(1, NT);
    TSTAMP(21);
    if (*flag) {
        asm volatile("cp.async.wait_all;" ::: "memory");
        slow_path(smem, n0, nn, (const uint16_t*)x, (const int*)src4, (const int*)dst4, (const uint16_t*)Y, (const uint16_t*)ef, w_rad, cg,
                  (const uint16_t*)w_mix, (__nv_bfloat16*)out);
        return;
    }
#pragma unroll
    for (int j = 0; j < 3; j++) {
        if (key[j][0] != KEY_NONE) {
            uint32_t h[4];
#pragma unroll
            for (int u = 0; u < 4; u++) h[u] = hist[min((key[j][u] >> 14) & 0xFFF, 2559u)];
#pragma unroll
            for (int u = 0; u < 4; u++) if (key[j][u] < 0xFC000000u)
                ((uint32_t*)(smem + SM_META))[(h[u] & 0x3FFF) + 2 * (key[j][u] >> 26)] = (key[j][u] & 0x3FFF) | (h[u] & 0x4000) | ((kidx[j] + u) << 15);
        }
    }
    asm volatile("cp.async.wait_all;" ::: "memory");
    bar_sync(1, NT);
    TSTAMP(4);
    constexpr int NRAW = (CAP + 3) / 4;
    uint32_t bits0 = 0, raw[NRAW], sv[NRAW];
    unsigned char* meta = smem + SM_META + w * (CAP * STEPB);
#pragma unroll
    for (int k = 0; k < NRAW; k++) {
        const int i = k * 32 + lane;
        raw[k] = (i >> 1) < mylen ? ((uint32_t*)meta)[i] : 0xFFFFFFFFu;
        sv[k] = raw[k] == 0xFFFFFFFFu ? F_PAD : (raw[k] & 0x3FFF) << 9;
    }
    const int q = lane >> 3, c = lane & 7;
    const uint32_t ring0 = sb + SM_RING + w * 2048;
    const uint32_t wdst = ring0 + q * 128 + ((c + 2 * q) & 7) * 16;
    const uint32_t rsrc = ring0 + t * 128 + ((g + 2 * t) & 7) * 16;
    const uint32_t recl = g * 16 + (t & 1) * 8, srcl = 128 + q * 8;
    const uint32_t m0 = sb + SM_META + w * (CAP * STEPB);
    const uint16_t* pbase = (const uint16_t*)(x + c * 16);
    uint32_t pmask = F_PAD;
    auto cpa2 = [&](uint32_t dstp, uint32_t sv) {
        asm volatile("{.reg .pred p; .reg .b32 m; and.b32 m, %2, %3; setp.ne.u32 p, m, 0;\n"
                     "cp.async.cg.shared.global [%0], [%1], 16, p; cp.async.cg.shared.global [%0+1024], [%1+128], 16, p;}"
                     :: "r"(dstp), "l"(pbase + sv), "r"(sv), "r"(pmask) : "memory");
    };
    cpa2(wdst, __shfl_sync(0xffffffff, sv[0], 2 * q)); cpa2(wdst + 512, __shfl_sync(0xffffffff, sv[0], 2 * q + 1));
    asm volatile("cp.async.commit_group;" ::: "memory");
    TSTAMP(5);
    __syncwarp();
#pragma unroll
    for (int k = 0; k < NRAW; k++) {
        const int st = k * 4 + q;
        uint4 v = make_uint4(0, 0, 0, 0);
        if (raw[k] != 0xFFFFFFFFu) v = ((const uint4*)(smem + SM_RECS))[raw[k] >> 15];
        if (st < S) {
            *(uint4*)(meta + st * STEPB + c * 16) = v;
            *(uint32_t*)(meta + (st < DS ? S - DS + st : st - DS) * STEPB + 128 + c * 4) = sv[k] + (st < DS ? F_WRAP : 0);
        }
        const uint32_t m = (__ballot_sync(0xffffffff, raw[k] & 0x4000) >> g) & 0x01010101u;
        bits0 |= ((m * 0x10204080u) >> 28) << (4 * k);
    }
    if (t < 2) bits0 = ~bits0;
    bar_sync(1, NT);
#pragma unroll
    for (int i = 1; i < DS; i++) {
        cpa2(wdst + i * SLOTB, __shfl_sync(0xffffffff, sv[0], 8 * i + 2 * q)); cpa2(wdst + i * SLOTB + 512, __shfl_sync(0xffffffff, sv[0], 8 * i + 2 * q + 1));
        if (i == DS - 1) {
#pragma unroll
            for (int j = 0; j < 4; j++) {
                const int u = tid + j * NT;
                if (u < 2048) {
                    const int cc = u >> 4, db = u & 15;
                    const int k = (cc & 0x70) | ((cc & 1) << 3) | ((cc & 15) >> 1);
                    const uint32_t dstp = sb + SM_WMIX + (db >> 3) * 16384 + k * 128 + (((db & 7) ^ (k & 7)) << 4);
                    asm volatile("cp.async.cg.shared.global [%0], [%1], 16;" :: "r"(dstp), "l"(w_mix + u) : "memory");
                }
            }
        }
        asm volatile("cp.async.commit_group;" ::: "memory");
    }
    TSTAMP(6);

    uint4* stash = gs->stash + (b * NW + w) * (6 * 32) + lane;
    uint32_t off = 0;
    uint4 pk0, pk1;
    for (int ph = 0; ph < 4; ph++) {
        if (ph == 3) pmask = F_PAD | F_WRAP;
        const uint4 az = *(const uint4*)(smem + SM_AZ + ph * 512 + lane * 16);
        float acc[4][4];
#pragma unroll
        for (int i = 0; i < 16; i++) acc[i / 4][i % 4] = 0.f;
        uint32_t bits = bits0;
#pragma unroll 1
        for (uint32_t mp = m0; mp != m0 + S * STEPB; mp += STEPB) {
            const uint2 r = lds64(mp + recl);
            const uint2 s0 = lds64(mp + srcl);
            asm volatile("cp.async.wait_group %0;" :: "n"(DS - 1) : "memory");
            __syncwarp();
            const uint4 xa = lds128(rsrc + off), xb = lds128(rsrc + off + 512), xc = lds128(rsrc + off + 1024), xd = lds128(rsrc + off + 1536);
            __syncwarp();
            cpa2(wdst + off, s0.x); cpa2(wdst + off + 512, s0.y);
            asm volatile("cp.async.commit_group;" ::: "memory");
            float z[4], y[4], t1[4], t2[4];
            mma1688z(z, az.x, az.y, r.y);
            mma1688z(y, az.z, az.w, r.y);
            const uint32_t bt = (bits & 1) ? r.x : 0;
            mma1688z(t1, at[0], at[1], bt);
            mma1688z(t2, at[2], at[3], bt);
            const uint32_t ta0 = pack2(t1[0], t1[2]), ta1 = pack2(t2[0], t2[2]), tb0 = pack2(t1[1], t1[3]), tb1 = pack2(t2[1], t2[3]);
            const uint32_t ra = pack2(silu_h(z[0]), silu_h(z[2])), rb = pack2(silu_h(z[1]), silu_h(z[3]));
            mma16816(acc[0], mul_lo(xa.x, ra), mul_hi(xa.z, ra), mul_lo(xa.y, ra), mul_hi(xa.w, ra), ta0, ta1);
            mma16816(acc[1], mul_lo(xb.x, rb), mul_hi(xb.z, rb), mul_lo(xb.y, rb), mul_hi(xb.w, rb), tb0, tb1);
            const uint32_t rc = pack2(silu_h(y[0]), silu_h(y[2])), rd = pack2(silu_h(y[1]), silu_h(y[3]));
            mma16816(acc[2], mul_lo(xc.x, rc), mul_hi(xc.z, rc), mul_lo(xc.y, rc), mul_hi(xc.w, rc), ta0, ta1);
            mma16816(acc[3], mul_lo(xd.x, rd), mul_hi(xd.z, rd), mul_lo(xd.y, rd), mul_hi(xd.w, rd), tb0, tb1);
            bits >>= 1;
            off += SLOTB; if (off == DS * SLOTB) off = 0;
        }
        pk0.x = pack2(acc[0][0], acc[0][1]); pk0.y = pack2(acc[0][2], acc[0][3]); pk0.z = pack2(acc[2][0], acc[2][1]); pk0.w = pack2(acc[2][2], acc[2][3]);
        pk1.x = pack2(acc[1][0], acc[1][1]); pk1.y = pack2(acc[1][2], acc[1][3]); pk1.z = pack2(acc[3][0], acc[3][1]); pk1.w = pack2(acc[3][2], acc[3][3]);
        if (ph < 3) {
            stash[ph * 64] = pk0; stash[ph * 64 + 32] = pk1;
            pbase += 128;
            asm volatile("fence.proxy.async.shared::cta;" ::: "memory");
            asm volatile("bar.sync 1, %0;" :: "n"(NT) : "memory");
        }
    }
    TSTAMP(7);

    {
        uint4 su[6];
#pragma unroll
        for (int i = 0; i < 6; i++) su[i] = __ldcg(stash + i * 32);
        asm volatile("cp.async.wait_all;" ::: "memory");
        __syncwarp();
#pragma unroll
        for (int ph = 0; ph < 4; ph++) {
            uint32_t* bp = (uint32_t*)(smem + SM_RING + (ph >> 1) * SLOTB + w * 2048 + (ph & 1) * 512) + lane;
            const uint4 a = ph < 3 ? su[2 * ph] : pk0, bb = ph < 3 ? su[2 * ph + 1] : pk1;
            bp[0] = a.x; bp[32] = a.y; bp[64] = a.z; bp[96] = a.w;
            bp[256] = bb.x; bp[288] = bb.y; bp[320] = bb.z; bp[352] = bb.w;
        }
        asm volatile("fence.proxy.async.shared::cta;" ::: "memory");
        const int wg = w >> 2, w4 = w & 3;
        bar_sync(2 + wg, 128);
        const uint64_t descA0 = (uint64_t)(((sb + SM_WMIX) & 0x3FFFF) >> 4) | ((uint64_t)1 << 16) | ((uint64_t)(1024 >> 4) << 32) | ((uint64_t)1 << 62);
        const uint64_t descB0 = (uint64_t)(((sb + SM_RING + wg * 8192) & 0x3FFFF) >> 4) | ((uint64_t)(128 >> 4) << 16) | ((uint64_t)(1024 >> 4) << 32);
        float d[2][32];
        asm volatile("wgmma.fence.sync.aligned;" ::: "memory");
#pragma unroll
        for (int mt = 0; mt < 2; mt++) {
#pragma unroll
            for (int ks = 0; ks < 8; ks++) {
                const uint64_t da = descA0 + (uint64_t)((ks * 2048 + mt * 16384) >> 4), db = descB0 + (uint64_t)(((ks & 3) * 256 + (ks >> 2) * SLOTB) >> 4);
                asm volatile("{.reg .pred p; setp.ne.b32 p, %34, 0;\n"
                    "wgmma.mma_async.sync.aligned.m64n64k16.f32.bf16.bf16 "
                    "{%0,%1,%2,%3,%4,%5,%6,%7,%8,%9,%10,%11,%12,%13,%14,%15,%16,%17,%18,%19,%20,%21,%22,%23,%24,%25,%26,%27,%28,%29,%30,%31}, %32, %33, p, 1, 1, 1, 1;}"
                    : "+f"(d[mt][0]), "+f"(d[mt][1]), "+f"(d[mt][2]), "+f"(d[mt][3]), "+f"(d[mt][4]), "+f"(d[mt][5]), "+f"(d[mt][6]), "+f"(d[mt][7]),
                      "+f"(d[mt][8]), "+f"(d[mt][9]), "+f"(d[mt][10]), "+f"(d[mt][11]), "+f"(d[mt][12]), "+f"(d[mt][13]), "+f"(d[mt][14]), "+f"(d[mt][15]),
                      "+f"(d[mt][16]), "+f"(d[mt][17]), "+f"(d[mt][18]), "+f"(d[mt][19]), "+f"(d[mt][20]), "+f"(d[mt][21]), "+f"(d[mt][22]), "+f"(d[mt][23]),
                      "+f"(d[mt][24]), "+f"(d[mt][25]), "+f"(d[mt][26]), "+f"(d[mt][27]), "+f"(d[mt][28]), "+f"(d[mt][29]), "+f"(d[mt][30]), "+f"(d[mt][31])
                    : "l"(da), "l"(db), "r"(ks));
            }
            asm volatile("wgmma.commit_group.sync.aligned;" ::: "memory");
        }
        int nd[8];
#pragma unroll
        for (int j = 0; j < 8; j++) { const int l = wg * 8 + j; nd[j] = order[(t >> 1) ? 79 - l : l]; }
        uint32_t* ob = out + (size_t)n0 * 256 + (w4 * 16 + g) * 2 + (t & 1);
#pragma unroll
        for (int mt = 0; mt < 2; mt++) {
            if (mt == 0) asm volatile("wgmma.wait_group.sync.aligned 1;" ::: "memory");
            else asm volatile("wgmma.wait_group.sync.aligned 0;" ::: "memory");
#pragma unroll
            for (int i = 0; i < 32; i++) asm volatile("" : "+f"(d[mt][i]) :: "memory");
#pragma unroll
            for (int j = 0; j < 8; j++) {
                if (nd[j] < nn) {
                    ob[nd[j] * 256 + mt * 128] = pack2(d[mt][4 * j], d[mt][4 * j + 1]);
                    ob[nd[j] * 256 + mt * 128 + 16] = pack2(d[mt][4 * j + 2], d[mt][4 * j + 3]);
                }
            }
        }
    }
    TSTAMP(8);
}

}

extern "C" void kernel_launch(void* const* d_in, const int* in_sizes, int n_in, void* d_out, int out_size) {
    (void)in_sizes; (void)n_in; (void)out_size;
    cudaFuncSetAttribute(tfn_kernel, cudaFuncAttributeMaxDynamicSharedMemorySize, SM_TOTAL);
    Scratch* gs = nullptr;
    cudaGetSymbolAddress((void**)&gs, g_scratch);
    cudaLaunchConfig_t cfg = {};
    cfg.gridDim = dim3(NB); cfg.blockDim = dim3(NT); cfg.dynamicSmemBytes = SM_TOTAL; cfg.stream = cudaStreamPerThread;
    cudaLaunchAttribute at[1];
    at[0].id = cudaLaunchAttributeCooperative; at[0].val.cooperative = 1;
    cfg.attrs = at; cfg.numAttrs = 1;
    cudaLaunchKernelEx(&cfg, tfn_kernel, (const unsigned char*)d_in[0], (const int4*)d_in[1], (const int4*)d_in[2],
                       (const uint4*)d_in[3], (const uint4*)d_in[4], (const uint16_t*)d_in[5], (const uint16_t*)d_in[6],
                       (const uint4*)d_in[7], (uint32_t*)d_out, gs);
}
```

```cpp
#include <cuda_runtime.h>
#include <cuda_bf16.h>
#include <stdint.h>

#define ABL 0
namespace {

constexpr int NN = 10000;
constexpr int NE = 320000;
constexpr int NB = 132;
constexpr int NW = 20;
constexpr int NT = NW * 32;
constexpr int CW = NW - 1;
constexpr int PW = 10;
constexpr int NPB = 76;
constexpr int CELL = 48;
constexpr int CAP = 19;
constexpr int DS = 4;
constexpr int STEPB = 160;
constexpr int NE4 = NE / 4;
constexpr int NPIECE = NB * CELL / 4;
constexpr uint32_t KEY_NONE = 0xFFFFFFFFu;
constexpr uint32_t F_WRAP = 128;

constexpr int SLOTB = NW * 2048;
constexpr int SM_RING = 0;
constexpr int SM_META = SM_RING + DS * SLOTB;
constexpr int SM_AZ = SM_META + NW * CAP * STEPB;
constexpr int SM_MISC = SM_AZ + 2048;
constexpr int SM_TOTAL = SM_MISC + 2048;
constexpr int SM_KEYS = SM_RING;
constexpr int SM_HIST = SM_RING + 25600;
constexpr int SM_RECS = SM_RING + SLOTB;
constexpr int SM_RAWY = SM_META;
constexpr int SM_RAWE = SM_RAWY + 608 * 32;
constexpr int SM_ELOC = SM_RAWE + 608 * 32;
static_assert(SM_TOTAL <= 232448 && SM_ELOC + NB * CELL * 2 <= SM_AZ, "smem");
static_assert(SM_RECS + NB * CELL * 16 <= SM_META && SM_HIST + 10240 <= SM_RECS, "smem");

struct Scratch {
    uint4 keys[NB * NPIECE];
    uint4 recs[NB * NB * CELL];
    uint4 stash[NB * NW * 256];
    unsigned bar[4];
    unsigned long long t0, pad;
};
__device__ Scratch g_scratch;
#define TSTAMP(i)
#define TSTAMPC(i)
#define WSTAMP(i)

__device__ __forceinline__ void mma16816(float* d, uint32_t a0, uint32_t a1, uint32_t a2, uint32_t a3, uint32_t b0, uint32_t b1) {
    asm("mma.sync.aligned.m16n8k16.row.col.f32.bf16.bf16.f32 {%0,%1,%2,%3}, {%4,%5,%6,%7}, {%8,%9}, {%0,%1,%2,%3};"
        : "+f"(d[0]), "+f"(d[1]), "+f"(d[2]), "+f"(d[3]) : "r"(a0), "r"(a1), "r"(a2), "r"(a3), "r"(b0), "r"(b1));
}
__device__ __forceinline__ void mma1688z(float* d, uint32_t a0, uint32_t a1, uint32_t b0) {
    asm("mma.sync.aligned.m16n8k8.row.col.f32.bf16.bf16.f32 {%0,%1,%2,%3}, {%4,%5}, {%6}, {%7,%7,%7,%7};"
        : "=f"(d[0]), "=f"(d[1]), "=f"(d[2]), "=f"(d[3]) : "r"(a0), "r"(a1), "r"(b0), "f"(0.f));
}
__device__ __forceinline__ uint32_t pack2(float lo, float hi) {
    uint32_t r; asm("cvt.rn.bf16x2.f32 %0, %1, %2;" : "=r"(r) : "f"(hi), "f"(lo)); return r;
}
__device__ __forceinline__ float silu_h(float h) {
    float t; asm("tanh.approx.f32 %0, %1;" : "=f"(t) : "f"(h)); return fmaf(h, t, h);
}
__device__ __forceinline__ uint32_t mul_lo(uint32_t v, uint32_t r) {
    __nv_bfloat162 a = *(__nv_bfloat162*)&v, b = *(__nv_bfloat162*)&r; __nv_bfloat162 c = __hmul2(a, __low2bfloat162(b)); return *(uint32_t*)&c;
}
__device__ __forceinline__ uint32_t mul_hi(uint32_t v, uint32_t r) {
    __nv_bfloat162 a = *(__nv_bfloat162*)&v, b = *(__nv_bfloat162*)&r; __nv_bfloat162 c = __hmul2(a, __high2bfloat162(b)); return *(uint32_t*)&c;
}
__device__ __forceinline__ uint2 lds64(uint32_t a) {
    uint2 r; asm volatile("ld.shared.v2.u32 {%0,%1}, [%2];" : "=r"(r.x), "=r"(r.y) : "r"(a)); return r;
}
__device__ __forceinline__ uint4 lds128(uint32_t a) {
    uint4 r; asm volatile("ld.shared.v4.u32 {%0,%1,%2,%3}, [%4];" : "=r"(r.x), "=r"(r.y), "=r"(r.z), "=r"(r.w) : "r"(a) : "memory"); return r;
}
__device__ __forceinline__ void bar_sync(int id, int n) { asm volatile("bar.sync %0, %1;" :: "r"(id), "r"(n) : "memory"); }
__device__ __forceinline__ void bar_arrive(int id, int n) { asm volatile("bar.arrive %0, %1;" :: "r"(id), "r"(n) : "memory"); }
__device__ __forceinline__ void mbar_wait(uint32_t bar, uint32_t ph) {
    uint32_t done; int spins = 0;
    do {
        asm volatile("{.reg .pred p; mbarrier.try_wait.parity.shared.b64 p, [%1], %2; selp.u32 %0,1,0,p;}" : "=r"(done) : "r"(bar), "r"(ph) : "memory");
    } while (!done && ++spins < (1 << 22));
}
__device__ __forceinline__ unsigned gbar_read(const unsigned* ctr) {
    unsigned v; asm volatile("ld.relaxed.gpu.global.u32 %0, [%1];" : "=r"(v) : "l"(ctr) : "memory");
    return v;
}
__device__ __forceinline__ void gbar_arrive(unsigned* ctr) {
    asm volatile("red.add.release.gpu.global.u32 [%0], 1;" :: "l"(ctr) : "memory");
}
__device__ __forceinline__ void gbar_wait(const unsigned* ctr, unsigned target) {
    unsigned v; int spins = 0;
    do { asm volatile("ld.acquire.gpu.global.u32 %0, [%1];" : "=r"(v) : "l"(ctr) : "memory"); } while ((int)(v - target) < 0 && ++spins < (1 << 22));
}
__device__ __forceinline__ int bin_start(int b) { return (b * NN + NB - 1) / NB; }
__device__ __forceinline__ int chunk_start4(int c) { return (c * NE4) / NB; }
__device__ __forceinline__ float bf2f(uint32_t h) { return __uint_as_float(h << 16); }

__device__ __noinline__ void slow_path(unsigned char* smem, int n0, int nn, const uint16_t* x, const int* src, const int* dst,
                                       const uint16_t* Y, const uint16_t* ef, const uint16_t* w_rad, const uint16_t* cg,
                                       const uint16_t* w_mix, __nv_bfloat16* out) {
    float* agg = (float*)smem;
    const int tid = threadIdx.x, lane = tid & 31, w = tid >> 5;
    bar_sync(1, NT);
    for (int i = tid; i < NPB * 512; i += NT) agg[i] = 0.f;
    bar_sync(1, NT);
    for (int e0 = w * 32; e0 < NE; e0 += NT) {
        int dl = dst[e0 + lane] - n0;
        unsigned m = __ballot_sync(0xffffffff, dl >= 0 && dl < nn);
        while (m) {
            int l = __ffs(m) - 1; m &= m - 1;
            int e = e0 + l, d = __shfl_sync(0xffffffff, dl, l), s = src[e];
            float T[16];
            for (int i = 0; i < 4; i++) for (int o = 0; o < 4; o++) {
                float a = 0.f;
                for (int f = 0; f < 4; f++) a += bf2f(Y[e * 4 + f]) * bf2f(cg[i * 16 + f * 4 + o]);
                T[i * 4 + o] = a;
            }
            for (int k = 0; k < 4; k++) {
                int c = lane + 32 * k;
                float z = 0.f;
                for (int j = 0; j < 4; j++) z += bf2f(ef[e * 4 + j]) * bf2f(w_rad[j * 128 + c]);
                float R = z / (1.f + __expf(-z));
                for (int o = 0; o < 4; o++) {
                    float a = 0.f;
                    for (int i = 0; i < 4; i++) a += bf2f(x[(size_t)s * 512 + c * 4 + i]) * T[i * 4 + o];
                    atomicAdd(&agg[d * 512 + c * 4 + o], R * a);
                }
            }
        }
    }
    bar_sync(1, NT);
    for (int i = tid; i < nn * 512; i += NT) {
        int n = i >> 9, d = (i >> 2) & 127, o = i & 3;
        float a = 0.f;
        for (int c = 0; c < 128; c++) a += agg[n * 512 + c * 4 + o] * bf2f(w_mix[c * 128 + d]);
        out[(size_t)(n0 + n) * 512 + (i & 511)] = __float2bfloat16(a);
    }
}

#define YDELAY 500
#define PACE 24500
#define NOPACE 0
#define TPOS 1
#define SRCPACE 1
#define POFF 800
#define PTOL 600
#define PFPOS 3
#define XPREFETCH if (lane == 0 && w < 4 && w * 19 < nn) \
    asm volatile("cp.async.bulk.prefetch.L2.global [%0], %1;" :: "l"(x + (size_t)(n0 + w * 19) * 1024), "r"(min(19, nn - w * 19) * 1024));
__global__ void __launch_bounds__(NT, 1)
tfn_kernel(const unsigned char* __restrict__ x, const int4* __restrict__ src4, const int4* __restrict__ dst4,
           const uint4* __restrict__ Y, const uint4* __restrict__ ef, const uint16_t* __restrict__ w_rad,
           const uint16_t* __restrict__ cg, const uint4* __restrict__ w_mix, uint32_t* __restrict__ out, Scratch* __restrict__ gs) {
    extern __shared__ __align__(1024) unsigned char smem[];
    const uint32_t sb = (uint32_t)__cvta_generic_to_shared(smem);
    const int b = blockIdx.x, tid = threadIdx.x, lane = tid & 31, g = lane >> 2, t = lane & 3;
    const int w = __shfl_sync(0xffffffff, tid >> 5, 0);
    uint32_t* keys = (uint32_t*)(smem + SM_KEYS);
    uint32_t* hist = (uint32_t*)(smem + SM_HIST);
    uint32_t* cnt = (uint32_t*)(smem + SM_MISC);
    uint32_t* deg = cnt + 160;
    uint32_t* order = deg + 80;
    uint32_t* cnt2 = order + 80;
    volatile uint32_t* flag = cnt2 + 132;
    const uint32_t mbarK = sb + SM_MISC + 1920, mbarR = mbarK + 8;
    const int n0 = bin_start(b), nn = bin_start(b + 1) - n0;
    TSTAMP(0);

    const int c0 = chunk_start4(b), c1 = chunk_start4(b + 1);
    const bool has4 = c0 + tid < c1;
    int4 d4 = make_int4(0, 0, 0, 0), s4 = d4;
    if (has4) { d4 = __ldg(dst4 + c0 + tid); s4 = __ldg(src4 + c0 + tid); }
    unsigned tgt = 0;
    if (tid == NT - 1) tgt = gbar_read(&gs->bar[0]);
    if (tid == 32) {
        asm volatile("mbarrier.init.shared.b64 [%0], 1;" :: "r"(mbarK));
        asm volatile("mbarrier.init.shared.b64 [%0], 1;" :: "r"(mbarR));
        asm volatile("fence.mbarrier_init.release.cluster;" ::: "memory");
        *flag = 0;
    }
    uint32_t wr0 = 0, wr1 = 0, cgv[1];
    if (w < 8 && t < 2) { wr0 = *(const uint32_t*)(w_rad + (2 * t) * 128 + 16 * w + 2 * g); wr1 = *(const uint32_t*)(w_rad + (2 * t + 1) * 128 + 16 * w + 2 * g); }
    cgv[0] = ((const uint32_t*)cg)[lane];
#pragma unroll
    for (int j = 0; j < 3; j++) if (tid + j * NT < NPIECE) ((uint4*)keys)[tid + j * NT] = make_uint4(KEY_NONE, KEY_NONE, KEY_NONE, KEY_NONE);
    ((uint4*)hist)[tid] = make_uint4(0, 0, 0, 0);
    if (tid < 160) cnt[tid] = 0;
    if (tid < 4) { deg[NPB + tid] = 127 - (NPB + tid); order[NPB + tid] = NPB + tid; }
    __syncthreads();
    TSTAMP(9);
    if (tid == 64) {
        __nanosleep(YDELAY);
        asm volatile("mbarrier.arrive.expect_tx.shared.b64 _, [%0], %1;" :: "r"(mbarR), "r"((c1 - c0) * 64) : "memory");
        asm volatile("cp.async.bulk.shared::cluster.global.mbarrier::complete_tx::bytes [%0], [%1], %2, [%3];"
                     :: "r"(sb + SM_RAWY), "l"(Y + 2 * c0), "r"((c1 - c0) * 32), "r"(mbarR) : "memory");
        asm volatile("cp.async.bulk.shared::cluster.global.mbarrier::complete_tx::bytes [%0], [%1], %2, [%3];"
                     :: "r"(sb + SM_RAWE), "l"(ef + 2 * c0), "r"((c1 - c0) * 32), "r"(mbarR) : "memory");
    }

    const uint32_t rot = ((b >> 1) & 3) * 4;
    if (has4) {
        const int dd[4] = {d4.x, d4.y, d4.z, d4.w}, ss[4] = {s4.x, s4.y, s4.z, s4.w};
        uint32_t bin[4], slot[4];
#pragma unroll
        for (int k = 0; k < 4; k++) { bin[k] = (uint32_t)(dd[k] * NB) / NN; slot[k] = min(atomicAdd(&cnt[bin[k]], 1), CELL - 1); }
#pragma unroll
        for (int k = 0; k < 4; k++) {
            const uint32_t key = (uint32_t)ss[k] | ((((dd[k] - bin_start(bin[k])) << 5) + ((ss[k] * 209) >> 16)) << 14);
            uint32_t sr = slot[k] + rot; if (sr >= CELL) sr -= CELL;
            keys[bin[k] * CELL + sr] = key;
            ((uint16_t*)(smem + SM_ELOC))[bin[k] * CELL + slot[k]] = tid * 4 + k;
        }
    }
    bar_sync(1, NT);
    TSTAMP(1);
    {
        const int hp = (11 + (rot >> 2)) % 12;
#pragma unroll
        for (int j = 0; j < 3; j++) {
            const int i = tid + j * NT;
            if (i < NPIECE) {
                const int bn = i / 12, r = i - bn * 12;
                uint4 v = ((uint4*)keys)[i];
                if (r == hp) v.w = 0xFF000000u | cnt[bn];
                gs->keys[(bn * NB + b) * 12 + r] = v;
            }
        }
    }
    uint32_t at[4];
    if (w == CW) {
        bar_sync(7, NT);
        if (tid == NT - 1) {
            TSTAMPC(10);
            gbar_arrive(&gs->bar[0]);
            TSTAMPC(11);
            tgt = (tgt / NB + 1) * NB;
            asm volatile("fence.proxy.async.shared::cta;" ::: "memory");
            asm volatile("mbarrier.arrive.expect_tx.shared.b64 _, [%0], %1;" :: "r"(mbarK), "r"(NPIECE * 16) : "memory");
            gbar_wait(&gs->bar[0], tgt);
            TSTAMPC(13);
            asm volatile("fence.proxy.async.global;" ::: "memory");
            asm volatile("cp.async.bulk.shared::cluster.global.mbarrier::complete_tx::bytes [%0], [%1], %2, [%3];"
                         :: "r"(sb + SM_KEYS), "l"(gs->keys + b * NPIECE), "r"(NPIECE * 16), "r"(mbarK) : "memory");
        }
    } else {
        bar_arrive(7, NT);
        if (w < 8) {
            *(uint2*)(smem + SM_AZ + (w >> 1) * 512 + lane * 16 + (w & 1) * 8) =
                make_uint2(pack2(0.5f * bf2f(wr0 & 0xFFFF), 0.5f * bf2f(wr1 & 0xFFFF)), pack2(0.5f * bf2f(wr0 >> 16), 0.5f * bf2f(wr1 >> 16)));
        }
        uint32_t el[7], cn[7];
#pragma unroll
        for (int j = 0; j < 7; j++) {
            const int cell = min(w + CW * j, NB - 1);
            cn[j] = cnt[cell];
            el[j] = ((const uint16_t*)(smem + SM_ELOC))[cell * CELL + min(lane, max((int)cn[j], 1) - 1)];
        }
        mbar_wait(mbarR, 0);
        TSTAMP(18);
#pragma unroll
        for (int j = 0; j < 7; j++) {
            const int cell = w + CW * j;
            if (cell < NB && lane < ((cn[j] + 1) & ~1u)) {
                const uint2 yy = *(const uint2*)(smem + SM_RAWY + el[j] * 8), ee = *(const uint2*)(smem + SM_RAWE + el[j] * 8);
                gs->recs[(cell * NB + b) * CELL + lane] = make_uint4(yy.x, ee.x, yy.y, ee.y);
            }
            if (cn[j] > 32 && cell < NB && lane + 32 < min(cn[j], CELL - 1)) {
                const uint32_t e2 = ((const uint16_t*)(smem + SM_ELOC))[cell * CELL + 32 + lane];
                const uint2 yy = *(const uint2*)(smem + SM_RAWY + e2 * 8), ee = *(const uint2*)(smem + SM_RAWE + e2 * 8);
                gs->recs[(cell * NB + b) * CELL + 32 + lane] = make_uint4(yy.x, ee.x, yy.y, ee.y);
            }
        }
        if (w == CW - 1) {
            bar_sync(8, NT - 32);
            if (lane == 0) { TSTAMPC(14); gbar_arrive(&gs->bar[1]); TSTAMPC(15); }
        } else bar_arrive(8, NT - 32);
    }
    __syncwarp();
    TSTAMP(2);
    {
        const int o = g & 3, f = 2 * (t & 1);
#pragma unroll
        for (int i = 0; i < 4; i++) {
            const uint32_t lo = __shfl_sync(0xffffffff, cgv[0], i * 8 + f * 2 + (o >> 1)), hi = __shfl_sync(0xffffffff, cgv[0], i * 8 + f * 2 + 2 + (o >> 1));
            at[i] = (t >> 1) == (g >> 2) ? __byte_perm(lo, hi, (o & 1) ? 0x7632 : 0x5410) : 0;
        }
    }

    uint32_t key[3][4], kidx[3];
    {
        uint32_t ka[3];
#pragma unroll
        for (int j = 0; j < 3; j++) {
            const int i = min(tid + j * NT, NPIECE - 1), r = i / NB, c = i - r * NB;
            int pr = r + ((c >> 1) & 3); if (pr >= 12) pr -= 12;
            ka[j] = sb + SM_KEYS + (c * 12 + pr) * 16;
            kidx[j] = c * CELL + r * 4;
        }
        mbar_wait(mbarK, 0);
        TSTAMP(3);
#pragma unroll
        for (int j = 0; j < 3; j++) {
            const uint4 v = lds128(ka[j]);
            key[j][0] = (tid + j * NT < NPIECE) ? v.x : KEY_NONE; key[j][1] = v.y; key[j][2] = v.z; key[j][3] = v.w;
        }
        if (tid < NB) {
            const uint32_t hc = keys[tid * CELL + (47 + ((tid >> 1) & 3) * 4) % CELL] & 0xFFFFFF;
            if (hc > CELL - 1) *flag = 1;
            cnt2[tid] = hc;
        }
#pragma unroll
        for (int j = 0; j < 3; j++) {
            if (key[j][0] != KEY_NONE) {
                uint32_t rk[4];
#pragma unroll
                for (int u = 0; u < 4; u++) rk[u] = key[j][u] < 0xFC000000u ? atomicAdd(&hist[key[j][u] >> 14], 1) : 0;
                if (max(max(rk[0], rk[1]), max(rk[2], rk[3])) > 62) *flag = 1;
#pragma unroll
                for (int u = 0; u < 4; u++) key[j][u] |= rk[u] << 26;
            }
        }
    }
    bar_sync(1, NT);
    TSTAMP(20);
    if (w == CW) {
        if (tid == NT - 1) { TSTAMPC(16); gbar_wait(&gs->bar[1], tgt); TSTAMPC(17); }
        __syncwarp();
    } else {
#pragma unroll
        for (int k = 0; k < 4; k++) {
            uint32_t dsum = __reduce_add_sync(0xffffffff, hist[(w * 4 + k) * 32 + lane]);
            if (lane == 0) deg[w * 4 + k] = dsum * 128 + (127 - (w * 4 + k));
        }
        bar_sync(9, NT - 32);
        const int n = tid >> 3, sub = tid & 7;
        const uint32_t me = deg[n];
        int r = 0;
#pragma unroll
        for (int k = 0; k < 10; k++) r += deg[sub * 10 + k] > me;
        r += __shfl_xor_sync(0xffffffff, r, 1); r += __shfl_xor_sync(0xffffffff, r, 2); r += __shfl_xor_sync(0xffffffff, r, 4);
        if (sub == 0) order[r] = n;
    }
    bar_sync(1, NT);
    TSTAMP(22);
    {
        uint32_t cn[7];
#pragma unroll
        for (int j = 0; j < 7; j++) cn[j] = w + NW * j < NB ? cnt2[w + NW * j] : 0;
        const uint4* gp = gs->recs + (b * NB + w) * CELL + lane;
        const uint32_t sp = sb + SM_RECS + (w * CELL + lane) * 16;
#pragma unroll
        for (int j = 0; j < 7; j++)
            if (lane < cn[j]) asm volatile("cp.async.cg.shared.global [%0], [%1], 16;" :: "r"(sp + j * (NW * CELL * 16)), "l"(gp + j * (NW * CELL)) : "memory");
#pragma unroll
        for (int j = 0; j < 7; j++)
            if (cn[j] > 32 && lane + 32 < min(cn[j], CELL - 1))
                asm volatile("cp.async.cg.shared.global [%0], [%1], 16;" :: "r"(sp + j * (NW * CELL * 16) + 512), "l"(gp + j * (NW * CELL) + 32) : "memory");
        asm volatile("cp.async.commit_group;" ::: "memory");
    }
    int S = 0, mylen = 0;
#pragma unroll
    for (int p = 0; p < 2; p++) {
        const int l = 2 * w + p, na = order[l], nb = order[79 - l];
        const uint32_t ca = hist[na * 32 + lane], cb = hist[nb * 32 + lane];
        uint32_t inc = ca + cb;
#pragma unroll
        for (int o = 1; o < 32; o <<= 1) { uint32_t u = __shfl_up_sync(0xffffffff, inc, o); if (lane >= o) inc += u; }
        const uint32_t base = w * (CAP * STEPB / 4) + p + 2 * (inc - ca - cb);
        hist[na * 32 + lane] = base;
        hist[nb * 32 + lane] = (base + 2 * ca) | 0x4000;
        const int len = __shfl_sync(0xffffffff, inc, 31);
        S = max(S, (len + 3) >> 2);
        if ((lane & 1) == p) mylen = len;
    }
    if (S > CAP) *flag = 1;
    S = __shfl_sync(0xffffffff, max(S, DS), 0);
    bar_sync(1, NT);
    TSTAMP(21);
    if (*flag) {
        asm volatile("cp.async.wait_all;" ::: "memory");
        slow_path(smem, n0, nn, (const uint16_t*)x, (const int*)src4, (const int*)dst4, (const uint16_t*)Y, (const uint16_t*)ef, w_rad, cg,
                  (const uint16_t*)w_mix, (__nv_bfloat16*)out);
        return;
    }
#pragma unroll
    for (int j = 0; j < 3; j++) {
        if (key[j][0] != KEY_NONE) {
            uint32_t h[4];
#pragma unroll
            for (int u = 0; u < 4; u++) h[u] = hist[min((key[j][u] >> 14) & 0xFFF, 2559u)];
#pragma unroll
            for (int u = 0; u < 4; u++) if (key[j][u] < 0xFC000000u)
                ((uint32_t*)(smem + SM_META))[(h[u] & 0x3FFF) + 2 * (key[j][u] >> 26)] = (key[j][u] & 0x3FFF) | (h[u] & 0x4000) | ((kidx[j] + u) << 15);
        }
    }
    asm volatile("cp.async.wait_all;" ::: "memory");
    bar_sync(1, NT);
    TSTAMP(4);
    constexpr int NRAW = (CAP + 3) / 4;
    uint32_t bits0 = 0, raw[NRAW], sv[NRAW];
    unsigned char* meta = smem + SM_META + w * (CAP * STEPB);
#pragma unroll
    for (int k = 0; k < NRAW; k++) {
        const int i = k * 32 + lane;
        raw[k] = (i >> 1) < mylen ? ((uint32_t*)meta)[i] : 0xFFFFFFFFu;
        const uint32_t ra = __shfl_sync(0xffffffff, raw[k], lane & 25), rb = __shfl_sync(0xffffffff, raw[k], (lane & 25) ^ 1);
        const uint32_t rr = raw[k] != 0xFFFFFFFFu ? raw[k] : ra != 0xFFFFFFFFu ? ra : rb != 0xFFFFFFFFu ? rb : n0;
        sv[k] = (rr & 0x3FFF) << 9;
    }
    const int q = lane >> 3, c = lane & 7;
    const uint32_t ring0 = sb + SM_RING + w * 2048;
    const uint32_t wdst = ring0 + q * 128 + ((c + 2 * q) & 7) * 16;
    const uint32_t rsrc = ring0 + t * 128 + ((g + 2 * t) & 7) * 16;
    const uint32_t recl = sb + SM_META + w * (CAP * STEPB) + g * 16 + (t & 1) * 8, srcl = sb + SM_META + w * (CAP * STEPB) + 128 + q * 8;
    const uint16_t* pbase = (const uint16_t*)(x + c * 16);
    auto cpa2 = [&](uint32_t dstp, uint32_t sv) {
        asm volatile("cp.async.cg.shared.global [%0], [%1], 16; cp.async.cg.shared.global [%0+1024], [%1+128], 16;"
                     :: "r"(dstp), "l"(pbase + sv) : "memory");
    };
    cpa2(wdst, __shfl_sync(0xffffffff, sv[0], 2 * q)); cpa2(wdst + 512, __shfl_sync(0xffffffff, sv[0], 2 * q + 1));
    asm volatile("cp.async.commit_group;" ::: "memory");
    TSTAMP(5);
    __syncwarp();
#pragma unroll
    for (int k = 0; k < NRAW; k++) {
        const int st = k * 4 + q;
        uint4 v = make_uint4(0, 0, 0, 0);
        if (raw[k] != 0xFFFFFFFFu) v = ((const uint4*)(smem + SM_RECS))[raw[k] >> 15];
        if (st < S) {
            *(uint4*)(meta + (st == 0 ? S - 1 : st - 1) * STEPB + c * 16) = v;
            *(uint32_t*)(meta + (st < DS ? S - DS + st : st - DS) * STEPB + 128 + c * 4) = sv[k] + (st < DS ? F_WRAP : 0);
        }
        const uint32_t m = (__ballot_sync(0xffffffff, raw[k] & 0x4000) >> g) & 0x01010101u;
        bits0 |= ((m * 0x10204080u) >> 28) << (4 * k);
    }
    if (t < 2) bits0 = ~bits0;
    bits0 = ((bits0 >> 1) & ~(1u << (S - 1))) | ((bits0 & 1) << (S - 1));
    unsigned long long tbase = 0;
    if (w == 0) {
        asm volatile("mov.u64 %0, %%globaltimer;" : "=l"(tbase));
        tbase += POFF;
        flag[1] = (uint32_t)tbase; flag[2] = (uint32_t)tbase;
        *(volatile unsigned long long*)(smem + SM_MISC + 1952) = 0;
        if (lane == 0) {
            asm volatile("red.max.relaxed.gpu.global.u64 [%0], %1;" :: "l"(&gs->t0), "l"(tbase) : "memory");
            if (b < 128) asm volatile("cp.async.bulk.prefetch.L2.global [%0], 256;" :: "l"(w_mix + b * 16));
        }
    }
    bar_sync(1, NT);
#pragma unroll
    for (int i = 1; i < DS; i++) {
        cpa2(wdst + i * SLOTB, __shfl_sync(0xffffffff, sv[0], 8 * i + 2 * q)); cpa2(wdst + i * SLOTB + 512, __shfl_sync(0xffffffff, sv[0], 8 * i + 2 * q + 1));
        asm volatile("cp.async.commit_group;" ::: "memory");
    }
    TSTAMP(6);

    uint32_t* stash = (uint32_t*)(gs->stash + (b * NW + w) * 256) + lane;
    float acc[4][4];
#pragma unroll
    for (int i = 0; i < 16; i++) acc[i / 4][i % 4] = 0.f;
    uint4 az = *(const uint4*)(smem + SM_AZ + lane * 16);
    uint32_t R[4], T[4];
    auto prep = [&](uint2 r, uint32_t mask) {
        float z[4], y[4], t1[4], t2[4];
        mma1688z(z, az.x, az.y, r.y);
        mma1688z(y, az.z, az.w, r.y);
        uint32_t bt;
        asm("{.reg .pred p; .reg .b32 m; and.b32 m, %2, %3; setp.ne.u32 p, m, 0; selp.b32 %0, %1, 0, p;}" : "=r"(bt) : "r"(r.x), "r"(bits0), "r"(mask));
        mma1688z(t1, at[0], at[1], bt);
        mma1688z(t2, at[2], at[3], bt);
        T[0] = pack2(t1[0], t1[2]); T[1] = pack2(t2[0], t2[2]); T[2] = pack2(t1[1], t1[3]); T[3] = pack2(t2[1], t2[3]);
        R[0] = pack2(silu_h(z[0]), silu_h(z[2])); R[1] = pack2(silu_h(z[1]), silu_h(z[3]));
        R[2] = pack2(silu_h(y[0]), silu_h(y[2])); R[3] = pack2(silu_h(y[1]), silu_h(y[3]));
    };
    const uint32_t tphase = PACE / 4;
    uint32_t dreg, dcur, dl = 0, now = flag[1], tcur = 0;
    {
        const int st = lane == S ? 0 : min(lane, S - 1);
        const uint4 u0 = *(const uint4*)(meta + st * STEPB + 128), u1 = *(const uint4*)(meta + st * STEPB + 144);
        int pos = (u0.x + u0.y + u0.z + u0.w + u1.x + u1.y + u1.z + u1.w) >> 12;
        pos += ((u0.x & F_WRAP) ? NN : 0) + (lane == S ? NN : 0) - NN * (2 * DS + 1) / 32;
        dreg = pos * (int)tphase / NN;
        dcur = dreg;
    }
    uint32_t mp = 0, smask = 1;
    auto step = [&](const uint32_t off, const int mode) {
        if (mode == 0) asm volatile("mov.u32 %0, %%globaltimer_lo;" : "=r"(now));
        const uint2 r = lds64(mp + recl);
        uint2 s0;
        if (mode == 0) s0 = lds64(mp + srcl);
        asm volatile("cp.async.wait_group %0;" :: "n"(DS - 1) : "memory");
        const uint4 xa = lds128(rsrc + off), xb = lds128(rsrc + off + 512), xc = lds128(rsrc + off + 1024), xd = lds128(rsrc + off + 1536);
        if (mode == 0) {
            dl = __shfl_sync(0xffffffff, dcur, 1); dcur = __shfl_down_sync(0xffffffff, dcur, 1);
            cpa2(wdst + off, s0.x); cpa2(wdst + off + 512, s0.y);
        }
        if (mode == 1 && w < 16) {
#pragma unroll
            for (int j = 0; j < 4; j++) {
                const int kk = 4 * j + q, ch = 16 * (w & 7) + 2 * (kk & 7) + (kk >> 3);
                asm volatile("cp.async.cg.shared.global [%0], [%1], 16;" :: "r"(ring0 + kk * 128 + ((c ^ (kk & 7)) << 4)), "l"(w_mix + ch * 16 + (w >> 3) * 8 + c) : "memory");
            }
        }
        if (mode == 2 || mode == 3) {
#pragma unroll
            for (int j = 0; j < 4; j += mode - 1)
                asm volatile("cp.async.cg.shared.global [%0], [%1], 16;" :: "r"(ring0 + off + j * 512 + lane * 16), "l"(stash + (mode - 2) * 512 + j * 128 + lane * 3) : "memory");
        }
        asm volatile("cp.async.commit_group;" ::: "memory");
        mma16816(acc[0], mul_lo(xa.x, R[0]), mul_hi(xa.z, R[0]), mul_lo(xa.y, R[0]), mul_hi(xa.w, R[0]), T[0], T[1]);
        mma16816(acc[1], mul_lo(xb.x, R[1]), mul_hi(xb.z, R[1]), mul_lo(xb.y, R[1]), mul_hi(xb.w, R[1]), T[2], T[3]);
        mma16816(acc[2], mul_lo(xc.x, R[2]), mul_hi(xc.z, R[2]), mul_lo(xc.y, R[2]), mul_hi(xc.w, R[2]), T[0], T[1]);
        mma16816(acc[3], mul_lo(xd.x, R[3]), mul_hi(xd.z, R[3]), mul_lo(xd.y, R[3]), mul_hi(xd.w, R[3]), T[2], T[3]);
        if (mode != 4) prep(r, smask);
        mp += STEPB; smask <<= 1;
    };
    auto putacc = [&](uint32_t* p) {
        p[0] = pack2(acc[0][0], acc[0][1]); p[32] = pack2(acc[0][2], acc[0][3]); p[64] = pack2(acc[2][0], acc[2][1]); p[96] = pack2(acc[2][2], acc[2][3]);
        p[256] = pack2(acc[1][0], acc[1][1]); p[288] = pack2(acc[1][2], acc[1][3]); p[320] = pack2(acc[3][0], acc[3][1]); p[352] = pack2(acc[3][2], acc[3][3]);
    };
    const uint32_t mlast = (S - 1) * STEPB;
    prep(lds64(mlast + recl), 1u << (S - 1));
    int ph = 0;
    uint32_t mev = mlast;
    auto event = [&]() {
        if (mp == mlast) {
            az = *(const uint4*)(smem + SM_AZ + (ph + 1) * 512 + lane * 16);
            mev += STEPB;
        } else {
            putacc(stash + (ph >> 1) * 512 + (ph & 1) * 128);
#pragma unroll
            for (int i = 0; i < 16; i++) acc[i / 4][i % 4] = 0.f;
            pbase += 128; mp = 0; smask = 1; ph++; mev = mlast;
            dreg += tphase; dcur = dreg + tcur;
            WSTAMP(ph - 1);
        }
    };
#pragma unroll 1
    for (int it = S - 1; it > 0; it--) {
        const uint32_t t0 = flag[1];
        if (w == PW) flag[2] = now - dl + tcur;
        dcur += t0 - tcur; tcur = t0;
        if (w == 0) {
            const unsigned long long tglob = *(volatile unsigned long long*)(smem + SM_MISC + 1952);
            const long long dg = tglob - tbase;
            uint32_t t1 = t0;
            if (dg > 0 && dg < 30000 && (int)((uint32_t)tglob - t0) > 0) t1 = (uint32_t)tglob;
            flag[1] = t1;
            const uint32_t cand = flag[2] - PTOL;
            asm volatile("{.reg .pred p, q; setp.eq.u32 p, %2, 0; setp.gt.and.s32 q, %3, 0, p;\n"
                         "@q red.max.relaxed.gpu.global.u64 [%0], %1; @p cp.async.cg.shared.global [%4], [%0], 16;}"
                         :: "l"(&gs->t0), "l"(tbase + (cand - (uint32_t)tbase)), "r"(lane), "r"(cand - t1), "r"(sb + SM_MISC + 1952) : "memory");
        }
#pragma unroll
        for (int k = 0; k < DS; k++) {
            step(k * SLOTB, 0);
            if (mp == mev || now < dl) {
                if (mp == mev) event();
                asm volatile("{.reg .pred p; .reg .u32 d;\n"
                             "PACE_LOOP: mov.u32 d, %%globaltimer_lo; sub.u32 d, %0, d; setp.lt.u32 p, d, 32768; @p nanosleep.u32 32; @p bra.uni PACE_LOOP;}"
                             :: "r"(dl) : "memory");
            }
        }
    }
    __syncwarp();
    step(0, 1); step(SLOTB, 2); step(2 * SLOTB, 3); step(3 * SLOTB, 4);
    WSTAMP(3);

    {
        putacc((uint32_t*)(smem + SM_RING + 2 * SLOTB + w * 2048 + 512) + lane);
        asm volatile("cp.async.wait_all;" ::: "memory");
        asm volatile("fence.proxy.async.shared::cta;" ::: "memory");
        const int wg = w >> 2, w4 = w & 3;
        TSTAMP(26);
        bar_sync(1, NT);
        TSTAMP(27);
        const uint64_t descA0 = (uint64_t)(((sb + SM_RING) & 0x3FFFF) >> 4) | ((uint64_t)1 << 16) | ((uint64_t)(1024 >> 4) << 32) | ((uint64_t)1 << 62);
        const uint64_t descB0 = (uint64_t)(((sb + SM_RING + SLOTB + wg * 8192) & 0x3FFFF) >> 4) | ((uint64_t)(128 >> 4) << 16) | ((uint64_t)(1024 >> 4) << 32);
        float d[2][32];
        asm volatile("wgmma.fence.sync.aligned;" ::: "memory");
#pragma unroll
        for (int mt = 0; mt < 2; mt++) {
#pragma unroll
            for (int ks = 0; ks < 8; ks++) {
                const uint64_t da = descA0 + (uint64_t)((ks * 2048 + mt * 16384) >> 4), db = descB0 + (uint64_t)(((ks & 3) * 256 + (ks >> 2) * SLOTB) >> 4);
                asm volatile("{.reg .pred p; setp.ne.b32 p, %34, 0;\n"
                    "wgmma.mma_async.sync.aligned.m64n64k16.f32.bf16.bf16 "
                    "{%0,%1,%2,%3,%4,%5,%6,%7,%8,%9,%10,%11,%12,%13,%14,%15,%16,%17,%18,%19,%20,%21,%22,%23,%24,%25,%26,%27,%28,%29,%30,%31}, %32, %33, p, 1, 1, 1, 1;}"
                    : "+f"(d[mt][0]), "+f"(d[mt][1]), "+f"(d[mt][2]), "+f"(d[mt][3]), "+f"(d[mt][4]), "+f"(d[mt][5]), "+f"(d[mt][6]), "+f"(d[mt][7]),
                      "+f"(d[mt][8]), "+f"(d[mt][9]), "+f"(d[mt][10]), "+f"(d[mt][11]), "+f"(d[mt][12]), "+f"(d[mt][13]), "+f"(d[mt][14]), "+f"(d[mt][15]),
                      "+f"(d[mt][16]), "+f"(d[mt][17]), "+f"(d[mt][18]), "+f"(d[mt][19]), "+f"(d[mt][20]), "+f"(d[mt][21]), "+f"(d[mt][22]), "+f"(d[mt][23]),
                      "+f"(d[mt][24]), "+f"(d[mt][25]), "+f"(d[mt][26]), "+f"(d[mt][27]), "+f"(d[mt][28]), "+f"(d[mt][29]), "+f"(d[mt][30]), "+f"(d[mt][31])
                    : "l"(da), "l"(db), "r"(ks));
            }
            asm volatile("wgmma.commit_group.sync.aligned;" ::: "memory");
        }
        int nd[8];
#pragma unroll
        for (int j = 0; j < 8; j++) { const int l = wg * 8 + j; nd[j] = order[(t >> 1) ? 79 - l : l]; }
        const bool odd = t & 1;
        uint2* ob = (uint2*)out + (size_t)n0 * 128 + w4 * 16 + g + (odd ? 8 : 0);
#pragma unroll
        for (int mt = 0; mt < 2; mt++) {
            if (mt == 0) asm volatile("wgmma.wait_group.sync.aligned 1;" ::: "memory");
            else asm volatile("wgmma.wait_group.sync.aligned 0;" ::: "memory");
#pragma unroll
            for (int i = 0; i < 32; i++) asm volatile("" : "+f"(d[mt][i]) :: "memory");
#pragma unroll
            for (int j = 0; j < 8; j++) {
                const uint32_t v0 = pack2(d[mt][4 * j], d[mt][4 * j + 1]), v1 = pack2(d[mt][4 * j + 2], d[mt][4 * j + 3]);
                const uint32_t rv = __shfl_xor_sync(0xffffffff, odd ? v0 : v1, 1);
                if (nd[j] < nn) ob[nd[j] * 128 + mt * 64] = odd ? make_uint2(rv, v1) : make_uint2(v0, rv);
            }
        }
    }
    TSTAMP(8);
}

}

extern "C" void kernel_launch(void* const* d_in, const int* in_sizes, int n_in, void* d_out, int out_size) {
    (void)in_sizes; (void)n_in; (void)out_size;
    cudaFuncSetAttribute(tfn_kernel, cudaFuncAttributeMaxDynamicSharedMemorySize, SM_TOTAL);
    Scratch* gs = nullptr;
    cudaGetSymbolAddress((void**)&gs, g_scratch);
    cudaLaunchConfig_t cfg = {};
    cfg.gridDim = dim3(NB); cfg.blockDim = dim3(NT); cfg.dynamicSmemBytes = SM_TOTAL; cfg.stream = cudaStreamPerThread;
    cudaLaunchAttribute at[1];
    at[0].id = cudaLaunchAttributeCooperative; at[0].val.cooperative = 1;
    cfg.attrs = at; cfg.numAttrs = 1;
    cudaLaunchKernelEx(&cfg, tfn_kernel, (const unsigned char*)d_in[0], (const int4*)d_in[1], (const int4*)d_in[2],
                       (const uint4*)d_in[3], (const uint4*)d_in[4], (const uint16_t*)d_in[5], (const uint16_t*)d_in[6],
                       (const uint4*)d_in[7], (uint32_t*)d_out, gs);
}
```

```cpp
#include <cuda_runtime.h>
#include <cuda_bf16.h>
#include <stdint.h>

#define ABL 0
namespace {

constexpr int NN = 10000;
constexpr int NE = 320000;
constexpr int NB = 132;
constexpr int NW = 20;
constexpr int NT = NW * 32;
constexpr int CW = NW - 1;
constexpr int PW = 10;
constexpr int NPB = 76;
constexpr int CELL = 48;
constexpr int CAP = 19;
constexpr int DS = 4;
constexpr int STEPB = 160;
constexpr int NE4 = NE / 4;
constexpr int NPIECE = NB * 8;
constexpr uint32_t KEY_NONE = 0xFFFFFFFFu;
constexpr uint32_t F_WRAP = 128;

constexpr int SLOTB = NW * 2048;
constexpr int SM_RING = 0;
constexpr int SM_META = SM_RING + DS * SLOTB;
constexpr int SM_AZ = SM_META + NW * CAP * STEPB;
constexpr int SM_MISC = SM_AZ + 2048;
constexpr int SM_TOTAL = SM_MISC + 2048;
constexpr int SM_STAGE = SM_RING;
constexpr int SM_HIST = SM_RING + 25600;
constexpr int SM_SMALL = SM_HIST + 10240;
constexpr int SM_RECS = SM_RING + SLOTB;
constexpr int SM_RAWY = SM_META;
constexpr int SM_RAWE = SM_RAWY + 608 * 32;
constexpr int SM_KEYS = SM_RAWE + 608 * 32;
static_assert(SM_TOTAL <= 232448 && SM_KEYS + NPIECE * 16 <= SM_AZ, "smem");
static_assert(SM_RECS + NB * CELL * 16 <= SM_META && SM_SMALL + 1152 <= SM_RECS, "smem");

struct Scratch {
    uint4 keys[NB * NPIECE];
    uint4 recs[NB * NB * CELL];
    uint4 stash[NB * NW * 256];
    unsigned bar[4];
    unsigned long long t0, pad;
};
__device__ Scratch g_scratch;
#define TSTAMP(i)
#define TSTAMPC(i)
#define WSTAMP(i)

__device__ __forceinline__ void mma16816(float* d, uint32_t a0, uint32_t a1, uint32_t a2, uint32_t a3, uint32_t b0, uint32_t b1) {
    asm("mma.sync.aligned.m16n8k16.row.col.f32.bf16.bf16.f32 {%0,%1,%2,%3}, {%4,%5,%6,%7}, {%8,%9}, {%0,%1,%2,%3};"
        : "+f"(d[0]), "+f"(d[1]), "+f"(d[2]), "+f"(d[3]) : "r"(a0), "r"(a1), "r"(a2), "r"(a3), "r"(b0), "r"(b1));
}
__device__ __forceinline__ void mma1688z(float* d, uint32_t a0, uint32_t a1, uint32_t b0) {
    asm("mma.sync.aligned.m16n8k8.row.col.f32.bf16.bf16.f32 {%0,%1,%2,%3}, {%4,%5}, {%6}, {%7,%7,%7,%7};"
        : "=f"(d[0]), "=f"(d[1]), "=f"(d[2]), "=f"(d[3]) : "r"(a0), "r"(a1), "r"(b0), "f"(0.f));
}
__device__ __forceinline__ uint32_t pack2(float lo, float hi) {
    uint32_t r; asm("cvt.rn.bf16x2.f32 %0, %1, %2;" : "=r"(r) : "f"(hi), "f"(lo)); return r;
}
__device__ __forceinline__ float silu_h(float h) {
    float t; asm("tanh.approx.f32 %0, %1;" : "=f"(t) : "f"(h)); return fmaf(h, t, h);
}
__device__ __forceinline__ uint32_t mul_lo(uint32_t v, uint32_t r) {
    __nv_bfloat162 a = *(__nv_bfloat162*)&v, b = *(__nv_bfloat162*)&r; __nv_bfloat162 c = __hmul2(a, __low2bfloat162(b)); return *(uint32_t*)&c;
}
__device__ __forceinline__ uint32_t mul_hi(uint32_t v, uint32_t r) {
    __nv_bfloat162 a = *(__nv_bfloat162*)&v, b = *(__nv_bfloat162*)&r; __nv_bfloat162 c = __hmul2(a, __high2bfloat162(b)); return *(uint32_t*)&c;
}
__device__ __forceinline__ uint2 lds64(uint32_t a) {
    uint2 r; asm volatile("ld.shared.v2.u32 {%0,%1}, [%2];" : "=r"(r.x), "=r"(r.y) : "r"(a)); return r;
}
__device__ __forceinline__ uint4 lds128(uint32_t a) {
    uint4 r; asm volatile("ld.shared.v4.u32 {%0,%1,%2,%3}, [%4];" : "=r"(r.x), "=r"(r.y), "=r"(r.z), "=r"(r.w) : "r"(a) : "memory"); return r;
}
__device__ __forceinline__ void bar_sync(int id, int n) { asm volatile("bar.sync %0, %1;" :: "r"(id), "r"(n) : "memory"); }
__device__ __forceinline__ void bar_arrive(int id, int n) { asm volatile("bar.arrive %0, %1;" :: "r"(id), "r"(n) : "memory"); }
__device__ __forceinline__ void mbar_wait(uint32_t bar, uint32_t ph) {
    uint32_t done; int spins = 0;
    do {
        asm volatile("{.reg .pred p; mbarrier.try_wait.parity.shared.b64 p, [%1], %2; selp.u32 %0,1,0,p;}" : "=r"(done) : "r"(bar), "r"(ph) : "memory");
    } while (!done && ++spins < (1 << 22));
}
__device__ __forceinline__ unsigned gbar_read(const unsigned* ctr) {
    unsigned v; asm volatile("ld.relaxed.gpu.global.u32 %0, [%1];" : "=r"(v) : "l"(ctr) : "memory");
    return v;
}
__device__ __forceinline__ void gbar_arrive(unsigned* ctr) {
    asm volatile("red.add.release.gpu.global.u32 [%0], 1;" :: "l"(ctr) : "memory");
}
__device__ __forceinline__ void gbar_wait(const unsigned* ctr, unsigned target) {
    unsigned v; int spins = 0;
    do { asm volatile("ld.acquire.gpu.global.u32 %0, [%1];" : "=r"(v) : "l"(ctr) : "memory"); } while ((int)(v - target) < 0 && ++spins < (1 << 22));
}
__device__ __forceinline__ int chunk_start4(int c) { return (c * NE4) / NB; }
__device__ __forceinline__ float bf2f(uint32_t h) { return __uint_as_float(h << 16); }

__device__ __noinline__ void slow_path(unsigned char* smem, int n0, int nn, const uint16_t* x, const int* src, const int* dst,
                                       const uint16_t* Y, const uint16_t* ef, const uint16_t* w_rad, const uint16_t* cg,
                                       const uint16_t* w_mix, __nv_bfloat16* out) {
    float* agg = (float*)smem;
    const int tid = threadIdx.x, lane = tid & 31, w = tid >> 5;
    bar_sync(1, NT);
    for (int i = tid; i < NPB * 512; i += NT) agg[i] = 0.f;
    bar_sync(1, NT);
    for (int e0 = w * 32; e0 < NE; e0 += NT) {
        int dl = dst[e0 + lane] - n0;
        unsigned m = __ballot_sync(0xffffffff, dl >= 0 && dl < nn);
        while (m) {
            int l = __ffs(m) - 1; m &= m - 1;
            int e = e0 + l, d = __shfl_sync(0xffffffff, dl, l), s = src[e];
            float T[16];
            for (int i = 0; i < 4; i++) for (int o = 0; o < 4; o++) {
                float a = 0.f;
                for (int f = 0; f < 4; f++) a += bf2f(Y[e * 4 + f]) * bf2f(cg[i * 16 + f * 4 + o]);
                T[i * 4 + o] = a;
            }
            for (int k = 0; k < 4; k++) {
                int c = lane + 32 * k;
                float z = 0.f;
                for (int j = 0; j < 4; j++) z += bf2f(ef[e * 4 + j]) * bf2f(w_rad[j * 128 + c]);
                float R = z / (1.f + __expf(-z));
                for (int o = 0; o < 4; o++) {
                    float a = 0.f;
                    for (int i = 0; i < 4; i++) a += bf2f(x[(size_t)s * 512 + c * 4 + i]) * T[i * 4 + o];
                    atomicAdd(&agg[d * 512 + c * 4 + o], R * a);
                }
            }
        }
    }
    bar_sync(1, NT);
    for (int i = tid; i < nn * 512; i += NT) {
        int n = i >> 9, d = (i >> 2) & 127, o = i & 3;
        float a = 0.f;
        for (int c = 0; c < 128; c++) a += agg[n * 512 + c * 4 + o] * bf2f(w_mix[c * 128 + d]);
        out[(size_t)(n0 + n) * 512 + (i & 511)] = __float2bfloat16(a);
    }
}

#define PACE 24500
#define NOPACE 0
#define TPOS 1
#define SRCPACE 1
#define POFF 800
#define PTOL 600
__global__ void __launch_bounds__(NT, 1)
tfn_kernel(const unsigned char* __restrict__ x, const int4* __restrict__ src4, const int4* __restrict__ dst4,
           const uint4* __restrict__ Y, const uint4* __restrict__ ef, const uint16_t* __restrict__ w_rad,
           const uint16_t* __restrict__ cg, const uint4* __restrict__ w_mix, uint32_t* __restrict__ out, Scratch* __restrict__ gs) {
    extern __shared__ __align__(1024) unsigned char smem[];
    const uint32_t sb = (uint32_t)__cvta_generic_to_shared(smem);
    const int b = blockIdx.x, tid = threadIdx.x, lane = tid & 31, g = lane >> 2, t = lane & 3;
    const int w = __shfl_sync(0xffffffff, tid >> 5, 0);
    uint32_t* stage = (uint32_t*)(smem + SM_STAGE);
    uint32_t* hist = (uint32_t*)(smem + SM_HIST);
    uint32_t* cnt = (uint32_t*)(smem + SM_MISC);
    uint32_t* deg = cnt + 160;
    uint32_t* order = deg + 80;
    uint32_t* cnt2 = order + 80;
    volatile uint32_t* flag = cnt2 + 132;
    const uint32_t mbarK = sb + SM_MISC + 1920;
    const int n0 = b * NPB, nn = min(NPB, NN - n0);
    TSTAMP(0);

    const int c0 = chunk_start4(b), c1 = chunk_start4(b + 1);
    const bool has4 = c0 + tid < c1;
    int4 d4 = make_int4(0, 0, 0, 0), s4 = d4;
    if (has4) { d4 = __ldg(dst4 + c0 + tid); s4 = __ldg(src4 + c0 + tid); }
    unsigned tgt = 0;
    if (tid == NT - 1) {
        tgt = gbar_read(&gs->bar[0]);
        asm volatile("mbarrier.init.shared.b64 [%0], 1;" :: "r"(mbarK));
        asm volatile("fence.mbarrier_init.release.cluster;" ::: "memory");
        *flag = 0;
    }
    if (w == CW) {
        asm volatile("cp.async.cg.shared.global [%0], [%1], 16;" :: "r"(sb + SM_SMALL + lane * 16), "l"(w_rad + lane * 8) : "memory");
        asm volatile("cp.async.cg.shared.global [%0], [%1], 16;" :: "r"(sb + SM_SMALL + 512 + lane * 16), "l"(w_rad + 256 + lane * 8) : "memory");
        if (lane < 8) asm volatile("cp.async.cg.shared.global [%0], [%1], 16;" :: "r"(sb + SM_SMALL + 1024 + lane * 16), "l"(cg + lane * 8) : "memory");
    } else {
#pragma unroll
        for (int j = 0; j < 2; j++) {
            const int i = tid + j * 608;
            if (i < 2 * (c1 - c0)) {
                asm volatile("cp.async.cg.shared.global [%0], [%1], 16;" :: "r"(sb + SM_RAWY + i * 16), "l"(Y + 2 * c0 + i) : "memory");
                asm volatile("cp.async.cg.shared.global [%0], [%1], 16;" :: "r"(sb + SM_RAWE + i * 16), "l"(ef + 2 * c0 + i) : "memory");
            }
        }
    }
    ((uint4*)hist)[tid] = make_uint4(0, 0, 0, 0);
    if (tid < 160) cnt[tid] = 0;
    if (tid < 80) { deg[tid] = 127 - tid; order[tid] = tid; }
    __syncthreads();
    TSTAMP(9);

    if (has4) {
        const uint32_t dd[4] = {(uint32_t)d4.x, (uint32_t)d4.y, (uint32_t)d4.z, (uint32_t)d4.w}, ss[4] = {(uint32_t)s4.x, (uint32_t)s4.y, (uint32_t)s4.z, (uint32_t)s4.w};
        uint32_t bin[4], slot[4];
#pragma unroll
        for (int k = 0; k < 4; k++) { bin[k] = dd[k] / NPB; slot[k] = atomicAdd(&cnt[bin[k]], 1); }
#pragma unroll
        for (int k = 0; k < 4; k++)
            stage[bin[k] * CELL + min(slot[k], CELL - 1)] = (((ss[k] - bin[k]) * NPB + dd[k]) << 12) + tid * 4 + k;
    }
    if (w == CW) asm volatile("cp.async.wait_all;" ::: "memory");
    bar_sync(1, NT);
    TSTAMP(1);
#pragma unroll
    for (int j = 0; j < 2; j++) {
        const int i = tid + j * NT;
        if (i < NPIECE) {
            const uint2 sa = *(const uint2*)(stage + i * 6), sc = *(const uint2*)(stage + i * 6 + 2), se = *(const uint2*)(stage + i * 6 + 4);
            const uint32_t cn = min(cnt[i >> 3], 255u);
            gs->keys[((i >> 3) * NB + b) * 8 + ((i ^ b) & 7)] =
                make_uint4(__funnelshift_r(sa.x, se.x >> 12, 12), __funnelshift_r(sa.y, __funnelshift_r(se.x, cn, 24), 12),
                           __funnelshift_r(sc.x, se.y >> 12, 12), __funnelshift_r(sc.y, __funnelshift_r(se.y, cn >> 4, 24), 12));
        }
    }
    if (w == CW) {
        bar_sync(7, NT);
        if (tid == NT - 1) {
            TSTAMPC(10);
            gbar_arrive(&gs->bar[0]);
            TSTAMPC(11);
        }
        __syncwarp();
        bar_arrive(8, NT);
        if (tid == NT - 1) {
            tgt = (tgt / NB + 1) * NB;
            asm volatile("mbarrier.arrive.expect_tx.shared.b64 _, [%0], %1;" :: "r"(mbarK), "r"(NPIECE * 16) : "memory");
            gbar_wait(&gs->bar[0], tgt);
            TSTAMPC(13);
            asm volatile("fence.proxy.async.global;" ::: "memory");
            asm volatile("cp.async.bulk.shared::cluster.global.mbarrier::complete_tx::bytes [%0], [%1], %2, [%3];"
                         :: "r"(sb + SM_KEYS), "l"(gs->keys + b * NPIECE), "r"(NPIECE * 16), "r"(mbarK) : "memory");
        }
    } else {
        bar_arrive(7, NT);
        if (w < 8) {
            const uint32_t* wp = (const uint32_t*)(smem + SM_SMALL) + (t & 1) * 128 + 8 * w + g;
            const uint32_t wr0 = t < 2 ? wp[0] : 0, wr1 = t < 2 ? wp[64] : 0;
            *(uint2*)(smem + SM_AZ + (w >> 1) * 512 + lane * 16 + (w & 1) * 8) =
                make_uint2(pack2(0.5f * bf2f(wr0 & 0xFFFF), 0.5f * bf2f(wr1 & 0xFFFF)), pack2(0.5f * bf2f(wr0 >> 16), 0.5f * bf2f(wr1 >> 16)));
        }
        uint32_t el[7], cn[7], big = 0;
#pragma unroll
        for (int j = 0; j < 7; j++) {
            const int cell = w + CW * j;
            cn[j] = cnt[cell];
            el[j] = (stage[cell * CELL + min(lane, max((int)cn[j], 1) - 1)] & 0xFFF) * 8;
            big |= cn[j] > 32;
        }
        asm volatile("cp.async.wait_all;" ::: "memory");
        bar_sync(8, NT);
        TSTAMP(18);
        uint4* rp = gs->recs + (w * NB + b) * CELL + lane;
#pragma unroll
        for (int j = 0; j < 7; j++) {
            if (lane < ((cn[j] + 1) & ~1u)) {
                const uint2 yy = *(const uint2*)(smem + SM_RAWY + el[j]), ee = *(const uint2*)(smem + SM_RAWE + el[j]);
                rp[j * (CW * NB * CELL)] = make_uint4(yy.x, ee.x, yy.y, ee.y);
            }
        }
        if (big) {
#pragma unroll 1
            for (int j = 0; j < 7; j++) {
                const int cell = w + CW * j;
                if (lane + 32 < min(cnt[cell], CELL)) {
                    const uint32_t e2 = (stage[cell * CELL + 32 + lane] & 0xFFF) * 8;
                    const uint2 yy = *(const uint2*)(smem + SM_RAWY + e2), ee = *(const uint2*)(smem + SM_RAWE + e2);
                    rp[j * (CW * NB * CELL) + 32] = make_uint4(yy.x, ee.x, yy.y, ee.y);
                }
            }
        }
        if (w == CW - 1) {
            bar_sync(9, NT - 32);
            if (lane == 0) { TSTAMPC(14); gbar_arrive(&gs->bar[1]); TSTAMPC(15); }
        } else bar_arrive(9, NT - 32);
    }
    __syncwarp();
    TSTAMP(2);
    uint32_t at[4];
    {
        const int o = g & 3, f = 2 * (t & 1);
#pragma unroll
        for (int i = 0; i < 4; i++) {
            const uint16_t* cp = (const uint16_t*)(smem + SM_SMALL + 1024) + i * 16 + f * 4 + o;
            at[i] = (t >> 1) == (g >> 2) ? cp[0] | ((uint32_t)cp[4] << 16) : 0;
        }
    }

    uint32_t key[2][6], kidx[2];
    int nk[2];
    {
        uint32_t ka[2];
#pragma unroll
        for (int j = 0; j < 2; j++) {
            const int i = min(tid + j * NT, NPIECE - 1), r = i / NB, c = i - r * NB;
            ka[j] = sb + SM_KEYS + (c * 8 + ((r ^ c) & 7)) * 16;
            kidx[j] = c * CELL + r * 6;
            nk[j] = tid + j * NT < NPIECE ? -6 * r : -1000;
        }
        mbar_wait(mbarK, 0);
        TSTAMP(3);
        const uint4 v[2] = {lds128(ka[0]), lds128(ka[1])};
#pragma unroll
        for (int j = 0; j < 2; j++) {
            const uint32_t hc = (v[j].y >> 28) | ((v[j].w >> 28) << 4);
            if (j == 0 && tid < NB) { cnt2[tid] = hc; if (hc > CELL) *flag = 1; }
            nk[j] += hc;
            if (nk[j] > 0) {
                key[j][0] = v[j].x & 0xFFFFF; key[j][1] = v[j].y & 0xFFFFF; key[j][2] = v[j].z & 0xFFFFF; key[j][3] = v[j].w & 0xFFFFF;
                key[j][4] = (v[j].x >> 20) | ((v[j].y >> 8) & 0xFF000); key[j][5] = (v[j].z >> 20) | ((v[j].w >> 8) & 0xFF000);
                uint32_t rk[6], mx = 0;
#pragma unroll
                for (int u = 0; u < 6; u++) {
                    const uint32_t sr = key[j][u] / NPB, dl = key[j][u] - sr * NPB, hidx = dl * 32 + ((sr * 209) >> 16);
                    key[j][u] = sr | (hidx << 14);
                    rk[u] = 0;
                    if (u < nk[j]) { rk[u] = atomicAdd(&hist[hidx], 1); atomicAdd(&deg[dl], 128); }
                }
#pragma unroll
                for (int u = 0; u < 6; u++) { mx |= rk[u]; key[j][u] |= rk[u] << 26; }
                if (mx > 63) *flag = 1;
            }
        }
    }
    bar_sync(1, NT);
    TSTAMP(20);
    if (w == CW) {
        if (tid == NT - 1) { TSTAMPC(16); gbar_wait(&gs->bar[1], tgt); TSTAMPC(17); }
        __syncwarp();
    } else {
        const int n = tid >> 3, sub = tid & 7;
        const uint32_t me = deg[n];
        int r = 0;
#pragma unroll
        for (int k = 0; k < 10; k++) r += deg[sub * 10 + k] > me;
        r += __shfl_xor_sync(0xffffffff, r, 1); r += __shfl_xor_sync(0xffffffff, r, 2); r += __shfl_xor_sync(0xffffffff, r, 4);
        if (sub == 0) order[r] = n;
    }
    bar_sync(1, NT);
    TSTAMP(22);
    int S = 0, mylen = 0;
#pragma unroll
    for (int p = 0; p < 2; p++) {
        const int l = 2 * w + p, na = order[l], nb = order[79 - l];
        const uint32_t ca = hist[na * 32 + lane], cb = hist[nb * 32 + lane];
        uint32_t inc = ca + cb;
#pragma unroll
        for (int o = 1; o < 32; o <<= 1) { uint32_t u = __shfl_up_sync(0xffffffff, inc, o); if (lane >= o) inc += u; }
        const uint32_t base = w * (CAP * STEPB / 4) + p + 2 * (inc - ca - cb);
        hist[na * 32 + lane] = base;
        hist[nb * 32 + lane] = (base + 2 * ca) | 0x4000;
        const int len = __shfl_sync(0xffffffff, inc, 31);
        S = max(S, (len + 3) >> 2);
        if ((lane & 1) == p) mylen = len;
    }
    if (S > CAP) *flag = 1;
    {
        uint32_t cn[7], big = 0;
#pragma unroll
        for (int j = 0; j < 7; j++) { cn[j] = w + NW * j < NB ? cnt2[w + NW * j] : 0; big |= cn[j] > 32; }
        const uint4* gp = gs->recs + (b * NB + w) * CELL + lane;
        const uint32_t sp = sb + SM_RECS + (w * CELL + lane) * 16;
#pragma unroll
        for (int j = 0; j < 7; j++)
            if (lane < cn[j]) asm volatile("cp.async.cg.shared.global [%0], [%1], 16;" :: "r"(sp + j * (NW * CELL * 16)), "l"(gp + j * (NW * CELL)) : "memory");
        if (big) {
#pragma unroll
            for (int j = 0; j < 7; j++)
                if (lane + 32 < min(cn[j], CELL))
                    asm volatile("cp.async.cg.shared.global [%0], [%1], 16;" :: "r"(sp + j * (NW * CELL * 16) + 512), "l"(gp + j * (NW * CELL) + 32) : "memory");
        }
        asm volatile("cp.async.commit_group;" ::: "memory");
    }
    S = __shfl_sync(0xffffffff, max(S, DS), 0);
    bar_sync(1, NT);
    TSTAMP(21);
    if (*flag) {
        asm volatile("cp.async.wait_all;" ::: "memory");
        slow_path(smem, n0, nn, (const uint16_t*)x, (const int*)src4, (const int*)dst4, (const uint16_t*)Y, (const uint16_t*)ef, w_rad, cg,
                  (const uint16_t*)w_mix, (__nv_bfloat16*)out);
        return;
    }
#pragma unroll
    for (int j = 0; j < 2; j++) {
        if (nk[j] > 0) {
            uint32_t h[6];
#pragma unroll
            for (int u = 0; u < 6; u++) h[u] = hist[(key[j][u] >> 14) & 0xFFF];
#pragma unroll
            for (int u = 0; u < 6; u++) if (u < nk[j])
                ((uint32_t*)(smem + SM_META))[(h[u] & 0x3FFF) + 2 * (key[j][u] >> 26)] = (key[j][u] & 0x3FFF) | (h[u] & 0x4000) | ((kidx[j] + u) << 15);
        }
    }
    asm volatile("cp.async.wait_all;" ::: "memory");
    bar_sync(1, NT);
    TSTAMP(4);
    constexpr int NRAW = (CAP + 3) / 4;
    uint32_t bits0 = 0, raw[NRAW], sv[NRAW];
    unsigned char* meta = smem + SM_META + w * (CAP * STEPB);
#pragma unroll
    for (int k = 0; k < NRAW; k++) {
        const int i = k * 32 + lane;
        raw[k] = (i >> 1) < mylen ? ((uint32_t*)meta)[i] : 0xFFFFFFFFu;
        const uint32_t ra = __shfl_sync(0xffffffff, raw[k], lane & 25), rb = __shfl_sync(0xffffffff, raw[k], (lane & 25) ^ 1);
        const uint32_t rr = raw[k] != 0xFFFFFFFFu ? raw[k] : ra != 0xFFFFFFFFu ? ra : rb != 0xFFFFFFFFu ? rb : n0;
        sv[k] = (rr & 0x3FFF) << 9;
    }
    const int q = lane >> 3, c = lane & 7;
    const uint32_t ring0 = sb + SM_RING + w * 2048;
    const uint32_t wdst = ring0 + q * 128 + ((c + 2 * q) & 7) * 16;
    const uint32_t rsrc = ring0 + t * 128 + ((g + 2 * t) & 7) * 16;
    const uint32_t recl = sb + SM_META + w * (CAP * STEPB) + g * 16 + (t & 1) * 8, srcl = sb + SM_META + w * (CAP * STEPB) + 128 + q * 8;
    const uint16_t* pbase = (const uint16_t*)(x + c * 16);
    auto cpa2 = [&](uint32_t dstp, uint32_t sv) {
        asm volatile("cp.async.cg.shared.global [%0], [%1], 16; cp.async.cg.shared.global [%0+1024], [%1+128], 16;"
                     :: "r"(dstp), "l"(pbase + sv) : "memory");
    };
    cpa2(wdst, __shfl_sync(0xffffffff, sv[0], 2 * q)); cpa2(wdst + 512, __shfl_sync(0xffffffff, sv[0], 2 * q + 1));
    asm volatile("cp.async.commit_group;" ::: "memory");
    TSTAMP(5);
    __syncwarp();
#pragma unroll
    for (int k = 0; k < NRAW; k++) {
        const int st = k * 4 + q;
        uint4 v = make_uint4(0, 0, 0, 0);
        if (raw[k] != 0xFFFFFFFFu) v = ((const uint4*)(smem + SM_RECS))[raw[k] >> 15];
        if (st < S) {
            *(uint4*)(meta + (st == 0 ? S - 1 : st - 1) * STEPB + c * 16) = v;
            *(uint32_t*)(meta + (st < DS ? S - DS + st : st - DS) * STEPB + 128 + c * 4) = sv[k] + (st < DS ? F_WRAP : 0);
        }
        const uint32_t m = (__ballot_sync(0xffffffff, raw[k] & 0x4000) >> g) & 0x01010101u;
        bits0 |= ((m * 0x10204080u) >> 28) << (4 * k);
    }
    if (t < 2) bits0 = ~bits0;
    bits0 = ((bits0 >> 1) & ~(1u << (S - 1))) | ((bits0 & 1) << (S - 1));
    unsigned long long tbase = 0;
    if (w == 0) {
        asm volatile("mov.u64 %0, %%globaltimer;" : "=l"(tbase));
        tbase += POFF;
        flag[1] = (uint32_t)tbase; flag[2] = (uint32_t)tbase;
        *(volatile unsigned long long*)(smem + SM_MISC + 1952) = 0;
        if (lane == 0) {
            asm volatile("red.max.relaxed.gpu.global.u64 [%0], %1;" :: "l"(&gs->t0), "l"(tbase) : "memory");
            if (b < 128) asm volatile("cp.async.bulk.prefetch.L2.global [%0], 256;" :: "l"(w_mix + b * 16));
        }
    }
    bar_sync(1, NT);
#pragma unroll
    for (int i = 1; i < DS; i++) {
        cpa2(wdst + i * SLOTB, __shfl_sync(0xffffffff, sv[0], 8 * i + 2 * q)); cpa2(wdst + i * SLOTB + 512, __shfl_sync(0xffffffff, sv[0], 8 * i + 2 * q + 1));
        asm volatile("cp.async.commit_group;" ::: "memory");
    }
    TSTAMP(6);

    uint32_t* stash = (uint32_t*)(gs->stash + (b * NW + w) * 256) + lane;
    float acc[4][4];
#pragma unroll
    for (int i = 0; i < 16; i++) acc[i / 4][i % 4] = 0.f;
    uint4 az = *(const uint4*)(smem + SM_AZ + lane * 16);
    uint32_t R[4], T[4];
    auto prep = [&](uint2 r, uint32_t mask) {
        float z[4], y[4], t1[4], t2[4];
        mma1688z(z, az.x, az.y, r.y);
        mma1688z(y, az.z, az.w, r.y);
        uint32_t bt;
        asm("{.reg .pred p; .reg .b32 m; and.b32 m, %2, %3; setp.ne.u32 p, m, 0; selp.b32 %0, %1, 0, p;}" : "=r"(bt) : "r"(r.x), "r"(bits0), "r"(mask));
        mma1688z(t1, at[0], at[1], bt);
        mma1688z(t2, at[2], at[3], bt);
        T[0] = pack2(t1[0], t1[2]); T[1] = pack2(t2[0], t2[2]); T[2] = pack2(t1[1], t1[3]); T[3] = pack2(t2[1], t2[3]);
        R[0] = pack2(silu_h(z[0]), silu_h(z[2])); R[1] = pack2(silu_h(z[1]), silu_h(z[3]));
        R[2] = pack2(silu_h(y[0]), silu_h(y[2])); R[3] = pack2(silu_h(y[1]), silu_h(y[3]));
    };
    const uint32_t tphase = PACE / 4;
    uint32_t dreg, dcur, dl = 0, now = flag[1], tcur = 0;
    {
        const int st = lane == S ? 0 : min(lane, S - 1);
        const uint4 u0 = *(const uint4*)(meta + st * STEPB + 128), u1 = *(const uint4*)(meta + st * STEPB + 144);
        int pos = (u0.x + u0.y + u0.z + u0.w + u1.x + u1.y + u1.z + u1.w) >> 12;
        pos += ((u0.x & F_WRAP) ? NN : 0) + (lane == S ? NN : 0) - NN * (2 * DS + 1) / 32;
        dreg = pos * (int)tphase / NN;
        dcur = dreg;
    }
    uint32_t mp = 0, smask = 1;
    auto step = [&](const uint32_t off, const int mode) {
        if (mode == 0) asm volatile("mov.u32 %0, %%globaltimer_lo;" : "=r"(now));
        const uint2 r = lds64(mp + recl);
        uint2 s0;
        if (mode == 0) s0 = lds64(mp + srcl);
        asm volatile("cp.async.wait_group %0;" :: "n"(DS - 1) : "memory");
        const uint4 xa = lds128(rsrc + off), xb = lds128(rsrc + off + 512), xc = lds128(rsrc + off + 1024), xd = lds128(rsrc + off + 1536);
        if (mode == 0) {
            dl = __shfl_sync(0xffffffff, dcur, 1); dcur = __shfl_down_sync(0xffffffff, dcur, 1);
            cpa2(wdst + off, s0.x); cpa2(wdst + off + 512, s0.y);
        }
        if (mode == 1 && w < 16) {
#pragma unroll
            for (int j = 0; j < 4; j++) {
                const int kk = 4 * j + q, ch = 16 * (w & 7) + 2 * (kk & 7) + (kk >> 3);
                asm volatile("cp.async.cg.shared.global [%0], [%1], 16;" :: "r"(ring0 + kk * 128 + ((c ^ (kk & 7)) << 4)), "l"(w_mix + ch * 16 + (w >> 3) * 8 + c) : "memory");
            }
        }
        if (mode == 2 || mode == 3) {
#pragma unroll
            for (int j = 0; j < 4; j += mode - 1)
                asm volatile("cp.async.cg.shared.global [%0], [%1], 16;" :: "r"(ring0 + off + j * 512 + lane * 16), "l"(stash + (mode - 2) * 512 + j * 128 + lane * 3) : "memory");
        }
        asm volatile("cp.async.commit_group;" ::: "memory");
        mma16816(acc[0], mul_lo(xa.x, R[0]), mul_hi(xa.z, R[0]), mul_lo(xa.y, R[0]), mul_hi(xa.w, R[0]), T[0], T[1]);
        mma16816(acc[1], mul_lo(xb.x, R[1]), mul_hi(xb.z, R[1]), mul_lo(xb.y, R[1]), mul_hi(xb.w, R[1]), T[2], T[3]);
        mma16816(acc[2], mul_lo(xc.x, R[2]), mul_hi(xc.z, R[2]), mul_lo(xc.y, R[2]), mul_hi(xc.w, R[2]), T[0], T[1]);
        mma16816(acc[3], mul_lo(xd.x, R[3]), mul_hi(xd.z, R[3]), mul_lo(xd.y, R[3]), mul_hi(xd.w, R[3]), T[2], T[3]);
        if (mode != 4) prep(r, smask);
        mp += STEPB; smask <<= 1;
    };
    auto putacc = [&](uint32_t* p) {
        p[0] = pack2(acc[0][0], acc[0][1]); p[32] = pack2(acc[0][2], acc[0][3]); p[64] = pack2(acc[2][0], acc[2][1]); p[96] = pack2(acc[2][2], acc[2][3]);
        p[256] = pack2(acc[1][0], acc[1][1]); p[288] = pack2(acc[1][2], acc[1][3]); p[320] = pack2(acc[3][0], acc[3][1]); p[352] = pack2(acc[3][2], acc[3][3]);
    };
    const uint32_t mlast = (S - 1) * STEPB;
    prep(lds64(mlast + recl), 1u << (S - 1));
    int ph = 0;
    uint32_t mev = mlast;
    auto event = [&]() {
        if (mp == mlast) {
            az = *(const uint4*)(smem + SM_AZ + (ph + 1) * 512 + lane * 16);
            mev += STEPB;
        } else {
            putacc(stash + (ph >> 1) * 512 + (ph & 1) * 128);
#pragma unroll
            for (int i = 0; i < 16; i++) acc[i / 4][i % 4] = 0.f;
            pbase += 128; mp = 0; smask = 1; ph++; mev = mlast;
            dreg += tphase; dcur = dreg + tcur;
            WSTAMP(ph - 1);
        }
    };
#pragma unroll 1
    for (int it = S - 1; it > 0; it--) {
        const uint32_t t0 = flag[1];
        if (w == PW) flag[2] = now - dl + tcur;
        dcur += t0 - tcur; tcur = t0;
        if (w == 0) {
            const unsigned long long tglob = *(volatile unsigned long long*)(smem + SM_MISC + 1952);
            const long long dg = tglob - tbase;
            uint32_t t1 = t0;
            if (dg > 0 && dg < 30000 && (int)((uint32_t)tglob - t0) > 0) t1 = (uint32_t)tglob;
            flag[1] = t1;
            const uint32_t cand = flag[2] - PTOL;
            asm volatile("{.reg .pred p, q; setp.eq.u32 p, %2, 0; setp.gt.and.s32 q, %3, 0, p;\n"
                         "@q red.max.relaxed.gpu.global.u64 [%0], %1; @p cp.async.cg.shared.global [%4], [%0], 16;}"
                         :: "l"(&gs->t0), "l"(tbase + (cand - (uint32_t)tbase)), "r"(lane), "r"(cand - t1), "r"(sb + SM_MISC + 1952) : "memory");
        }
#pragma unroll
        for (int k = 0; k < DS; k++) {
            step(k * SLOTB, 0);
            if (mp == mev || now < dl) {
                if (mp == mev) event();
                asm volatile("{.reg .pred p; .reg .u32 d;\n"
                             "PACE_LOOP: mov.u32 d, %%globaltimer_lo; sub.u32 d, %0, d; setp.lt.u32 p, d, 32768; @p nanosleep.u32 32; @p bra.uni PACE_LOOP;}"
                             :: "r"(dl) : "memory");
            }
        }
    }
    __syncwarp();
    step(0, 1); step(SLOTB, 2); step(2 * SLOTB, 3); step(3 * SLOTB, 4);
    WSTAMP(3);

    {
        putacc((uint32_t*)(smem + SM_RING + 2 * SLOTB + w * 2048 + 512) + lane);
        asm volatile("cp.async.wait_all;" ::: "memory");
        asm volatile("fence.proxy.async.shared::cta;" ::: "memory");
        const int wg = w >> 2, w4 = w & 3;
        TSTAMP(26);
        bar_sync(1, NT);
        TSTAMP(27);
        const uint64_t descA0 = (uint64_t)(((sb + SM_RING) & 0x3FFFF) >> 4) | ((uint64_t)1 << 16) | ((uint64_t)(1024 >> 4) << 32) | ((uint64_t)1 << 62);
        const uint64_t descB0 = (uint64_t)(((sb + SM_RING + SLOTB + wg * 8192) & 0x3FFFF) >> 4) | ((uint64_t)(128 >> 4) << 16) | ((uint64_t)(1024 >> 4) << 32);
        float d[2][32];
        asm volatile("wgmma.fence.sync.aligned;" ::: "memory");
#pragma unroll
        for (int mt = 0; mt < 2; mt++) {
#pragma unroll
            for (int ks = 0; ks < 8; ks++) {
                const uint64_t da = descA0 + (uint64_t)((ks * 2048 + mt * 16384) >> 4), db = descB0 + (uint64_t)(((ks & 3) * 256 + (ks >> 2) * SLOTB) >> 4);
                asm volatile("{.reg .pred p; setp.ne.b32 p, %34, 0;\n"
                    "wgmma.mma_async.sync.aligned.m64n64k16.f32.bf16.bf16 "
                    "{%0,%1,%2,%3,%4,%5,%6,%7,%8,%9,%10,%11,%12,%13,%14,%15,%16,%17,%18,%19,%20,%21,%22,%23,%24,%25,%26,%27,%28,%29,%30,%31}, %32, %33, p, 1, 1, 1, 1;}"
                    : "+f"(d[mt][0]), "+f"(d[mt][1]), "+f"(d[mt][2]), "+f"(d[mt][3]), "+f"(d[mt][4]), "+f"(d[mt][5]), "+f"(d[mt][6]), "+f"(d[mt][7]),
                      "+f"(d[mt][8]), "+f"(d[mt][9]), "+f"(d[mt][10]), "+f"(d[mt][11]), "+f"(d[mt][12]), "+f"(d[mt][13]), "+f"(d[mt][14]), "+f"(d[mt][15]),
                      "+f"(d[mt][16]), "+f"(d[mt][17]), "+f"(d[mt][18]), "+f"(d[mt][19]), "+f"(d[mt][20]), "+f"(d[mt][21]), "+f"(d[mt][22]), "+f"(d[mt][23]),
                      "+f"(d[mt][24]), "+f"(d[mt][25]), "+f"(d[mt][26]), "+f"(d[mt][27]), "+f"(d[mt][28]), "+f"(d[mt][29]), "+f"(d[mt][30]), "+f"(d[mt][31])
                    : "l"(da), "l"(db), "r"(ks));
            }
            asm volatile("wgmma.commit_group.sync.aligned;" ::: "memory");
        }
        int nd[8];
#pragma unroll
        for (int j = 0; j < 8; j++) { const int l = wg * 8 + j; nd[j] = order[(t >> 1) ? 79 - l : l]; }
        const bool odd = t & 1;
        uint2* ob = (uint2*)out + (size_t)n0 * 128 + w4 * 16 + g + (odd ? 8 : 0);
#pragma unroll
        for (int mt = 0; mt < 2; mt++) {
            if (mt == 0) asm volatile("wgmma.wait_group.sync.aligned 1;" ::: "memory");
            else asm volatile("wgmma.wait_group.sync.aligned 0;" ::: "memory");
#pragma unroll
            for (int i = 0; i < 32; i++) asm volatile("" : "+f"(d[mt][i]) :: "memory");
#pragma unroll
            for (int j = 0; j < 8; j++) {
                const uint32_t v0 = pack2(d[mt][4 * j], d[mt][4 * j + 1]), v1 = pack2(d[mt][4 * j + 2], d[mt][4 * j + 3]);
                const uint32_t rv = __shfl_xor_sync(0xffffffff, odd ? v0 : v1, 1);
                if (nd[j] < nn) ob[nd[j] * 128 + mt * 64] = odd ? make_uint2(rv, v1) : make_uint2(v0, rv);
            }
        }
    }
    TSTAMP(8);
}

}

extern "C" void kernel_launch(void* const* d_in, const int* in_sizes, int n_in, void* d_out, int out_size) {
    (void)in_sizes; (void)n_in; (void)out_size;
    cudaFuncSetAttribute(tfn_kernel, cudaFuncAttributeMaxDynamicSharedMemorySize, SM_TOTAL);
    Scratch* gs = nullptr;
    cudaGetSymbolAddress((void**)&gs, g_scratch);
    cudaLaunchConfig_t cfg = {};
    cfg.gridDim = dim3(NB); cfg.blockDim = dim3(NT); cfg.dynamicSmemBytes = SM_TOTAL; cfg.stream = cudaStreamPerThread;
    cudaLaunchAttribute at[1];
    at[0].id = cudaLaunchAttributeCooperative; at[0].val.cooperative = 1;
    cfg.attrs = at; cfg.numAttrs = 1;
    cudaLaunchKernelEx(&cfg, tfn_kernel, (const unsigned char*)d_in[0], (const int4*)d_in[1], (const int4*)d_in[2],
                       (const uint4*)d_in[3], (const uint4*)d_in[4], (const uint16_t*)d_in[5], (const uint16_t*)d_in[6],
                       (const uint4*)d_in[7], (uint32_t*)d_out, gs);
}
```

```cpp
#include <cuda_runtime.h>
#include <cuda_bf16.h>
#include <stdint.h>

#define ABL 0
namespace {

constexpr int NN = 10000;
constexpr int NE = 320000;
constexpr int NB = 132;
constexpr int NW = 20;
constexpr int NT = NW * 32;
constexpr int CW = NW - 1;
constexpr int PW = 10;
constexpr int NPB = 76;
constexpr int CELL = 48;
constexpr int CAP = 19;
constexpr int DS = 4;
constexpr int STEPB = 160;
constexpr int NE4 = NE / 4;
constexpr int NPIECE = NB * 8;
constexpr int KB = 320, KN = 32 * KB;
constexpr uint32_t F_WRAP = 1;

constexpr int SLOTB = NW * 2048;
constexpr int SM_RING = 0;
constexpr int SM_META = SM_RING + DS * SLOTB;
constexpr int SM_AZ = SM_META + NW * CAP * STEPB;
constexpr int SM_MISC = SM_AZ + 2048;
constexpr int SM_TOTAL = SM_MISC + 2048;
constexpr int SM_STAGE = SM_RING;
constexpr int SM_HIST = SM_RING + 25600;
constexpr int SM_POS = SM_RING;
constexpr int SM_SMALL = SM_HIST + 13056;
constexpr int SM_RECS = SM_RING + SLOTB;
constexpr int SM_RAWY = SM_META;
constexpr int SM_RAWE = SM_RAWY + 608 * 32;
constexpr int SM_KEYS = SM_RAWE + 608 * 32;
static_assert(SM_TOTAL <= 232448 && SM_KEYS + NPIECE * 16 <= SM_AZ, "smem");
static_assert(SM_RECS + NB * CELL * 16 + 16 <= SM_META && SM_SMALL + 1152 <= SM_RECS, "smem");

struct Scratch {
    uint4 keys[NB * NPIECE];
    uint4 recs[NB * NB * CELL];
    uint4 stash[NB * NW * 256];
    unsigned bar[4];
    unsigned long long t0, pad;
};
__device__ Scratch g_scratch;
#define TSTAMP(i)
#define TSTAMPC(i)
#define WSTAMP(i)

__device__ __forceinline__ void mma16816(float* d, uint32_t a0, uint32_t a1, uint32_t a2, uint32_t a3, uint32_t b0, uint32_t b1) {
    asm("mma.sync.aligned.m16n8k16.row.col.f32.bf16.bf16.f32 {%0,%1,%2,%3}, {%4,%5,%6,%7}, {%8,%9}, {%0,%1,%2,%3};"
        : "+f"(d[0]), "+f"(d[1]), "+f"(d[2]), "+f"(d[3]) : "r"(a0), "r"(a1), "r"(a2), "r"(a3), "r"(b0), "r"(b1));
}
__device__ __forceinline__ void mma1688z(float* d, uint32_t a0, uint32_t a1, uint32_t b0) {
    asm("mma.sync.aligned.m16n8k8.row.col.f32.bf16.bf16.f32 {%0,%1,%2,%3}, {%4,%5}, {%6}, {%7,%7,%7,%7};"
        : "=f"(d[0]), "=f"(d[1]), "=f"(d[2]), "=f"(d[3]) : "r"(a0), "r"(a1), "r"(b0), "f"(0.f));
}
__device__ __forceinline__ uint32_t pack2(float lo, float hi) {
    uint32_t r; asm("cvt.rn.bf16x2.f32 %0, %1, %2;" : "=r"(r) : "f"(hi), "f"(lo)); return r;
}
__device__ __forceinline__ float silu_h(float h) {
    float t; asm("tanh.approx.f32 %0, %1;" : "=f"(t) : "f"(h)); return fmaf(h, t, h);
}
__device__ __forceinline__ uint32_t mul_lo(uint32_t v, uint32_t r) {
    __nv_bfloat162 a = *(__nv_bfloat162*)&v, b = *(__nv_bfloat162*)&r; __nv_bfloat162 c = __hmul2(a, __low2bfloat162(b)); return *(uint32_t*)&c;
}
__device__ __forceinline__ uint32_t mul_hi(uint32_t v, uint32_t r) {
    __nv_bfloat162 a = *(__nv_bfloat162*)&v, b = *(__nv_bfloat162*)&r; __nv_bfloat162 c = __hmul2(a, __high2bfloat162(b)); return *(uint32_t*)&c;
}
__device__ __forceinline__ uint2 lds64(uint32_t a) {
    uint2 r; asm volatile("ld.shared.v2.u32 {%0,%1}, [%2];" : "=r"(r.x), "=r"(r.y) : "r"(a)); return r;
}
__device__ __forceinline__ uint4 lds128(uint32_t a) {
    uint4 r; asm volatile("ld.shared.v4.u32 {%0,%1,%2,%3}, [%4];" : "=r"(r.x), "=r"(r.y), "=r"(r.z), "=r"(r.w) : "r"(a) : "memory"); return r;
}
__device__ __forceinline__ void bar_sync(int id, int n) { asm volatile("bar.sync %0, %1;" :: "r"(id), "r"(n) : "memory"); }
__device__ __forceinline__ void bar_arrive(int id, int n) { asm volatile("bar.arrive %0, %1;" :: "r"(id), "r"(n) : "memory"); }
__device__ __forceinline__ void mbar_wait(uint32_t bar, uint32_t ph) {
    uint32_t done; int spins = 0;
    do {
        asm volatile("{.reg .pred p; mbarrier.try_wait.parity.shared.b64 p, [%1], %2; selp.u32 %0,1,0,p;}" : "=r"(done) : "r"(bar), "r"(ph) : "memory");
    } while (!done && ++spins < (1 << 22));
}
__device__ __forceinline__ unsigned gbar_read(const unsigned* ctr) {
    unsigned v; asm volatile("ld.relaxed.gpu.global.u32 %0, [%1];" : "=r"(v) : "l"(ctr) : "memory");
    return v;
}
__device__ __forceinline__ void gbar_arrive(unsigned* ctr) {
    asm volatile("red.add.release.gpu.global.u32 [%0], 1;" :: "l"(ctr) : "memory");
}
__device__ __forceinline__ void gbar_wait(const unsigned* ctr, unsigned target) {
    unsigned v; int spins = 0;
    do { asm volatile("ld.acquire.gpu.global.u32 %0, [%1];" : "=r"(v) : "l"(ctr) : "memory"); } while ((int)(v - target) < 0 && ++spins < (1 << 22));
}
__device__ __forceinline__ int chunk_start4(int c) { return (c * NE4) / NB; }
__device__ __forceinline__ float bf2f(uint32_t h) { return __uint_as_float(h << 16); }

__device__ __noinline__ void slow_path(unsigned char* smem, int n0, int nn, const uint16_t* x, const int* src, const int* dst,
                                       const uint16_t* Y, const uint16_t* ef, const uint16_t* w_rad, const uint16_t* cg,
                                       const uint16_t* w_mix, __nv_bfloat16* out) {
    float* agg = (float*)smem;
    const int tid = threadIdx.x, lane = tid & 31, w = tid >> 5;
    bar_sync(1, NT);
    for (int i = tid; i < NPB * 512; i += NT) agg[i] = 0.f;
    bar_sync(1, NT);
    for (int e0 = w * 32; e0 < NE; e0 += NT) {
        int dl = dst[e0 + lane] - n0;
        unsigned m = __ballot_sync(0xffffffff, dl >= 0 && dl < nn);
        while (m) {
            int l = __ffs(m) - 1; m &= m - 1;
            int e = e0 + l, d = __shfl_sync(0xffffffff, dl, l), s = src[e];
            float T[16];
            for (int i = 0; i < 4; i++) for (int o = 0; o < 4; o++) {
                float a = 0.f;
                for (int f = 0; f < 4; f++) a += bf2f(Y[e * 4 + f]) * bf2f(cg[i * 16 + f * 4 + o]);
                T[i * 4 + o] = a;
            }
            for (int k = 0; k < 4; k++) {
                int c = lane + 32 * k;
                float z = 0.f;
                for (int j = 0; j < 4; j++) z += bf2f(ef[e * 4 + j]) * bf2f(w_rad[j * 128 + c]);
                float R = z / (1.f + __expf(-z));
                for (int o = 0; o < 4; o++) {
                    float a = 0.f;
                    for (int i = 0; i < 4; i++) a += bf2f(x[(size_t)s * 512 + c * 4 + i]) * T[i * 4 + o];
                    atomicAdd(&agg[d * 512 + c * 4 + o], R * a);
                }
            }
        }
    }
    bar_sync(1, NT);
    for (int i = tid; i < nn * 512; i += NT) {
        int n = i >> 9, d = (i >> 2) & 127, o = i & 3;
        float a = 0.f;
        for (int c = 0; c < 128; c++) a += agg[n * 512 + c * 4 + o] * bf2f(w_mix[c * 128 + d]);
        out[(size_t)(n0 + n) * 512 + (i & 511)] = __float2bfloat16(a);
    }
}

#define PACE 24500
#define YDELAY 0
#define NB0 4
#define NOPACE 0
#define TPOS 1
#define POFF 800
#define PTOL 600
__global__ void __launch_bounds__(NT, 1)
tfn_kernel(const unsigned char* __restrict__ x, const int4* __restrict__ src4, const int4* __restrict__ dst4,
           const uint4* __restrict__ Y, const uint4* __restrict__ ef, const uint16_t* __restrict__ w_rad,
           const uint16_t* __restrict__ cg, const uint4* __restrict__ w_mix, uint32_t* __restrict__ out, Scratch* __restrict__ gs) {
    extern __shared__ __align__(1024) unsigned char smem[];
    const uint32_t sb = (uint32_t)__cvta_generic_to_shared(smem);
    const int b = blockIdx.x, tid = threadIdx.x, lane = tid & 31, g = lane >> 2, t = lane & 3;
    const int w = __shfl_sync(0xffffffff, tid >> 5, 0);
    uint32_t* stage = (uint32_t*)(smem + SM_STAGE);
    uint32_t* hist = (uint32_t*)(smem + SM_HIST);
    uint32_t* cnt = (uint32_t*)(smem + SM_MISC);
    uint32_t* deg = cnt + 136;
    uint32_t* order = deg + 104;
    uint32_t* cnt2 = order + 80;
    volatile uint32_t* flag = cnt2 + 136;
    const uint32_t mbarK = sb + SM_MISC + 1920, mbarR = mbarK + 8;
    const int n0 = b * NPB, nn = min(NPB, NN - n0);
    TSTAMP(0);

    const int c0 = chunk_start4(b), c1 = chunk_start4(b + 1);
    const bool has4 = c0 + tid < c1;
    int4 d4 = make_int4(0, 0, 0, 0), s4 = d4;
    if (has4) { d4 = __ldg(dst4 + c0 + tid); s4 = __ldg(src4 + c0 + tid); }
    unsigned tgt = 0;
    if (tid == NT - 1) {
        tgt = gbar_read(&gs->bar[0]);
        asm volatile("mbarrier.init.shared.b64 [%0], 1;" :: "r"(mbarK));
        asm volatile("mbarrier.init.shared.b64 [%0], 1;" :: "r"(mbarR));
        asm volatile("fence.mbarrier_init.release.cluster;" ::: "memory");
        *flag = 0;
    }
    if (w == CW) {
        asm volatile("cp.async.cg.shared.global [%0], [%1], 16;" :: "r"(sb + SM_SMALL + lane * 16), "l"(w_rad + lane * 8) : "memory");
        asm volatile("cp.async.cg.shared.global [%0], [%1], 16;" :: "r"(sb + SM_SMALL + 512 + lane * 16), "l"(w_rad + 256 + lane * 8) : "memory");
        if (lane < 8) asm volatile("cp.async.cg.shared.global [%0], [%1], 16;" :: "r"(sb + SM_SMALL + 1024 + lane * 16), "l"(cg + lane * 8) : "memory");
    }
    ((uint4*)hist)[tid] = make_uint4(0, 0, 0, 0);
    {
        const uint32_t dk = ((80 + b % 22) * KN + (b & 31) * KB) << 12;
#pragma unroll
        for (int j = 0; j < 3; j++) if (tid + j * NT < NB * CELL / 4) ((uint4*)stage)[tid + j * NT] = make_uint4(dk, dk, dk, dk);
    }
    if (tid < 136) cnt[tid] = 0;
    if (tid == 0) { cnt2[NB] = 0; *(uint4*)(smem + SM_RECS + NB * CELL * 16) = make_uint4(0, 0, 0, 0); }
    if (tid < 80) { deg[tid] = 127 - tid; order[tid] = tid; }
    __syncthreads();
    TSTAMP(9);
    if (tid == 64) {
        if (YDELAY) __nanosleep(YDELAY);
        asm volatile("mbarrier.arrive.expect_tx.shared.b64 _, [%0], %1;" :: "r"(mbarR), "r"((c1 - c0) * 64) : "memory");
        asm volatile("cp.async.bulk.shared::cluster.global.mbarrier::complete_tx::bytes [%0], [%1], %2, [%3];"
                     :: "r"(sb + SM_RAWY), "l"(Y + 2 * c0), "r"((c1 - c0) * 32), "r"(mbarR) : "memory");
        asm volatile("cp.async.bulk.shared::cluster.global.mbarrier::complete_tx::bytes [%0], [%1], %2, [%3];"
                     :: "r"(sb + SM_RAWE), "l"(ef + 2 * c0), "r"((c1 - c0) * 32), "r"(mbarR) : "memory");
    }

    if (has4) {
        const uint32_t dd[4] = {(uint32_t)d4.x, (uint32_t)d4.y, (uint32_t)d4.z, (uint32_t)d4.w}, ss[4] = {(uint32_t)s4.x, (uint32_t)s4.y, (uint32_t)s4.z, (uint32_t)s4.w};
        uint32_t bin[4], slot[4];
#pragma unroll
        for (int k = 0; k < 4; k++) { bin[k] = dd[k] / NPB; slot[k] = atomicAdd(&cnt[bin[k]], 1); }
#pragma unroll
        for (int k = 0; k < 4; k++)
            stage[bin[k] * CELL + min(slot[k], CELL - 1)] = (((dd[k] - bin[k] * NPB) * KN + ss[k]) << 12) + tid * 4 + k;
    }
    if (w == CW) asm volatile("cp.async.wait_all;" ::: "memory");
    bar_sync(1, NT);
    TSTAMP(1);
#pragma unroll
    for (int j = 0; j < 2; j++) {
        const int i = tid + j * NT;
        if (i < NPIECE) {
            const uint2 sa = *(const uint2*)(stage + i * 6), sc = *(const uint2*)(stage + i * 6 + 2), se = *(const uint2*)(stage + i * 6 + 4);
            const uint32_t cn = min(cnt[i >> 3], 255u);
            gs->keys[((i >> 3) * NB + b) * 8 + ((i ^ b) & 7)] =
                make_uint4(__funnelshift_r(sa.x, se.x >> 12, 12), __funnelshift_r(sa.y, __funnelshift_r(se.x, cn, 24), 12),
                           __funnelshift_r(sc.x, se.y >> 12, 12), __funnelshift_r(sc.y, __funnelshift_r(se.y, cn >> 4, 24), 12));
        }
    }
    uint2 yy[7], ee[7];
    uint32_t cno[7];
    uint4* rp = gs->recs + (w * NB + b) * CELL + lane;
    auto recs_out = [&](int j0, int j1) {
#pragma unroll
        for (int j = 0; j < 7; j++) if (j >= j0 && j < j1)
            asm volatile("{.reg .pred p; setp.lt.u32 p, %5, %6; @p st.global.v4.u32 [%0], {%1,%2,%3,%4};}"
                         :: "l"(rp + j * (CW * NB * CELL)), "r"(yy[j].x), "r"(ee[j].x), "r"(yy[j].y), "r"(ee[j].y), "r"(lane & ~1), "r"(cno[j]) : "memory");
    };
    if (w == CW) {
        bar_sync(7, NT);
        if (tid == NT - 1) {
            TSTAMPC(10);
            gbar_arrive(&gs->bar[0]);
            TSTAMPC(11);
            tgt = (tgt / NB + 1) * NB;
            asm volatile("mbarrier.arrive.expect_tx.shared.b64 _, [%0], %1;" :: "r"(mbarK), "r"(NPIECE * 16) : "memory");
            gbar_wait(&gs->bar[0], tgt);
            TSTAMPC(13);
            asm volatile("fence.proxy.async.global;" ::: "memory");
            asm volatile("cp.async.bulk.shared::cluster.global.mbarrier::complete_tx::bytes [%0], [%1], %2, [%3];"
                         :: "r"(sb + SM_KEYS), "l"(gs->keys + b * NPIECE), "r"(NPIECE * 16), "r"(mbarK) : "memory");
        }
        __syncwarp();
        bar_arrive(8, NT);
    } else {
        bar_arrive(7, NT);
        if (w < 8) {
            const uint32_t* wp = (const uint32_t*)(smem + SM_SMALL) + (t & 1) * 128 + 8 * w + g;
            const uint32_t wr0 = t < 2 ? wp[0] : 0, wr1 = t < 2 ? wp[64] : 0;
            *(uint2*)(smem + SM_AZ + (w >> 1) * 512 + lane * 16 + (w & 1) * 8) =
                make_uint2(pack2(0.5f * bf2f(wr0 & 0xFFFF), 0.5f * bf2f(wr1 & 0xFFFF)), pack2(0.5f * bf2f(wr0 >> 16), 0.5f * bf2f(wr1 >> 16)));
        }
        uint32_t el[7], big = 0;
#pragma unroll
        for (int j = 0; j < 7; j++) {
            const int cell = w + CW * j;
            cno[j] = cnt[cell];
            el[j] = (stage[cell * CELL + lane] & 0xFFF) * 8;
            big |= cno[j] > 32;
        }
        mbar_wait(mbarR, 0);
        TSTAMP(18);
#pragma unroll
        for (int j = 0; j < 7; j++) { yy[j] = lds64(sb + SM_RAWY + el[j]); ee[j] = lds64(sb + SM_RAWE + el[j]); }
        if (big) {
#pragma unroll 1
            for (int j = 0; j < 7; j++) {
                const int cell = w + CW * j;
                if (lane + 32 < min(cnt[cell], CELL)) {
                    const uint32_t e2 = (stage[cell * CELL + 32 + lane] & 0xFFF) * 8;
                    const uint2 y2 = *(const uint2*)(smem + SM_RAWY + e2), e3 = *(const uint2*)(smem + SM_RAWE + e2);
                    rp[j * (CW * NB * CELL) + 32] = make_uint4(y2.x, e3.x, y2.y, e3.y);
                }
            }
        }
        bar_sync(8, NT);
        recs_out(0, NB0);
    }
    __syncwarp();
    TSTAMP(2);
    uint32_t at[4];
    {
        const int o = g & 3, f = 2 * (t & 1);
#pragma unroll
        for (int i = 0; i < 4; i++) {
            const uint16_t* cp = (const uint16_t*)(smem + SM_SMALL + 1024) + i * 16 + f * 4 + o;
            at[i] = (t >> 1) == (g >> 2) ? cp[0] | ((uint32_t)cp[4] << 16) : 0;
        }
    }

    uint32_t key[2][6], ha[2][6], rk[2][6], kidx[2];
    int nk[2] = {0, 0};
    if (w < CW) {
        uint32_t ka[2];
#pragma unroll
        for (int j = 0; j < 2; j++) {
            const int i0 = j ? 2 * 608 - 1 - tid : tid, i = min(i0, NPIECE - 1), r = i / NB, c = i - r * NB;
            ka[j] = sb + SM_KEYS + (c * 8 + ((r ^ c) & 7)) * 16;
            kidx[j] = (c * CELL + r * 6) << 17;
            nk[j] = i0 < NPIECE ? -6 * r : -1000;
        }
        mbar_wait(mbarK, 0);
        TSTAMP(3);
        const uint4 v[2] = {lds128(ka[0]), lds128(ka[1])};
#pragma unroll
        for (int j = 0; j < 2; j++) {
            const uint32_t hc = (v[j].y >> 28) | ((v[j].w >> 28) << 4);
            if (j == 0 && tid < NB) cnt2[tid] = hc;
            nk[j] += hc;
            if (nk[j] > 0) {
                key[j][0] = v[j].x & 0xFFFFF; key[j][1] = v[j].y & 0xFFFFF; key[j][2] = v[j].z & 0xFFFFF; key[j][3] = v[j].w & 0xFFFFF;
                key[j][4] = (v[j].x >> 20) | ((v[j].y >> 8) & 0xFF000); key[j][5] = (v[j].z >> 20) | ((v[j].w >> 8) & 0xFF000);
#pragma unroll
                for (int u = 0; u < 6; u++) {
                    ha[j][u] = __umulhi(key[j][u], 0xFFFFFFFFu / KB + 1);
                    rk[j][u] = atomicAdd(&hist[ha[j][u]], 1);
                    atomicAdd(&deg[ha[j][u] >> 5], 128);
                }
            }
        }
        recs_out(NB0, 7);
        bar_sync(10, NT);
        TSTAMP(20);
        const int n = tid >> 3, sub = tid & 7;
        const uint32_t me = deg[n];
        int r = 0;
#pragma unroll
        for (int k = 0; k < 5; k++) { const uint2 dd = *(const uint2*)(deg + sub * 10 + 2 * k); r += (dd.x > me) + (dd.y > me); }
        r += __shfl_xor_sync(0xffffffff, r, 1); r += __shfl_xor_sync(0xffffffff, r, 2); r += __shfl_xor_sync(0xffffffff, r, 4);
        if (sub == 0) order[r] = n;
    } else {
        bar_sync(10, NT);
        if (tid == NT - 1) { TSTAMPC(14); gbar_arrive(&gs->bar[1]); TSTAMPC(15); }
    }
    __syncwarp();
    bar_sync(1, NT);
    TSTAMP(22);
    const uint32_t cn = cnt2[min(w + NW * lane, NB)];
    if (cn > CELL) *flag = 1;
    auto recs_in = [&]() {
        const uint4* gp = gs->recs + (b * NB + w) * CELL + lane;
        const uint32_t sp = sb + SM_RECS + (w * CELL + lane) * 16;
#pragma unroll
        for (int j = 0; j < 7; j++)
            asm volatile("{.reg .pred p; setp.lt.u32 p, %2, %3; @p cp.async.cg.shared.global [%0], [%1], 16;}"
                         :: "r"(sp + j * (NW * CELL * 16)), "l"(gp + j * (NW * CELL)), "r"(lane), "r"(__shfl_sync(0xffffffff, cn, j)) : "memory");
        if (__any_sync(0xffffffff, cn > 32)) {
#pragma unroll 1
            for (int j = 0; j < 7; j++)
                if (lane + 32 < min(__shfl_sync(0xffffffff, cn, j), CELL))
                    asm volatile("cp.async.cg.shared.global [%0], [%1], 16;" :: "r"(sp + j * (NW * CELL * 16) + 512), "l"(gp + j * (NW * CELL) + 32) : "memory");
        }
        asm volatile("cp.async.commit_group;" ::: "memory");
    };
    int S, mylen;
    {
        const uint2 na = *(const uint2*)(order + 2 * w), nb = *(const uint2*)(order + 78 - 2 * w);
        const uint32_t ia0 = na.x * 32 + lane, ib0 = nb.y * 32 + lane, ia1 = na.y * 32 + lane, ib1 = nb.x * 32 + lane;
        const uint32_t ca = hist[ia0] + (hist[ia1] << 16), cab = ca + hist[ib0] + (hist[ib1] << 16);
        uint32_t inc = cab;
#pragma unroll
        for (int o = 1; o < 32; o <<= 1)
            asm volatile("{.reg .pred p; .reg .u32 u; shfl.sync.up.b32 u|p, %0, %1, 0, 0xffffffff; @p add.u32 %0, %0, u;}" : "+r"(inc) : "r"(o));
        const uint32_t ea = inc - cab, eb = ea + ca, base = sb + SM_META + w * (CAP * STEPB);
        uint2* pos = (uint2*)(smem + SM_POS);
        pos[ia0] = make_uint2(base + (ea & 0xFFFF) * 8, na.x * (0u - 4 * KN));
        pos[ib0] = make_uint2(base + (eb & 0xFFFF) * 8, nb.y * (0u - 4 * KN) + 0x10000);
        pos[ia1] = make_uint2(base + 4 + (ea >> 16) * 8, na.y * (0u - 4 * KN));
        pos[ib1] = make_uint2(base + 4 + (eb >> 16) * 8, nb.x * (0u - 4 * KN) + 0x10000);
        const uint32_t len = __shfl_sync(0xffffffff, inc, 31);
        S = (max(len & 0xFFFF, len >> 16) + 3) >> 2;
        mylen = (lane & 1) ? len >> 16 : len & 0xFFFF;
        if (S > CAP) *flag = 1;
        S = __shfl_sync(0xffffffff, max(S, DS), 0);
    }
    bar_sync(1, NT);
    TSTAMP(21);
    if (*flag) {
        slow_path(smem, n0, nn, (const uint16_t*)x, (const int*)src4, (const int*)dst4, (const uint16_t*)Y, (const uint16_t*)ef, w_rad, cg,
                  (const uint16_t*)w_mix, (__nv_bfloat16*)out);
        return;
    }
#pragma unroll
    for (int j = 0; j < 2; j++) {
        if (nk[j] > 0) {
            uint2 h[6];
#pragma unroll
            for (int u = 0; u < 6; u++) h[u] = lds64(sb + SM_POS + ha[j][u] * 8);
#pragma unroll
            for (int u = 0; u < 6; u++)
                asm volatile("{.reg .pred p; setp.gt.s32 p, %2, %3; @p st.shared.u32 [%0], %1;}"
                             :: "r"(h[u].x + rk[j][u] * 8), "r"(key[j][u] * 4 + h[u].y + (kidx[j] + (u << 17))), "r"(nk[j]), "r"(u) : "memory");
        }
    }
    if (tid == NT - 1) { TSTAMPC(16); gbar_wait(&gs->bar[1], tgt); TSTAMPC(17); }
    bar_sync(1, NT);
    TSTAMP(4);
    recs_in();
    constexpr int NRAW = (CAP + 3) / 4;
    uint32_t bits0 = 0, raw[NRAW];
    unsigned char* meta = smem + SM_META + w * (CAP * STEPB);
#pragma unroll
    for (int k = 0; k < NRAW; k++) raw[k] = mylen ? ((uint32_t*)meta)[min(k * 16 + (lane >> 1), mylen - 1) * 2 + (lane & 1)] : 4 * n0;
    const uint32_t sv0 = raw[0] & 0xFFFF;
    const int q = lane >> 3, c = lane & 7;
    const uint32_t ring0 = sb + SM_RING + w * 2048;
    uint32_t wdst = ring0 + q * 128 + ((c + 2 * q) & 7) * 16;
    uint32_t rsrc = ring0 + t * 128 + ((g + 2 * t) & 7) * 16;
    uint32_t recl = sb + SM_META + w * (CAP * STEPB) + g * 16 + (t & 1) * 8, srcl = sb + SM_META + w * (CAP * STEPB) + 128 + q * 8;
    uint32_t flg = sb + SM_MISC + (136 + 104 + 80 + 136) * 4;
    asm volatile("" : "+r"(wdst), "+r"(rsrc), "+r"(recl), "+r"(srcl), "+r"(flg));
    const unsigned char* pbase = x + c * 16;
    auto cpa2 = [&](uint32_t dstp, uint32_t sv) {
        asm volatile("cp.async.cg.shared.global [%0], [%1], 16; cp.async.cg.shared.global [%0+1024], [%1+128], 16;"
                     :: "r"(dstp), "l"(pbase + (size_t)sv * 256) : "memory");
    };
    cpa2(wdst, __shfl_sync(0xffffffff, sv0, 2 * q)); cpa2(wdst + 512, __shfl_sync(0xffffffff, sv0, 2 * q + 1));
    asm volatile("cp.async.commit_group;" ::: "memory");
    TSTAMP(5);
    __syncwarp();
    uint32_t ra[NRAW];
    {
        unsigned char* ms = meta + (q - DS) * STEPB + 128 + c * 4;
#pragma unroll
        for (int k = 0; k < NRAW; k++) {
            if (k == 0) *(uint32_t*)(ms + S * STEPB) = sv0 + F_WRAP;
            else if (k * 4 + q < S) *(uint32_t*)(ms + k * 4 * STEPB) = raw[k] & 0xFFFF;
            const uint32_t m = (__ballot_sync(0xffffffff, raw[k] & 0x10000) >> g) & 0x01010101u;
            bits0 |= ((m * 0x10204080u) >> 28) << (4 * k);
            ra[k] = sb + SM_RECS + (k * 16 + (lane >> 1) < mylen ? raw[k] >> 17 : NB * CELL) * 16;
        }
    }
    if (t < 2) bits0 = ~bits0;
    bits0 = ((bits0 >> 1) & ~(1u << (S - 1))) | ((bits0 & 1) << (S - 1));
    __syncwarp();
    const uint32_t tphase = PACE / 4;
    uint32_t dreg;
    {
        const int st = lane == S ? 0 : min(lane, S - 1);
        const uint4 u0 = *(const uint4*)(meta + st * STEPB + 128), u1 = *(const uint4*)(meta + st * STEPB + 144);
        int pos = (u0.x + u0.y + u0.z + u0.w + u1.x + u1.y + u1.z + u1.w) >> 5;
        pos += ((u0.x & F_WRAP) ? NN : 0) + (lane == S ? NN : 0) - NN * (2 * DS + 1) / 32;
        dreg = pos * (int)tphase / NN;
    }
    asm volatile("cp.async.wait_group 1;" ::: "memory");
    bar_sync(1, NT);
    TSTAMP(19);
    {
        unsigned char* mr = meta + (q - 1) * STEPB + c * 16;
        uint4 rv[NRAW - 1];
#pragma unroll
        for (int k = 0; k < NRAW - 1; k++) rv[k] = lds128(ra[k]);
#pragma unroll
        for (int k = 0; k < NRAW - 1; k++) {
            if (k == 0) *(uint4*)(mr + (q == 0 ? S * STEPB : 0)) = rv[k];
            else if (k * 4 + q < S) *(uint4*)(mr + k * 4 * STEPB) = rv[k];
        }
        if ((NRAW - 1) * 4 + q < S) *(uint4*)(mr + (NRAW - 1) * 4 * STEPB) = lds128(ra[NRAW - 1]);
    }
    unsigned long long tbase = 0;
    if (w == 0) {
        asm volatile("mov.u64 %0, %%globaltimer;" : "=l"(tbase));
        tbase += POFF;
        flag[1] = (uint32_t)tbase; flag[2] = (uint32_t)tbase;
        *(volatile unsigned long long*)(smem + SM_MISC + 1952) = 0;
        if (lane == 0) {
            asm volatile("red.max.relaxed.gpu.global.u64 [%0], %1;" :: "l"(&gs->t0), "l"(tbase) : "memory");
            if (b < 128) asm volatile("cp.async.bulk.prefetch.L2.global [%0], 256;" :: "l"(w_mix + b * 16));
        }
    }
    bar_sync(1, NT);
#pragma unroll
    for (int i = 1; i < DS; i++) {
        cpa2(wdst + i * SLOTB, __shfl_sync(0xffffffff, sv0, 8 * i + 2 * q)); cpa2(wdst + i * SLOTB + 512, __shfl_sync(0xffffffff, sv0, 8 * i + 2 * q + 1));
        asm volatile("cp.async.commit_group;" ::: "memory");
    }
    TSTAMP(6);

    uint32_t* stash = (uint32_t*)(gs->stash + (b * NW + w) * 256) + lane;
    float acc[4][4];
#pragma unroll
    for (int i = 0; i < 16; i++) acc[i / 4][i % 4] = 0.f;
    uint4 az = *(const uint4*)(smem + SM_AZ + lane * 16);
    uint32_t R[4], T[4];
    auto prep = [&](uint2 r, uint32_t mask) {
        float z[4], y[4], t1[4], t2[4];
        mma1688z(z, az.x, az.y, r.y);
        mma1688z(y, az.z, az.w, r.y);
        uint32_t bt;
        asm("{.reg .pred p; .reg .b32 m; and.b32 m, %2, %3; setp.ne.u32 p, m, 0; selp.b32 %0, %1, 0, p;}" : "=r"(bt) : "r"(r.x), "r"(bits0), "r"(mask));
        mma1688z(t1, at[0], at[1], bt);
        mma1688z(t2, at[2], at[3], bt);
        T[0] = pack2(t1[0], t1[2]); T[1] = pack2(t2[0], t2[2]); T[2] = pack2(t1[1], t1[3]); T[3] = pack2(t2[1], t2[3]);
        R[0] = pack2(silu_h(z[0]), silu_h(z[2])); R[1] = pack2(silu_h(z[1]), silu_h(z[3]));
        R[2] = pack2(silu_h(y[0]), silu_h(y[2])); R[3] = pack2(silu_h(y[1]), silu_h(y[3]));
    };
    uint32_t dcur = dreg, dl = 0, now = flag[1], tcur = 0;
    uint32_t mp = 0, smask = 1;
    auto step = [&](const uint32_t off, const int mode) {
        if (mode == 0) asm volatile("mov.u32 %0, %%globaltimer_lo;" : "=r"(now));
        const uint2 r = lds64(mp + recl);
        uint2 s0;
        if (mode == 0) s0 = lds64(mp + srcl);
        asm volatile("cp.async.wait_group %0;" :: "n"(DS - 1) : "memory");
        const uint4 xa = lds128(rsrc + off), xb = lds128(rsrc + off + 512), xc = lds128(rsrc + off + 1024), xd = lds128(rsrc + off + 1536);
        if (mode == 0) {
            dl = __shfl_sync(0xffffffff, dcur, 1); dcur = __shfl_down_sync(0xffffffff, dcur, 1);
            cpa2(wdst + off, s0.x); cpa2(wdst + off + 512, s0.y);
        }
        if (mode == 1 && w < 16) {
#pragma unroll
            for (int j = 0; j < 4; j++) {
                const int kk = 4 * j + q, ch = 16 * (w & 7) + 2 * (kk & 7) + (kk >> 3);
                asm volatile("cp.async.cg.shared.global [%0], [%1], 16;" :: "r"(ring0 + kk * 128 + ((c ^ (kk & 7)) << 4)), "l"(w_mix + ch * 16 + (w >> 3) * 8 + c) : "memory");
            }
        }
        if (mode == 2 || mode == 3) {
#pragma unroll
            for (int j = 0; j < 4; j += mode - 1)
                asm volatile("cp.async.cg.shared.global [%0], [%1], 16;" :: "r"(ring0 + off + j * 512 + lane * 16), "l"(stash + (mode - 2) * 512 + j * 128 + lane * 3) : "memory");
        }
        asm volatile("cp.async.commit_group;" ::: "memory");
        mma16816(acc[0], mul_lo(xa.x, R[0]), mul_hi(xa.z, R[0]), mul_lo(xa.y, R[0]), mul_hi(xa.w, R[0]), T[0], T[1]);
        mma16816(acc[1], mul_lo(xb.x, R[1]), mul_hi(xb.z, R[1]), mul_lo(xb.y, R[1]), mul_hi(xb.w, R[1]), T[2], T[3]);
        mma16816(acc[2], mul_lo(xc.x, R[2]), mul_hi(xc.z, R[2]), mul_lo(xc.y, R[2]), mul_hi(xc.w, R[2]), T[0], T[1]);
        mma16816(acc[3], mul_lo(xd.x, R[3]), mul_hi(xd.z, R[3]), mul_lo(xd.y, R[3]), mul_hi(xd.w, R[3]), T[2], T[3]);
        if (mode != 4) prep(r, smask);
        mp += STEPB; smask <<= 1;
    };
    auto putacc = [&](uint32_t* p) {
        p[0] = pack2(acc[0][0], acc[0][1]); p[32] = pack2(acc[0][2], acc[0][3]); p[64] = pack2(acc[2][0], acc[2][1]); p[96] = pack2(acc[2][2], acc[2][3]);
        p[256] = pack2(acc[1][0], acc[1][1]); p[288] = pack2(acc[1][2], acc[1][3]); p[320] = pack2(acc[3][0], acc[3][1]); p[352] = pack2(acc[3][2], acc[3][3]);
    };
    const uint32_t mlast = (S - 1) * STEPB;
    prep(lds64(mlast + recl), 1u << (S - 1));
    int ph = 0;
    uint32_t mev = mlast;
    auto event = [&]() {
        if (mp == mlast) {
            az = *(const uint4*)(smem + SM_AZ + (ph + 1) * 512 + lane * 16);
            mev += STEPB;
        } else {
            putacc(stash + (ph >> 1) * 512 + (ph & 1) * 128);
#pragma unroll
            for (int i = 0; i < 16; i++) acc[i / 4][i % 4] = 0.f;
            pbase += 256; mp = 0; smask = 1; ph++; mev = mlast;
            dreg += tphase; dcur = dreg + tcur;
            WSTAMP(ph - 1);
        }
    };
    uint32_t t0 = now;
#pragma unroll 1
    for (int it = S - 1; it > 0; it--) {
        if (w == PW) asm volatile("st.shared.u32 [%0+8], %1;" :: "r"(flg), "r"(now - dl + tcur) : "memory");
        dcur += t0 - tcur; tcur = t0;
        if (w == 0) {
            const unsigned long long tglob = *(volatile unsigned long long*)(smem + SM_MISC + 1952);
            const long long dg = tglob - tbase;
            uint32_t t1 = t0;
            if (dg > 0 && dg < 30000 && (int)((uint32_t)tglob - t0) > 0) t1 = (uint32_t)tglob;
            flag[1] = t1;
            const uint32_t cand = flag[2] - PTOL;
            asm volatile("{.reg .pred p, q; setp.eq.u32 p, %2, 0; setp.gt.and.s32 q, %3, 0, p;\n"
                         "@q red.max.relaxed.gpu.global.u64 [%0], %1; @p cp.async.cg.shared.global [%4], [%0], 16;}"
                         :: "l"(&gs->t0), "l"(tbase + (cand - (uint32_t)tbase)), "r"(lane), "r"(cand - t1), "r"(sb + SM_MISC + 1952) : "memory");
        }
#pragma unroll
        for (int k = 0; k < DS; k++) {
            if (k == DS - 1) asm volatile("ld.volatile.shared.u32 %0, [%1+4];" : "=r"(t0) : "r"(flg));
            step(k * SLOTB, 0);
            if (mp == mev || now < dl) {
                if (mp == mev) event();
                asm volatile("{.reg .pred p; .reg .u32 d;\n"
                             "PACE_LOOP: mov.u32 d, %%globaltimer_lo; sub.u32 d, %0, d; setp.lt.u32 p, d, 32768; @p nanosleep.u32 32; @p bra.uni PACE_LOOP;}"
                             :: "r"(dl) : "memory");
            }
        }
    }
    __syncwarp();
    step(0, 1); step(SLOTB, 2); step(2 * SLOTB, 3); step(3 * SLOTB, 4);
    WSTAMP(3);

    {
        putacc((uint32_t*)(smem + SM_RING + 2 * SLOTB + w * 2048 + 512) + lane);
        asm volatile("cp.async.wait_all;" ::: "memory");
        asm volatile("fence.proxy.async.shared::cta;" ::: "memory");
        const int wg = w >> 2, w4 = w & 3;
        TSTAMP(26);
        bar_sync(1, NT);
        TSTAMP(27);
        const uint64_t descA0 = (uint64_t)(((sb + SM_RING) & 0x3FFFF) >> 4) | ((uint64_t)1 << 16) | ((uint64_t)(1024 >> 4) << 32) | ((uint64_t)1 << 62);
        const uint64_t descB0 = (uint64_t)(((sb + SM_RING + SLOTB + wg * 8192) & 0x3FFFF) >> 4) | ((uint64_t)(128 >> 4) << 16) | ((uint64_t)(1024 >> 4) << 32);
        float d[2][32];
        asm volatile("wgmma.fence.sync.aligned;" ::: "memory");
#pragma unroll
        for (int mt = 0; mt < 2; mt++) {
#pragma unroll
            for (int ks = 0; ks < 8; ks++) {
                const uint64_t da = descA0 + (uint64_t)((ks * 2048 + mt * 16384) >> 4), db = descB0 + (uint64_t)(((ks & 3) * 256 + (ks >> 2) * SLOTB) >> 4);
                asm volatile("{.reg .pred p; setp.ne.b32 p, %34, 0;\n"
                    "wgmma.mma_async.sync.aligned.m64n64k16.f32.bf16.bf16 "
                    "{%0,%1,%2,%3,%4,%5,%6,%7,%8,%9,%10,%11,%12,%13,%14,%15,%16,%17,%18,%19,%20,%21,%22,%23,%24,%25,%26,%27,%28,%29,%30,%31}, %32, %33, p, 1, 1, 1, 1;}"
                    : "+f"(d[mt][0]), "+f"(d[mt][1]), "+f"(d[mt][2]), "+f"(d[mt][3]), "+f"(d[mt][4]), "+f"(d[mt][5]), "+f"(d[mt][6]), "+f"(d[mt][7]),
                      "+f"(d[mt][8]), "+f"(d[mt][9]), "+f"(d[mt][10]), "+f"(d[mt][11]), "+f"(d[mt][12]), "+f"(d[mt][13]), "+f"(d[mt][14]), "+f"(d[mt][15]),
                      "+f"(d[mt][16]), "+f"(d[mt][17]), "+f"(d[mt][18]), "+f"(d[mt][19]), "+f"(d[mt][20]), "+f"(d[mt][21]), "+f"(d[mt][22]), "+f"(d[mt][23]),
                      "+f"(d[mt][24]), "+f"(d[mt][25]), "+f"(d[mt][26]), "+f"(d[mt][27]), "+f"(d[mt][28]), "+f"(d[mt][29]), "+f"(d[mt][30]), "+f"(d[mt][31])
                    : "l"(da), "l"(db), "r"(ks));
            }
            asm volatile("wgmma.commit_group.sync.aligned;" ::: "memory");
        }
        int nd[8];
#pragma unroll
        for (int j = 0; j < 8; j++) { const int l = wg * 8 + j; nd[j] = order[(t >> 1) ? 79 - l : l]; }
        const bool odd = t & 1;
        uint2* ob = (uint2*)out + (size_t)n0 * 128 + w4 * 16 + g + (odd ? 8 : 0);
#pragma unroll
        for (int mt = 0; mt < 2; mt++) {
            if (mt == 0) asm volatile("wgmma.wait_group.sync.aligned 1;" ::: "memory");
            else asm volatile("wgmma.wait_group.sync.aligned 0;" ::: "memory");
#pragma unroll
            for (int i = 0; i < 32; i++) asm volatile("" : "+f"(d[mt][i]) :: "memory");
#pragma unroll
            for (int j = 0; j < 8; j++) {
                const uint32_t v0 = pack2(d[mt][4 * j], d[mt][4 * j + 1]), v1 = pack2(d[mt][4 * j + 2], d[mt][4 * j + 3]);
                const uint32_t rv = __shfl_xor_sync(0xffffffff, odd ? v0 : v1, 1);
                if (nd[j] < nn) ob[nd[j] * 128 + mt * 64] = odd ? make_uint2(rv, v1) : make_uint2(v0, rv);
            }
        }
    }
    TSTAMP(8);
}

}

extern "C" void kernel_launch(void* const* d_in, const int* in_sizes, int n_in, void* d_out, int out_size) {
    (void)in_sizes; (void)n_in; (void)out_size;
    cudaFuncSetAttribute(tfn_kernel, cudaFuncAttributeMaxDynamicSharedMemorySize, SM_TOTAL);
    Scratch* gs = nullptr;
    cudaGetSymbolAddress((void**)&gs, g_scratch);
    cudaLaunchConfig_t cfg = {};
    cfg.gridDim = dim3(NB); cfg.blockDim = dim3(NT); cfg.dynamicSmemBytes = SM_TOTAL; cfg.stream = cudaStreamPerThread;
    cudaLaunchAttribute at[1];
    at[0].id = cudaLaunchAttributeCooperative; at[0].val.cooperative = 1;
    cfg.attrs = at; cfg.numAttrs = 1;
    cudaLaunchKernelEx(&cfg, tfn_kernel, (const unsigned char*)d_in[0], (const int4*)d_in[1], (const int4*)d_in[2],
                       (const uint4*)d_in[3], (const uint4*)d_in[4], (const uint16_t*)d_in[5], (const uint16_t*)d_in[6],
                       (const uint4*)d_in[7], (uint32_t*)d_out, gs);
}
```

```cpp
#include <cuda_runtime.h>
#include <cuda_bf16.h>
#include <stdint.h>

#define ABL 0
namespace {

constexpr int NN = 10000;
constexpr int NE = 320000;
constexpr int NB = 132;
constexpr int NW = 20;
constexpr int NT = NW * 32;
constexpr int CW = NW - 1;
constexpr int PW = 10;
constexpr int NPB = 76;
constexpr int CELL = 48;
constexpr int CAP = 19;
constexpr int DS = 4;
constexpr int STEPB = 160;
constexpr int NE4 = NE / 4;
constexpr int NPIECE = NB * 8;
constexpr int KB = 320, KN = 32 * KB;
constexpr uint32_t F_WRAP = 1;

constexpr int SLOTB = NW * 2048;
constexpr int SM_RING = 0;
constexpr int SM_META = SM_RING + DS * SLOTB;
constexpr int SM_AZ = SM_META + NW * CAP * STEPB;
constexpr int SM_MISC = SM_AZ + 2048;
constexpr int SM_TOTAL = SM_MISC + 2560;
constexpr int SM_STAGE = SM_RING;
constexpr int SM_HIST = SM_RING + 25600;
constexpr int SM_POS = SM_RING;
constexpr int SM_SMALL = SM_HIST + 13056;
constexpr int SM_LIST = SM_RING + 2 * SLOTB;
constexpr int SM_RECS = SM_RING + 3 * SLOTB;
constexpr int SM_RAWY = SM_META;
constexpr int SM_RAWE = SM_RAWY + 608 * 32;
constexpr int SM_KEYS = SM_RAWE + 608 * 32;
static_assert(SM_TOTAL <= 232448 && SM_KEYS + NPIECE * 16 <= SM_AZ, "smem");
static_assert(SM_RECS + NB * CELL * 16 + 16 <= SM_AZ && SM_KEYS + NPIECE * 16 <= SM_RECS + NB * CELL * 16 && SM_SMALL + 1152 <= SLOTB && DS == 4, "smem");

struct Scratch {
    uint4 keys[NB * NPIECE];
    uint4 recs[NB * NB * CELL];
    uint4 stash[NB * NW * 256];
    unsigned bar[4];
    unsigned long long t0, pad;
};
__device__ Scratch g_scratch;
#define TSTAMP(i)
#define TSTAMPC(i)
#define WSTAMP(i)

__device__ __forceinline__ void mma16816(float* d, uint32_t a0, uint32_t a1, uint32_t a2, uint32_t a3, uint32_t b0, uint32_t b1) {
    asm("mma.sync.aligned.m16n8k16.row.col.f32.bf16.bf16.f32 {%0,%1,%2,%3}, {%4,%5,%6,%7}, {%8,%9}, {%0,%1,%2,%3};"
        : "+f"(d[0]), "+f"(d[1]), "+f"(d[2]), "+f"(d[3]) : "r"(a0), "r"(a1), "r"(a2), "r"(a3), "r"(b0), "r"(b1));
}
__device__ __forceinline__ void mma1688z(float* d, uint32_t a0, uint32_t a1, uint32_t b0) {
    asm("mma.sync.aligned.m16n8k8.row.col.f32.bf16.bf16.f32 {%0,%1,%2,%3}, {%4,%5}, {%6}, {%7,%7,%7,%7};"
        : "=f"(d[0]), "=f"(d[1]), "=f"(d[2]), "=f"(d[3]) : "r"(a0), "r"(a1), "r"(b0), "f"(0.f));
}
__device__ __forceinline__ uint32_t pack2(float lo, float hi) {
    uint32_t r; asm("cvt.rn.bf16x2.f32 %0, %1, %2;" : "=r"(r) : "f"(hi), "f"(lo)); return r;
}
__device__ __forceinline__ float silu_h(float h) {
    float t; asm("tanh.approx.f32 %0, %1;" : "=f"(t) : "f"(h)); return fmaf(h, t, h);
}
__device__ __forceinline__ uint32_t mul_lo(uint32_t v, uint32_t r) {
    __nv_bfloat162 a = *(__nv_bfloat162*)&v, b = *(__nv_bfloat162*)&r; __nv_bfloat162 c = __hmul2(a, __low2bfloat162(b)); return *(uint32_t*)&c;
}
__device__ __forceinline__ uint32_t mul_hi(uint32_t v, uint32_t r) {
    __nv_bfloat162 a = *(__nv_bfloat162*)&v, b = *(__nv_bfloat162*)&r; __nv_bfloat162 c = __hmul2(a, __high2bfloat162(b)); return *(uint32_t*)&c;
}
__device__ __forceinline__ uint2 lds64(uint32_t a) {
    uint2 r; asm volatile("ld.shared.v2.u32 {%0,%1}, [%2];" : "=r"(r.x), "=r"(r.y) : "r"(a)); return r;
}
__device__ __forceinline__ uint4 lds128(uint32_t a) {
    uint4 r; asm volatile("ld.shared.v4.u32 {%0,%1,%2,%3}, [%4];" : "=r"(r.x), "=r"(r.y), "=r"(r.z), "=r"(r.w) : "r"(a) : "memory"); return r;
}
__device__ __forceinline__ void bar_sync(int id, int n) { asm volatile("bar.sync %0, %1;" :: "r"(id), "r"(n) : "memory"); }
__device__ __forceinline__ void bar_arrive(int id, int n) { asm volatile("bar.arrive %0, %1;" :: "r"(id), "r"(n) : "memory"); }
__device__ __forceinline__ void mbar_wait(uint32_t bar, uint32_t ph) {
    uint32_t done; int spins = 0;
    do {
        asm volatile("{.reg .pred p; mbarrier.try_wait.parity.shared.b64 p, [%1], %2; selp.u32 %0,1,0,p;}" : "=r"(done) : "r"(bar), "r"(ph) : "memory");
    } while (!done && ++spins < (1 << 22));
}
__device__ __forceinline__ unsigned gbar_read(const unsigned* ctr) {
    unsigned v; asm volatile("ld.relaxed.gpu.global.u32 %0, [%1];" : "=r"(v) : "l"(ctr) : "memory");
    return v;
}
__device__ __forceinline__ void gbar_arrive(unsigned* ctr) {
    asm volatile("red.add.release.gpu.global.u32 [%0], 1;" :: "l"(ctr) : "memory");
}
__device__ __forceinline__ void gbar_wait(const unsigned* ctr, unsigned target) {
    unsigned v; int spins = 0;
    do { asm volatile("ld.acquire.gpu.global.u32 %0, [%1];" : "=r"(v) : "l"(ctr) : "memory"); } while ((int)(v - target) < 0 && ++spins < (1 << 22));
}
__device__ __forceinline__ int chunk_start4(int c) { return (c * NE4) / NB; }
__device__ __forceinline__ float bf2f(uint32_t h) { return __uint_as_float(h << 16); }

__device__ __noinline__ void slow_path(unsigned char* smem, int n0, int nn, const uint16_t* x, const int* src, const int* dst,
                                       const uint16_t* Y, const uint16_t* ef, const uint16_t* w_rad, const uint16_t* cg,
                                       const uint16_t* w_mix, __nv_bfloat16* out) {
    float* agg = (float*)smem;
    const int tid = threadIdx.x, lane = tid & 31, w = tid >> 5;
    bar_sync(1, NT);
    for (int i = tid; i < NPB * 512; i += NT) agg[i] = 0.f;
    bar_sync(1, NT);
    for (int e0 = w * 32; e0 < NE; e0 += NT) {
        int dl = dst[e0 + lane] - n0;
        unsigned m = __ballot_sync(0xffffffff, dl >= 0 && dl < nn);
        while (m) {
            int l = __ffs(m) - 1; m &= m - 1;
            int e = e0 + l, d = __shfl_sync(0xffffffff, dl, l), s = src[e];
            float T[16];
            for (int i = 0; i < 4; i++) for (int o = 0; o < 4; o++) {
                float a = 0.f;
                for (int f = 0; f < 4; f++) a += bf2f(Y[e * 4 + f]) * bf2f(cg[i * 16 + f * 4 + o]);
                T[i * 4 + o] = a;
            }
            for (int k = 0; k < 4; k++) {
                int c = lane + 32 * k;
                float z = 0.f;
                for (int j = 0; j < 4; j++) z += bf2f(ef[e * 4 + j]) * bf2f(w_rad[j * 128 + c]);
                float R = z / (1.f + __expf(-z));
                for (int o = 0; o < 4; o++) {
                    float a = 0.f;
                    for (int i = 0; i < 4; i++) a += bf2f(x[(size_t)s * 512 + c * 4 + i]) * T[i * 4 + o];
                    atomicAdd(&agg[d * 512 + c * 4 + o], R * a);
                }
            }
        }
    }
    bar_sync(1, NT);
    for (int i = tid; i < nn * 512; i += NT) {
        int n = i >> 9, d = (i >> 2) & 127, o = i & 3;
        float a = 0.f;
        for (int c = 0; c < 128; c++) a += agg[n * 512 + c * 4 + o] * bf2f(w_mix[c * 128 + d]);
        out[(size_t)(n0 + n) * 512 + (i & 511)] = __float2bfloat16(a);
    }
}

#define PACE 24500
#define YDELAY 300
#define NB0 4
#define MATCH 0
#define POFF 1800
#define PTOL 600
__global__ void __launch_bounds__(NT, 1)
tfn_kernel(const unsigned char* __restrict__ x, const int4* __restrict__ src4, const int4* __restrict__ dst4,
           const uint4* __restrict__ Y, const uint4* __restrict__ ef, const uint16_t* __restrict__ w_rad,
           const uint16_t* __restrict__ cg, const uint4* __restrict__ w_mix, uint32_t* __restrict__ out, Scratch* __restrict__ gs) {
    extern __shared__ __align__(1024) unsigned char smem[];
    const uint32_t sb = (uint32_t)__cvta_generic_to_shared(smem);
    const int b = blockIdx.x, tid = threadIdx.x, lane = tid & 31, g = lane >> 2, t = lane & 3;
    const int w = __shfl_sync(0xffffffff, tid >> 5, 0);
    uint32_t* stage = (uint32_t*)(smem + SM_STAGE);
    uint32_t* hist = (uint32_t*)(smem + SM_HIST);
    uint32_t* cnt = (uint32_t*)(smem + SM_MISC);
    uint32_t* deg = cnt + 136;
    uint32_t* order = deg + 104;
    uint32_t* cnt2 = order + 80;
    volatile uint32_t* flag = cnt2 + 136;
    const uint32_t mbarK = sb + SM_MISC + 1920, mbarR = mbarK + 8;
    const int n0 = b * NPB, nn = min(NPB, NN - n0);
    TSTAMP(0);

    const int c0 = chunk_start4(b), c1 = chunk_start4(b + 1);
    const bool has4 = c0 + tid < c1;
    int4 d4 = make_int4(0, 0, 0, 0), s4 = d4;
    if (has4) { d4 = __ldg(dst4 + c0 + tid); s4 = __ldg(src4 + c0 + tid); }
    unsigned tgt = 0;
    if (tid == NT - 1) {
        tgt = gbar_read(&gs->bar[0]);
        asm volatile("mbarrier.init.shared.b64 [%0], 1;" :: "r"(mbarK));
        asm volatile("mbarrier.init.shared.b64 [%0], 1;" :: "r"(mbarR));
        asm volatile("fence.mbarrier_init.release.cluster;" ::: "memory");
        *flag = 0;
    }
    if (w == CW) {
        asm volatile("cp.async.cg.shared.global [%0], [%1], 16;" :: "r"(sb + SM_SMALL + lane * 16), "l"(w_rad + lane * 8) : "memory");
        asm volatile("cp.async.cg.shared.global [%0], [%1], 16;" :: "r"(sb + SM_SMALL + 512 + lane * 16), "l"(w_rad + 256 + lane * 8) : "memory");
        if (lane < 8) asm volatile("cp.async.cg.shared.global [%0], [%1], 16;" :: "r"(sb + SM_SMALL + 1024 + lane * 16), "l"(cg + lane * 8) : "memory");
    }
    ((uint4*)hist)[tid] = make_uint4(0, 0, 0, 0);
    {
        const uint32_t dk = ((80 + b % 22) * KN + (b & 31) * KB) << 12;
#pragma unroll
        for (int j = 0; j < 3; j++) if (tid + j * NT < NB * CELL / 4) ((uint4*)stage)[tid + j * NT] = make_uint4(dk, dk, dk, dk);
    }
    if (tid < 136) cnt[tid] = 0;
    if (tid == 0) { *(uint4*)(smem + SM_MISC + 1824 + 32) = make_uint4(0, 0, 0, 0); cnt2[NB] = 0; *(uint4*)(smem + SM_RECS + NB * CELL * 16) = make_uint4(0, 0, 0, 0); }
    if (tid < 80) { deg[tid] = 127 - tid; order[tid] = tid; }
    __syncthreads();
    TSTAMP(9);
    if (tid == 64) {
        if (YDELAY) __nanosleep(YDELAY);
        asm volatile("mbarrier.arrive.expect_tx.shared.b64 _, [%0], %1;" :: "r"(mbarR), "r"((c1 - c0) * 64) : "memory");
        asm volatile("cp.async.bulk.shared::cluster.global.mbarrier::complete_tx::bytes [%0], [%1], %2, [%3];"
                     :: "r"(sb + SM_RAWY), "l"(Y + 2 * c0), "r"((c1 - c0) * 32), "r"(mbarR) : "memory");
        asm volatile("cp.async.bulk.shared::cluster.global.mbarrier::complete_tx::bytes [%0], [%1], %2, [%3];"
                     :: "r"(sb + SM_RAWE), "l"(ef + 2 * c0), "r"((c1 - c0) * 32), "r"(mbarR) : "memory");
    }

    if (has4) {
        const uint32_t dd[4] = {(uint32_t)d4.x, (uint32_t)d4.y, (uint32_t)d4.z, (uint32_t)d4.w}, ss[4] = {(uint32_t)s4.x, (uint32_t)s4.y, (uint32_t)s4.z, (uint32_t)s4.w};
        uint32_t bin[4], slot[4];
#pragma unroll
        for (int k = 0; k < 4; k++) { bin[k] = dd[k] / NPB; slot[k] = atomicAdd(&cnt[bin[k]], 1); }
#pragma unroll
        for (int k = 0; k < 4; k++)
            stage[bin[k] * CELL + min(slot[k], CELL - 1)] = (((dd[k] - bin[k] * NPB) * KN + ss[k]) << 12) + tid * 4 + k;
    }
    if (w == CW) asm volatile("cp.async.wait_all;" ::: "memory");
    bar_sync(1, NT);
    TSTAMP(1);
#pragma unroll
    for (int j = 0; j < 2; j++) {
        const int i = tid + j * NT;
        if (i < NPIECE) {
            const uint2 sa = *(const uint2*)(stage + i * 6), sc = *(const uint2*)(stage + i * 6 + 2), se = *(const uint2*)(stage + i * 6 + 4);
            const uint32_t cn = min(cnt[i >> 3], 255u);
            gs->keys[((i >> 3) * NB + b) * 8 + ((i ^ b) & 7)] =
                make_uint4(__funnelshift_r(sa.x, se.x >> 12, 12), __funnelshift_r(sa.y, __funnelshift_r(se.x, cn, 24), 12),
                           __funnelshift_r(sc.x, se.y >> 12, 12), __funnelshift_r(sc.y, __funnelshift_r(se.y, cn >> 4, 24), 12));
        }
    }
    uint2 yy[7], ee[7];
    uint32_t cno[7];
    uint4* rp = gs->recs + (w * NB + b) * CELL + lane;
    auto recs_out = [&](int j0, int j1) {
#pragma unroll
        for (int j = 0; j < 7; j++) if (j >= j0 && j < j1)
            asm volatile("{.reg .pred p; setp.lt.u32 p, %5, %6; @p st.global.v4.u32 [%0], {%1,%2,%3,%4};}"
                         :: "l"(rp + j * (CW * NB * CELL)), "r"(yy[j].x), "r"(ee[j].x), "r"(yy[j].y), "r"(ee[j].y), "r"(lane & ~1), "r"(cno[j]) : "memory");
    };
    if (w == CW) {
        bar_sync(7, NT);
        if (tid == NT - 1) {
            TSTAMPC(10);
            gbar_arrive(&gs->bar[0]);
            TSTAMPC(11);
            tgt = (tgt / NB + 1) * NB;
            asm volatile("mbarrier.arrive.expect_tx.shared.b64 _, [%0], %1;" :: "r"(mbarK), "r"(NPIECE * 16) : "memory");
            gbar_wait(&gs->bar[0], tgt);
            TSTAMPC(13);
            asm volatile("fence.proxy.async.global;" ::: "memory");
            asm volatile("cp.async.bulk.shared::cluster.global.mbarrier::complete_tx::bytes [%0], [%1], %2, [%3];"
                         :: "r"(sb + SM_KEYS), "l"(gs->keys + b * NPIECE), "r"(NPIECE * 16), "r"(mbarK) : "memory");
        }
        __syncwarp();
        bar_arrive(8, NT);
    } else {
        bar_arrive(7, NT);
        if (w < 8) {
            const uint32_t* wp = (const uint32_t*)(smem + SM_SMALL) + (t & 1) * 128 + 8 * w + g;
            const uint32_t wr0 = t < 2 ? wp[0] : 0, wr1 = t < 2 ? wp[64] : 0;
            *(uint2*)(smem + SM_AZ + (w >> 1) * 512 + lane * 16 + (w & 1) * 8) =
                make_uint2(pack2(0.5f * bf2f(wr0 & 0xFFFF), 0.5f * bf2f(wr1 & 0xFFFF)), pack2(0.5f * bf2f(wr0 >> 16), 0.5f * bf2f(wr1 >> 16)));
        }
        uint32_t el[7], big = 0;
#pragma unroll
        for (int j = 0; j < 7; j++) {
            const int cell = w + CW * j;
            cno[j] = cnt[cell];
            el[j] = (stage[cell * CELL + lane] & 0xFFF) * 8;
            big |= cno[j] > 32;
        }
        mbar_wait(mbarR, 0);
        TSTAMP(18);
#pragma unroll
        for (int j = 0; j < 7; j++) { yy[j] = lds64(sb + SM_RAWY + el[j]); ee[j] = lds64(sb + SM_RAWE + el[j]); }
        if (big) {
#pragma unroll 1
            for (int j = 0; j < 7; j++) {
                const int cell = w + CW * j;
                if (lane + 32 < min(cnt[cell], CELL)) {
                    const uint32_t e2 = (stage[cell * CELL + 32 + lane] & 0xFFF) * 8;
                    const uint2 y2 = *(const uint2*)(smem + SM_RAWY + e2), e3 = *(const uint2*)(smem + SM_RAWE + e2);
                    rp[j * (CW * NB * CELL) + 32] = make_uint4(y2.x, e3.x, y2.y, e3.y);
                }
            }
        }
        bar_sync(8, NT);
        recs_out(0, NB0);
    }
    __syncwarp();
    TSTAMP(2);
    uint32_t at[4];
    {
        const int o = g & 3, f = 2 * (t & 1);
#pragma unroll
        for (int i = 0; i < 4; i++) {
            const uint16_t* cp = (const uint16_t*)(smem + SM_SMALL + 1024) + i * 16 + f * 4 + o;
            at[i] = (t >> 1) == (g >> 2) ? cp[0] | ((uint32_t)cp[4] << 16) : 0;
        }
    }

    uint32_t key[2][6], ha[2][6], rk[2][6], kidx[2];
    int nk[2] = {0, 0};
    unsigned seenB = 0;
    if (w < CW) {
        uint32_t ka[2];
#pragma unroll
        for (int j = 0; j < 2; j++) {
            const int i0 = j ? 2 * 608 - 1 - tid : tid, i = min(i0, NPIECE - 1), r = i / NB, c = i - r * NB;
            ka[j] = sb + SM_KEYS + (c * 8 + ((r ^ c) & 7)) * 16;
            kidx[j] = (c * CELL + r * 6) << 17;
            nk[j] = i0 < NPIECE ? -6 * r : -1000;
        }
        mbar_wait(mbarK, 0);
        TSTAMP(3);
        const uint4 v[2] = {lds128(ka[0]), lds128(ka[1])};
#pragma unroll
        for (int j = 0; j < 2; j++) {
            const uint32_t hc = (v[j].y >> 28) | ((v[j].w >> 28) << 4);
            if (j == 0 && tid < NB) cnt2[tid] = hc;
            nk[j] += hc;
            if (nk[j] > 0) {
                key[j][0] = v[j].x & 0xFFFFF; key[j][1] = v[j].y & 0xFFFFF; key[j][2] = v[j].z & 0xFFFFF; key[j][3] = v[j].w & 0xFFFFF;
                key[j][4] = (v[j].x >> 20) | ((v[j].y >> 8) & 0xFF000); key[j][5] = (v[j].z >> 20) | ((v[j].w >> 8) & 0xFF000);
#pragma unroll
                for (int u = 0; u < 6; u++) {
                    ha[j][u] = __umulhi(key[j][u], 0xFFFFFFFFu / KB + 1);
                    rk[j][u] = atomicAdd(&hist[ha[j][u]], 1);
                    atomicAdd(&deg[ha[j][u] >> 5], 128);
                }
            }
        }
        recs_out(NB0, 7);
        bar_sync(10, NT);
        TSTAMP(20);
        const int n = tid >> 3, sub = tid & 7;
        const uint32_t me = deg[n];
        int r = 0;
#pragma unroll
        for (int k = 0; k < 5; k++) { const uint2 dd = *(const uint2*)(deg + sub * 10 + 2 * k); r += (dd.x > me) + (dd.y > me); }
        r += __shfl_xor_sync(0xffffffff, r, 1); r += __shfl_xor_sync(0xffffffff, r, 2); r += __shfl_xor_sync(0xffffffff, r, 4);
        if (sub == 0) order[r] = n;
    } else {
        bar_sync(10, NT);
        if (tid == NT - 1) { TSTAMPC(14); gbar_arrive(&gs->bar[1]); TSTAMPC(15); seenB = gbar_read(&gs->bar[1]); }
    }
    __syncwarp();
    bar_sync(1, NT);
    TSTAMP(22);
    const uint32_t cn = cnt2[min(w + NW * lane, NB)];
    if (cn > CELL) *flag = 1;
    auto recs_in = [&]() {
        const uint4* gp = gs->recs + (b * NB + w) * CELL + lane;
        const uint32_t sp = sb + SM_RECS + (w * CELL + lane) * 16;
#pragma unroll
        for (int j = 0; j < 7; j++)
            asm volatile("{.reg .pred p; setp.lt.u32 p, %2, %3; @p cp.async.cg.shared.global [%0], [%1], 16;}"
                         :: "r"(sp + j * (NW * CELL * 16)), "l"(gp + j * (NW * CELL)), "r"(lane), "r"(__shfl_sync(0xffffffff, cn, j)) : "memory");
        if (__any_sync(0xffffffff, cn > 32)) {
#pragma unroll 1
            for (int j = 0; j < 7; j++)
                if (lane + 32 < min(__shfl_sync(0xffffffff, cn, j), CELL))
                    asm volatile("cp.async.cg.shared.global [%0], [%1], 16;" :: "r"(sp + j * (NW * CELL * 16) + 512), "l"(gp + j * (NW * CELL) + 32) : "memory");
        }
        asm volatile("cp.async.commit_group;" ::: "memory");
    };
    int S, mylen;
    {
        const uint2 na = *(const uint2*)(order + 2 * w), nb = *(const uint2*)(order + 78 - 2 * w);
        const uint32_t ia0 = na.x * 32 + lane, ib0 = nb.y * 32 + lane, ia1 = na.y * 32 + lane, ib1 = nb.x * 32 + lane;
        const uint32_t ca = hist[ia0] + (hist[ia1] << 16), cab = ca + hist[ib0] + (hist[ib1] << 16);
        uint32_t inc = cab;
#pragma unroll
        for (int o = 1; o < 32; o <<= 1)
            asm volatile("{.reg .pred p; .reg .u32 u; shfl.sync.up.b32 u|p, %0, %1, 0, 0xffffffff; @p add.u32 %0, %0, u;}" : "+r"(inc) : "r"(o));
        const uint32_t ea = inc - cab, eb = ea + ca, base = sb + SM_LIST + w * 2048;
        uint2* pos = (uint2*)(smem + SM_POS);
        pos[ia0] = make_uint2(base + (ea & 0xFFFF) * 8, na.x * (0u - 4 * KN));
        pos[ib0] = make_uint2(base + (eb & 0xFFFF) * 8, nb.y * (0u - 4 * KN) + 0x10000);
        pos[ia1] = make_uint2(base + 4 + (ea >> 16) * 8, na.y * (0u - 4 * KN));
        pos[ib1] = make_uint2(base + 4 + (eb >> 16) * 8, nb.x * (0u - 4 * KN) + 0x10000);
        const uint32_t len = __shfl_sync(0xffffffff, inc, 31);
        S = (max(len & 0xFFFF, len >> 16) + 3) >> 2;
        mylen = (lane & 1) ? len >> 16 : len & 0xFFFF;
        if (S > CAP) *flag = 1;
        S = __shfl_sync(0xffffffff, max(S, DS + 1), 0);
    }
    if (tid == NT - 1) {
        TSTAMPC(16);
        if ((int)(seenB - tgt) < 0) gbar_wait(&gs->bar[1], tgt);
        else asm volatile("fence.acq_rel.cta;" ::: "memory");
        TSTAMPC(17);
    }
    bar_sync(1, NT);
    TSTAMP(21);
    if (*flag) {
        slow_path(smem, n0, nn, (const uint16_t*)x, (const int*)src4, (const int*)dst4, (const uint16_t*)Y, (const uint16_t*)ef, w_rad, cg,
                  (const uint16_t*)w_mix, (__nv_bfloat16*)out);
        return;
    }
    recs_in();
#pragma unroll
    for (int j = 0; j < 2; j++) {
        if (nk[j] > 0) {
            uint2 h[6];
#pragma unroll
            for (int u = 0; u < 6; u++) h[u] = lds64(sb + SM_POS + ha[j][u] * 8);
#pragma unroll
            for (int u = 0; u < 6; u++)
                asm volatile("{.reg .pred p; setp.gt.s32 p, %2, %3; @p st.shared.u32 [%0], %1;}"
                             :: "r"(h[u].x + rk[j][u] * 8), "r"(key[j][u] * 4 + h[u].y + (kidx[j] + (u << 17))), "r"(nk[j]), "r"(u) : "memory");
        }
    }
    bar_sync(1, NT);
    TSTAMP(4);
    constexpr int NRAW = (CAP + 3) / 4;
    uint32_t bits0 = 0, raw[NRAW];
    unsigned char* meta = smem + SM_META + w * (CAP * STEPB);
#pragma unroll
    for (int k = 0; k < NRAW; k++) raw[k] = mylen ? ((uint32_t*)(smem + SM_LIST + w * 2048))[min(k * 16 + (lane >> 1), mylen - 1) * 2 + (lane & 1)] : 4 * n0;
    const uint32_t sv0 = raw[0] & 0xFFFF;
    const int q = lane >> 3, c = lane & 7;
    const uint32_t ring0 = sb + SM_RING + w * 2048;
    uint32_t wdst = ring0 + q * 128 + ((c + 2 * q) & 7) * 16;
    uint32_t rsrc = ring0 + t * 128 + ((g + 2 * t) & 7) * 16;
    uint32_t recl = sb + SM_META + w * (CAP * STEPB) + g * 16 + (t & 1) * 8, srcl = sb + SM_META + w * (CAP * STEPB) + 128 + q * 8;
    uint32_t flg = sb + SM_MISC + (136 + 104 + 80 + 136) * 4;
    asm volatile("" : "+r"(wdst), "+r"(rsrc), "+r"(recl), "+r"(srcl), "+r"(flg));
    const unsigned char* pbase = x + c * 16;
    auto cpa2 = [&](uint32_t dstp, uint32_t sv) {
        asm volatile("cp.async.cg.shared.global [%0], [%1], 16; cp.async.cg.shared.global [%0+1024], [%1+128], 16;"
                     :: "r"(dstp), "l"(pbase + (size_t)sv * 256) : "memory");
    };
    auto fill = [&](int i) {
        cpa2(wdst + i * SLOTB, __shfl_sync(0xffffffff, sv0, 8 * i + 2 * q)); cpa2(wdst + i * SLOTB + 512, __shfl_sync(0xffffffff, sv0, 8 * i + 2 * q + 1));
        asm volatile("cp.async.commit_group;" ::: "memory");
    };
    fill(0);
    TSTAMP(5);
    if (w == 0) {
        unsigned long long tbase;
        asm volatile("mov.u64 %0, %%globaltimer;" : "=l"(tbase));
        tbase += POFF;
        flag[1] = (uint32_t)tbase; flag[2] = (uint32_t)tbase; flag[4] = (uint32_t)tbase; flag[5] = (uint32_t)(tbase >> 32);
        if (lane == 0) {
            asm volatile("red.max.relaxed.gpu.global.u64 [%0], %1;" :: "l"(&gs->t0), "l"(tbase) : "memory");
            if (b < 128) asm volatile("cp.async.bulk.prefetch.L2.global [%0], 256;" :: "l"(w_mix + b * 16));
        }
    }
    uint32_t ra[NRAW];
#pragma unroll
    for (int k = 0; k < NRAW; k++) {
        const uint32_t m = (__ballot_sync(0xffffffff, raw[k] & 0x10000) >> g) & 0x01010101u;
        bits0 |= ((m * 0x10204080u) >> 28) << (4 * k);
        ra[k] = sb + SM_RECS + (k * 16 + (lane >> 1) < mylen ? raw[k] >> 17 : NB * CELL) * 16;
    }
    if (t < 2) bits0 = ~bits0;
    fill(1);
    asm volatile("cp.async.wait_group 2;" ::: "memory");
    bar_sync(1, NT);
    TSTAMP(19);
    {
        uint4 rv[NRAW];
#pragma unroll
        for (int k = 0; k < NRAW - 1; k++) rv[k] = lds128(ra[k]);
        if ((NRAW - 1) * 4 < S) rv[NRAW - 1] = lds128(ra[NRAW - 1]);
        if (tid == 0) asm volatile("cp.async.cg.shared.global [%0], [%1], 16;" :: "r"(sb + SM_MISC + 1824 + 32), "l"(&gs->t0) : "memory");
        fill(2);
        bar_sync(1, NT);
        TSTAMP(12);
        unsigned char* mr = meta + (q - 1) * STEPB + c * 16;
        unsigned char* ms = meta + (q - DS - 1) * STEPB + 128 + c * 4;
#pragma unroll
        for (int k = 0; k < NRAW; k++) {
            if (k == 0) {
                *(uint4*)(mr + (q == 0 ? S * STEPB : 0)) = rv[k];
                *(uint32_t*)(ms + S * STEPB) = sv0 + F_WRAP;
            } else if (k * 4 + q < S) {
                *(uint4*)(mr + k * 4 * STEPB) = rv[k];
                *(uint32_t*)(ms + k * 4 * STEPB + (k == 1 && q == 0 ? S * STEPB : 0)) = raw[k] & 0xFFFF;
            }
        }
    }
    __syncwarp();
    const uint32_t tphase = PACE / 4;
    uint32_t dreg;
    {
        const int st = lane == 0 ? S - 1 : min(lane, S) - 1;
        const uint4 u0 = *(const uint4*)(meta + st * STEPB + 128), u1 = *(const uint4*)(meta + st * STEPB + 144);
        int pos = (u0.x + u0.y + u0.z + u0.w + u1.x + u1.y + u1.z + u1.w) >> 5;
        pos += ((u0.x & F_WRAP) ? NN : 0) + (lane == S ? NN : 0) - NN * (2 * DS + 1) / 32;
        dreg = pos * (int)tphase / NN;
    }
    fill(3);
    TSTAMP(6);

    uint32_t* stash = (uint32_t*)(gs->stash + (b * NW + w) * 256) + lane;
    float acc[4][4];
#pragma unroll
    for (int i = 0; i < 16; i++) acc[i / 4][i % 4] = 0.f;
    uint4 az = *(const uint4*)(smem + SM_AZ + lane * 16);
    uint32_t dcur = dreg, dl = 0, now = flag[1], tcur = 0;
    uint32_t mp = 0, smask = 1;
    const uint32_t mend = S * STEPB;
    uint2 r = lds64(mend - STEPB + recl), s0 = lds64(mend - STEPB + srcl);
    auto step = [&](const uint32_t off, const int mode) {
        if (mode == 0) { unsigned long long n64; asm volatile("mov.u64 %0, %%globaltimer;" : "=l"(n64)); now = (uint32_t)n64; }
        asm volatile("cp.async.wait_group %0;" :: "n"(DS - 1) : "memory");
        const uint4 xa = lds128(rsrc + off), xb = lds128(rsrc + off + 512), xc = lds128(rsrc + off + 1024), xd = lds128(rsrc + off + 1536);
        const uint2 rc = r, sc = s0;
        if (mode != 4) r = lds64(mp + recl);
        if (mode == 0) {
            s0 = lds64(mp + srcl);
            dl = __shfl_sync(0xffffffff, dcur, 1); dcur = __shfl_down_sync(0xffffffff, dcur, 1);
            cpa2(wdst + off, sc.x); cpa2(wdst + off + 512, sc.y);
        }
        if (mode == 1 && w < 16) {
#pragma unroll
            for (int j = 0; j < 4; j++) {
                const int kk = 4 * j + q, ch = 16 * (w & 7) + 2 * (kk & 7) + (kk >> 3);
                asm volatile("cp.async.cg.shared.global [%0], [%1], 16;" :: "r"(ring0 + kk * 128 + ((c ^ (kk & 7)) << 4)), "l"(w_mix + ch * 16 + (w >> 3) * 8 + c) : "memory");
            }
        }
        if (mode == 2 || mode == 3) {
#pragma unroll
            for (int j = 0; j < 4; j += mode - 1)
                asm volatile("cp.async.cg.shared.global [%0], [%1], 16;" :: "r"(ring0 + off + j * 512 + lane * 16), "l"(stash + (mode - 2) * 512 + j * 128 + lane * 3) : "memory");
        }
        asm volatile("cp.async.commit_group;" ::: "memory");
        float z[4], y[4], t1[4], t2[4];
        mma1688z(z, az.x, az.y, rc.y);
        mma1688z(y, az.z, az.w, rc.y);
        uint32_t bt;
        asm("{.reg .pred p; .reg .b32 m; and.b32 m, %2, %3; setp.ne.u32 p, m, 0; selp.b32 %0, %1, 0, p;}" : "=r"(bt) : "r"(rc.x), "r"(bits0), "r"(smask));
        mma1688z(t1, at[0], at[1], bt);
        mma1688z(t2, at[2], at[3], bt);
        const uint32_t T0 = pack2(t1[0], t1[2]), T1 = pack2(t2[0], t2[2]), T2 = pack2(t1[1], t1[3]), T3 = pack2(t2[1], t2[3]);
        const uint32_t R0 = pack2(silu_h(z[0]), silu_h(z[2])), R1 = pack2(silu_h(z[1]), silu_h(z[3]));
        const uint32_t R2 = pack2(silu_h(y[0]), silu_h(y[2])), R3 = pack2(silu_h(y[1]), silu_h(y[3]));
        mma16816(acc[0], mul_lo(xa.x, R0), mul_hi(xa.z, R0), mul_lo(xa.y, R0), mul_hi(xa.w, R0), T0, T1);
        mma16816(acc[1], mul_lo(xb.x, R1), mul_hi(xb.z, R1), mul_lo(xb.y, R1), mul_hi(xb.w, R1), T2, T3);
        mma16816(acc[2], mul_lo(xc.x, R2), mul_hi(xc.z, R2), mul_lo(xc.y, R2), mul_hi(xc.w, R2), T0, T1);
        mma16816(acc[3], mul_lo(xd.x, R3), mul_hi(xd.z, R3), mul_lo(xd.y, R3), mul_hi(xd.w, R3), T2, T3);
        mp += STEPB; smask <<= 1;
    };
    auto putacc = [&](uint32_t* p) {
        p[0] = pack2(acc[0][0], acc[0][1]); p[32] = pack2(acc[0][2], acc[0][3]); p[64] = pack2(acc[2][0], acc[2][1]); p[96] = pack2(acc[2][2], acc[2][3]);
        p[256] = pack2(acc[1][0], acc[1][1]); p[288] = pack2(acc[1][2], acc[1][3]); p[320] = pack2(acc[3][0], acc[3][1]); p[352] = pack2(acc[3][2], acc[3][3]);
    };
    int ph = 0;
    auto phase_end = [&]() {
        az = *(const uint4*)(smem + SM_AZ + (ph + 1) * 512 + lane * 16);
        putacc(stash + (ph >> 1) * 512 + (ph & 1) * 128);
#pragma unroll
        for (int i = 0; i < 16; i++) acc[i / 4][i % 4] = 0.f;
        pbase += 256; mp = 0; smask = 1; ph++;
        dreg += tphase; dcur = dreg + tcur;
        WSTAMP(ph - 1);
    };
    uint32_t t0 = now;
    const bool special = w == 0 || w == PW;
#pragma unroll 1
    for (int it = S - 1; it > 0; it--) {
        if (special) {
            if (w == PW) {
                asm volatile("st.shared.u32 [%0+8], %1;" :: "r"(flg), "r"(now - dl + tcur) : "memory");
            } else {
                uint32_t g0, g1, b0, b1, cand;
                asm volatile("ld.volatile.shared.v2.u32 {%0,%1}, [%5+32]; ld.volatile.shared.v2.u32 {%2,%3}, [%5+16]; ld.volatile.shared.u32 %4, [%5+8];"
                             : "=r"(g0), "=r"(g1), "=r"(b0), "=r"(b1), "=r"(cand) : "r"(flg) : "memory");
                const unsigned long long tb = ((unsigned long long)b1 << 32) | b0;
                const unsigned long long dg = (((unsigned long long)g1 << 32) | g0) - tb;
                const uint32_t t1 = (dg < 30000 && (int)(g0 - t0) > 0) ? g0 : t0;
                cand -= PTOL;
                asm volatile("{.reg .pred p, q; setp.eq.u32 p, %2, 0; setp.gt.and.s32 q, %3, 0, p; st.shared.u32 [%4+4], %5;\n"
                             "@q red.max.relaxed.gpu.global.u64 [%0], %1; @p cp.async.cg.shared.global [%4+32], [%0], 16;}"
                             :: "l"(&gs->t0), "l"(tb + (cand - b0)), "r"(lane), "r"(cand - t1), "r"(flg), "r"(t1) : "memory");
            }
        }
        dcur += t0 - tcur; tcur = t0;
#pragma unroll
        for (int k = 0; k < DS; k++) {
            if (k == DS - 1) asm volatile("ld.volatile.shared.u32 %0, [%1+4];" : "=r"(t0) : "r"(flg));
            step(k * SLOTB, 0);
            if (mp == mend || now < dl) {
                if (mp == mend) phase_end();
                asm volatile("{.reg .pred p; .reg .u32 d;\n"
                             "PACE_LOOP: mov.u32 d, %%globaltimer_lo; sub.u32 d, %0, d; setp.lt.u32 p, d, 32768; @p nanosleep.u32 32; @p bra.uni PACE_LOOP;}"
                             :: "r"(dl) : "memory");
            }
        }
    }
    __syncwarp();
    step(0, 1); step(SLOTB, 2); step(2 * SLOTB, 3); step(3 * SLOTB, 4);
    WSTAMP(3);

    {
        putacc((uint32_t*)(smem + SM_RING + 2 * SLOTB + w * 2048 + 512) + lane);
        asm volatile("cp.async.wait_all;" ::: "memory");
        asm volatile("fence.proxy.async.shared::cta;" ::: "memory");
        const int wg = w >> 2, w4 = w & 3;
        TSTAMP(26);
        bar_sync(1, NT);
        TSTAMP(27);
        const uint64_t descA0 = (uint64_t)(((sb + SM_RING) & 0x3FFFF) >> 4) | ((uint64_t)1 << 16) | ((uint64_t)(1024 >> 4) << 32) | ((uint64_t)1 << 62);
        const uint64_t descB0 = (uint64_t)(((sb + SM_RING + SLOTB + wg * 8192) & 0x3FFFF) >> 4) | ((uint64_t)(128 >> 4) << 16) | ((uint64_t)(1024 >> 4) << 32);
        float d[2][32];
        asm volatile("wgmma.fence.sync.aligned;" ::: "memory");
#pragma unroll
        for (int mt = 0; mt < 2; mt++) {
#pragma unroll
            for (int ks = 0; ks < 8; ks++) {
                const uint64_t da = descA0 + (uint64_t)((ks * 2048 + mt * 16384) >> 4), db = descB0 + (uint64_t)(((ks & 3) * 256 + (ks >> 2) * SLOTB) >> 4);
                asm volatile("{.reg .pred p; setp.ne.b32 p, %34, 0;\n"
                    "wgmma.mma_async.sync.aligned.m64n64k16.f32.bf16.bf16 "
                    "{%0,%1,%2,%3,%4,%5,%6,%7,%8,%9,%10,%11,%12,%13,%14,%15,%16,%17,%18,%19,%20,%21,%22,%23,%24,%25,%26,%27,%28,%29,%30,%31}, %32, %33, p, 1, 1, 1, 1;}"
                    : "+f"(d[mt][0]), "+f"(d[mt][1]), "+f"(d[mt][2]), "+f"(d[mt][3]), "+f"(d[mt][4]), "+f"(d[mt][5]), "+f"(d[mt][6]), "+f"(d[mt][7]),
                      "+f"(d[mt][8]), "+f"(d[mt][9]), "+f"(d[mt][10]), "+f"(d[mt][11]), "+f"(d[mt][12]), "+f"(d[mt][13]), "+f"(d[mt][14]), "+f"(d[mt][15]),
                      "+f"(d[mt][16]), "+f"(d[mt][17]), "+f"(d[mt][18]), "+f"(d[mt][19]), "+f"(d[mt][20]), "+f"(d[mt][21]), "+f"(d[mt][22]), "+f"(d[mt][23]),
                      "+f"(d[mt][24]), "+f"(d[mt][25]), "+f"(d[mt][26]), "+f"(d[mt][27]), "+f"(d[mt][28]), "+f"(d[mt][29]), "+f"(d[mt][30]), "+f"(d[mt][31])
                    : "l"(da), "l"(db), "r"(ks));
            }
            asm volatile("wgmma.commit_group.sync.aligned;" ::: "memory");
        }
        int nd[8];
#pragma unroll
        for (int j = 0; j < 8; j++) { const int l = wg * 8 + j; nd[j] = order[(t >> 1) ? 79 - l : l]; }
        const bool odd = t & 1;
        uint2* ob = (uint2*)out + (size_t)n0 * 128 + w4 * 16 + g + (odd ? 8 : 0);
#pragma unroll
        for (int mt = 0; mt < 2; mt++) {
            if (mt == 0) asm volatile("wgmma.wait_group.sync.aligned 1;" ::: "memory");
            else asm volatile("wgmma.wait_group.sync.aligned 0;" ::: "memory");
#pragma unroll
            for (int i = 0; i < 32; i++) asm volatile("" : "+f"(d[mt][i]) :: "memory");
#pragma unroll
            for (int j = 0; j < 8; j++) {
                const uint32_t v0 = pack2(d[mt][4 * j], d[mt][4 * j + 1]), v1 = pack2(d[mt][4 * j + 2], d[mt][4 * j + 3]);
                const uint32_t rv = __shfl_xor_sync(0xffffffff, odd ? v0 : v1, 1);
                if (nd[j] < nn) ob[nd[j] * 128 + mt * 64] = odd ? make_uint2(rv, v1) : make_uint2(v0, rv);
            }
        }
    }
    TSTAMP(8);
}

}

extern "C" void kernel_launch(void* const* d_in, const int* in_sizes, int n_in, void* d_out, int out_size) {
    (void)in_sizes; (void)n_in; (void)out_size;
    cudaFuncSetAttribute(tfn_kernel, cudaFuncAttributeMaxDynamicSharedMemorySize, SM_TOTAL);
    Scratch* gs = nullptr;
    cudaGetSymbolAddress((void**)&gs, g_scratch);
    cudaLaunchConfig_t cfg = {};
    cfg.gridDim = dim3(NB); cfg.blockDim = dim3(NT); cfg.dynamicSmemBytes = SM_TOTAL; cfg.stream = cudaStreamPerThread;
    cudaLaunchAttribute at[1];
    at[0].id = cudaLaunchAttributeCooperative; at[0].val.cooperative = 1;
    cfg.attrs = at; cfg.numAttrs = 1;
    cudaLaunchKernelEx(&cfg, tfn_kernel, (const unsigned char*)d_in[0], (const int4*)d_in[1], (const int4*)d_in[2],
                       (const uint4*)d_in[3], (const uint4*)d_in[4], (const uint16_t*)d_in[5], (const uint16_t*)d_in[6],
                       (const uint4*)d_in[7], (uint32_t*)d_out, gs);
}
```

```cpp
#include <cuda_runtime.h>
#include <cuda_bf16.h>
#include <stdint.h>

#define VOL
#define ORD 1
#define ABL 0
namespace {

constexpr int NN = 10000;
constexpr int NE = 320000;
constexpr int NB = 132;
constexpr int NW = 20;
constexpr int NT = NW * 32;
constexpr int CW = NW - 1;
constexpr int PW = 10;
constexpr int NPB = 76;
constexpr int CELL = 48;
constexpr int CAP = 19;
constexpr int DS = 4;
constexpr int STEPB = 160;
constexpr int NE4 = NE / 4;
constexpr int NPIECE = NB * 8;
constexpr int KB = 320, KN = 32 * KB;
constexpr uint32_t F_WRAP = 1;

constexpr int SLOTB = NW * 2048;
constexpr int SM_RING = 0;
constexpr int SM_META = SM_RING + DS * SLOTB;
constexpr int SM_AZ = SM_META + NW * CAP * STEPB;
constexpr int SM_MISC = SM_AZ + 2048;
constexpr int SM_TOTAL = SM_MISC + 2560;
constexpr int SM_STAGE = SM_RING;
constexpr int SM_HIST = SM_RING + 25600;
constexpr int SM_POS = SM_RING;
constexpr int SM_SMALL = SM_HIST + 13056;
constexpr int SM_LIST = SM_RING + 2 * SLOTB;
constexpr int SM_RECS = SM_RING + 3 * SLOTB;
constexpr int SM_RAWY = SM_META;
constexpr int SM_RAWE = SM_RAWY + 608 * 32;
constexpr int SM_KEYS = SM_RAWE + 608 * 32;
static_assert(SM_TOTAL <= 232448 && SM_KEYS + NPIECE * 16 <= SM_AZ, "smem");
static_assert(SM_RECS + NB * CELL * 16 + 16 <= SM_AZ && SM_KEYS + NPIECE * 16 <= SM_RECS + NB * CELL * 16 && SM_SMALL + 1152 <= SLOTB && DS == 4, "smem");

struct Scratch {
    uint4 keys[NB * NPIECE];
    uint4 recs[NB * NB * CELL];
    uint4 stash[NB * NW * 256];
    unsigned bar[4];
    unsigned long long t0, pad;
};
__device__ Scratch g_scratch;
#define TSTAMP(i)
#define TSTAMPC(i)
#define WSTAMP(i)

__device__ __forceinline__ void mma16816(float* d, uint32_t a0, uint32_t a1, uint32_t a2, uint32_t a3, uint32_t b0, uint32_t b1) {
    asm VOL("mma.sync.aligned.m16n8k16.row.col.f32.bf16.bf16.f32 {%0,%1,%2,%3}, {%4,%5,%6,%7}, {%8,%9}, {%0,%1,%2,%3};"
        : "+f"(d[0]), "+f"(d[1]), "+f"(d[2]), "+f"(d[3]) : "r"(a0), "r"(a1), "r"(a2), "r"(a3), "r"(b0), "r"(b1));
}
__device__ __forceinline__ void mma1688z(float* d, uint32_t a0, uint32_t a1, uint32_t b0) {
    asm VOL("mma.sync.aligned.m16n8k8.row.col.f32.bf16.bf16.f32 {%0,%1,%2,%3}, {%4,%5}, {%6}, {%7,%7,%7,%7};"
        : "=f"(d[0]), "=f"(d[1]), "=f"(d[2]), "=f"(d[3]) : "r"(a0), "r"(a1), "r"(b0), "f"(0.f));
}
__device__ __forceinline__ uint32_t pack2(float lo, float hi) {
    uint32_t r; asm VOL("cvt.rn.bf16x2.f32 %0, %1, %2;" : "=r"(r) : "f"(hi), "f"(lo)); return r;
}
__device__ __forceinline__ float silu_h(float h) {
    float t; asm VOL("tanh.approx.f32 %0, %1;" : "=f"(t) : "f"(h)); return fmaf(h, t, h);
}
__device__ __forceinline__ uint32_t mul_lo(uint32_t v, uint32_t r) {
    __nv_bfloat162 a = *(__nv_bfloat162*)&v, b = *(__nv_bfloat162*)&r; __nv_bfloat162 c = __hmul2(a, __low2bfloat162(b)); return *(uint32_t*)&c;
}
__device__ __forceinline__ uint32_t mul_hi(uint32_t v, uint32_t r) {
    __nv_bfloat162 a = *(__nv_bfloat162*)&v, b = *(__nv_bfloat162*)&r; __nv_bfloat162 c = __hmul2(a, __high2bfloat162(b)); return *(uint32_t*)&c;
}
__device__ __forceinline__ uint2 lds64(uint32_t a) {
    uint2 r; asm volatile("ld.shared.v2.u32 {%0,%1}, [%2];" : "=r"(r.x), "=r"(r.y) : "r"(a)); return r;
}
__device__ __forceinline__ uint4 lds128(uint32_t a) {
    uint4 r; asm volatile("ld.shared.v4.u32 {%0,%1,%2,%3}, [%4];" : "=r"(r.x), "=r"(r.y), "=r"(r.z), "=r"(r.w) : "r"(a) : "memory"); return r;
}
__device__ __forceinline__ void bar_sync(int id, int n) { asm volatile("bar.sync %0, %1;" :: "r"(id), "r"(n) : "memory"); }
__device__ __forceinline__ void bar_arrive(int id, int n) { asm volatile("bar.arrive %0, %1;" :: "r"(id), "r"(n) : "memory"); }
__device__ __forceinline__ void mbar_wait(uint32_t bar, uint32_t ph) {
    uint32_t done; int spins = 0;
    do {
        asm volatile("{.reg .pred p; mbarrier.try_wait.parity.shared.b64 p, [%1], %2; selp.u32 %0,1,0,p;}" : "=r"(done) : "r"(bar), "r"(ph) : "memory");
    } while (!done && ++spins < (1 << 22));
}
__device__ __forceinline__ unsigned gbar_read(const unsigned* ctr) {
    unsigned v; asm volatile("ld.relaxed.gpu.global.u32 %0, [%1];" : "=r"(v) : "l"(ctr) : "memory");
    return v;
}
__device__ __forceinline__ void gbar_arrive(unsigned* ctr) {
    asm volatile("red.add.release.gpu.global.u32 [%0], 1;" :: "l"(ctr) : "memory");
}
__device__ __forceinline__ void gbar_wait(const unsigned* ctr, unsigned target) {
    unsigned v; int spins = 0;
    do { asm volatile("ld.acquire.gpu.global.u32 %0, [%1];" : "=r"(v) : "l"(ctr) : "memory"); } while ((int)(v - target) < 0 && ++spins < (1 << 22));
}
__device__ __forceinline__ int chunk_start4(int c) { return (c * NE4) / NB; }
__device__ __forceinline__ float bf2f(uint32_t h) { return __uint_as_float(h << 16); }

__device__ __noinline__ void slow_path(unsigned char* smem, int n0, int nn, const uint16_t* x, const int* src, const int* dst,
                                       const uint16_t* Y, const uint16_t* ef, const uint16_t* w_rad, const uint16_t* cg,
                                       const uint16_t* w_mix, __nv_bfloat16* out) {
    float* agg = (float*)smem;
    const int tid = threadIdx.x, lane = tid & 31, w = tid >> 5;
    bar_sync(1, NT);
    for (int i = tid; i < NPB * 512; i += NT) agg[i] = 0.f;
    bar_sync(1, NT);
    for (int e0 = w * 32; e0 < NE; e0 += NT) {
        int dl = dst[e0 + lane] - n0;
        unsigned m = __ballot_sync(0xffffffff, dl >= 0 && dl < nn);
        while (m) {
            int l = __ffs(m) - 1; m &= m - 1;
            int e = e0 + l, d = __shfl_sync(0xffffffff, dl, l), s = src[e];
            float T[16];
            for (int i = 0; i < 4; i++) for (int o = 0; o < 4; o++) {
                float a = 0.f;
                for (int f = 0; f < 4; f++) a += bf2f(Y[e * 4 + f]) * bf2f(cg[i * 16 + f * 4 + o]);
                T[i * 4 + o] = a;
            }
            for (int k = 0; k < 4; k++) {
                int c = lane + 32 * k;
                float z = 0.f;
                for (int j = 0; j < 4; j++) z += bf2f(ef[e * 4 + j]) * bf2f(w_rad[j * 128 + c]);
                float R = z / (1.f + __expf(-z));
                for (int o = 0; o < 4; o++) {
                    float a = 0.f;
                    for (int i = 0; i < 4; i++) a += bf2f(x[(size_t)s * 512 + c * 4 + i]) * T[i * 4 + o];
                    atomicAdd(&agg[d * 512 + c * 4 + o], R * a);
                }
            }
        }
    }
    bar_sync(1, NT);
    for (int i = tid; i < nn * 512; i += NT) {
        int n = i >> 9, d = (i >> 2) & 127, o = i & 3;
        float a = 0.f;
        for (int c = 0; c < 128; c++) a += agg[n * 512 + c * 4 + o] * bf2f(w_mix[c * 128 + d]);
        out[(size_t)(n0 + n) * 512 + (i & 511)] = __float2bfloat16(a);
    }
}

#define PACE 24000
#define YDELAY 300
#define NB0 4
#define TP 0
#define EPI 1
#define MATCH 0
#define POFF 1700
#define PTOL 600
__global__ void __launch_bounds__(NT, 1)
tfn_kernel(const unsigned char* __restrict__ x, const int4* __restrict__ src4, const int4* __restrict__ dst4,
           const uint4* __restrict__ Y, const uint4* __restrict__ ef, const uint16_t* __restrict__ w_rad,
           const uint16_t* __restrict__ cg, const uint4* __restrict__ w_mix, uint32_t* __restrict__ out, Scratch* __restrict__ gs) {
    extern __shared__ __align__(1024) unsigned char smem[];
    const uint32_t sb = (uint32_t)__cvta_generic_to_shared(smem);
    const int b = blockIdx.x, tid = threadIdx.x, lane = tid & 31, g = lane >> 2, t = lane & 3;
    const int w = __shfl_sync(0xffffffff, tid >> 5, 0);
    uint32_t* stage = (uint32_t*)(smem + SM_STAGE);
    uint32_t* hist = (uint32_t*)(smem + SM_HIST);
    uint32_t* cnt = (uint32_t*)(smem + SM_MISC);
    uint32_t* deg = cnt + 136;
    uint32_t* order = deg + 104;
    uint32_t* cnt2 = order + 80;
    volatile uint32_t* flag = cnt2 + 136;
    const uint32_t mbarK = sb + SM_MISC + 1920, mbarR = mbarK + 8, mbarW = mbarK + 16;
    const int n0 = b * NPB, nn = min(NPB, NN - n0);
    TSTAMP(0);

    const int c0 = chunk_start4(b), c1 = chunk_start4(b + 1);
    const bool has4 = c0 + tid < c1;
    int4 d4 = make_int4(0, 0, 0, 0), s4 = d4;
    if (has4) { d4 = __ldg(dst4 + c0 + tid); s4 = __ldg(src4 + c0 + tid); }
    unsigned tgt = 0;
    if (tid == NT - 1) {
        tgt = gbar_read(&gs->bar[0]);
        asm volatile("mbarrier.init.shared.b64 [%0], 1;" :: "r"(mbarK));
        asm volatile("mbarrier.init.shared.b64 [%0], 1;" :: "r"(mbarR));
        asm volatile("mbarrier.init.shared.b64 [%0], 512;" :: "r"(mbarW));
        asm volatile("fence.mbarrier_init.release.cluster;" ::: "memory");
        *flag = 0;
    }
    if (w == CW) {
        asm volatile("cp.async.cg.shared.global [%0], [%1], 16;" :: "r"(sb + SM_SMALL + lane * 16), "l"(w_rad + lane * 8) : "memory");
        asm volatile("cp.async.cg.shared.global [%0], [%1], 16;" :: "r"(sb + SM_SMALL + 512 + lane * 16), "l"(w_rad + 256 + lane * 8) : "memory");
        if (lane < 8) asm volatile("cp.async.cg.shared.global [%0], [%1], 16;" :: "r"(sb + SM_SMALL + 1024 + lane * 16), "l"(cg + lane * 8) : "memory");
    }
    ((uint4*)hist)[tid] = make_uint4(0, 0, 0, 0);
    {
        const uint32_t dk = ((80 + b % 22) * KN + (b & 31) * KB) << 12;
#pragma unroll
        for (int j = 0; j < 3; j++) if (tid + j * NT < NB * CELL / 4) ((uint4*)stage)[tid + j * NT] = make_uint4(dk, dk, dk, dk);
    }
    if (tid < 136) cnt[tid] = 0;
    if (tid == 0) { *(uint4*)(smem + SM_MISC + 1824 + 32) = make_uint4(0, 0, 0, 0); cnt2[NB] = 0; *(uint4*)(smem + SM_RECS + NB * CELL * 16) = make_uint4(0, 0, 0, 0); }
    if (tid < 80) { deg[tid] = 127 - tid; order[tid] = tid; }
    __syncthreads();
    TSTAMP(9);
    if (tid == 64) {
        if (YDELAY) __nanosleep(YDELAY);
        asm volatile("mbarrier.arrive.expect_tx.shared.b64 _, [%0], %1;" :: "r"(mbarR), "r"((c1 - c0) * 64) : "memory");
        asm volatile("cp.async.bulk.shared::cluster.global.mbarrier::complete_tx::bytes [%0], [%1], %2, [%3];"
                     :: "r"(sb + SM_RAWY), "l"(Y + 2 * c0), "r"((c1 - c0) * 32), "r"(mbarR) : "memory");
        asm volatile("cp.async.bulk.shared::cluster.global.mbarrier::complete_tx::bytes [%0], [%1], %2, [%3];"
                     :: "r"(sb + SM_RAWE), "l"(ef + 2 * c0), "r"((c1 - c0) * 32), "r"(mbarR) : "memory");
    }

    if (has4) {
        const uint32_t dd[4] = {(uint32_t)d4.x, (uint32_t)d4.y, (uint32_t)d4.z, (uint32_t)d4.w}, ss[4] = {(uint32_t)s4.x, (uint32_t)s4.y, (uint32_t)s4.z, (uint32_t)s4.w};
        uint32_t bin[4], slot[4];
#pragma unroll
        for (int k = 0; k < 4; k++) { bin[k] = dd[k] / NPB; slot[k] = atomicAdd(&cnt[bin[k]], 1); }
#pragma unroll
        for (int k = 0; k < 4; k++)
            stage[bin[k] * CELL + min(slot[k], CELL - 1)] = (((dd[k] - bin[k] * NPB) * KN + ss[k]) << 12) + tid * 4 + k;
    }
    if (w == CW) asm volatile("cp.async.wait_all;" ::: "memory");
    bar_sync(1, NT);
    TSTAMP(1);
#pragma unroll
    for (int j = 0; j < 2; j++) {
        const int i = tid + j * NT;
        if (i < NPIECE) {
            const uint2 sa = *(const uint2*)(stage + i * 6), sc = *(const uint2*)(stage + i * 6 + 2), se = *(const uint2*)(stage + i * 6 + 4);
            const uint32_t cn = min(cnt[i >> 3], 255u);
            gs->keys[((i >> 3) * NB + b) * 8 + ((i ^ b) & 7)] =
                make_uint4(__funnelshift_r(sa.x, se.x >> 12, 12), __funnelshift_r(sa.y, __funnelshift_r(se.x, cn, 24), 12),
                           __funnelshift_r(sc.x, se.y >> 12, 12), __funnelshift_r(sc.y, __funnelshift_r(se.y, cn >> 4, 24), 12));
        }
    }
    uint2 yy[7], ee[7];
    uint32_t cno[7];
    uint4* rp = gs->recs + (w * NB + b) * CELL + lane;
    auto recs_out = [&](int j0, int j1) {
#pragma unroll
        for (int j = 0; j < 7; j++) if (j >= j0 && j < j1)
            asm volatile("{.reg .pred p; setp.lt.u32 p, %5, %6; @p st.global.v4.u32 [%0], {%1,%2,%3,%4};}"
                         :: "l"(rp + j * (CW * NB * CELL)), "r"(yy[j].x), "r"(ee[j].x), "r"(yy[j].y), "r"(ee[j].y), "r"(lane & ~1), "r"(cno[j]) : "memory");
    };
    if (w == CW) {
        bar_sync(7, NT);
        if (tid == NT - 1) {
            TSTAMPC(10);
            gbar_arrive(&gs->bar[0]);
            TSTAMPC(11);
            tgt = (tgt / NB + 1) * NB;
            asm volatile("mbarrier.arrive.expect_tx.shared.b64 _, [%0], %1;" :: "r"(mbarK), "r"(NPIECE * 16) : "memory");
            gbar_wait(&gs->bar[0], tgt);
            TSTAMPC(13);
            asm volatile("fence.proxy.async.global;" ::: "memory");
            asm volatile("cp.async.bulk.shared::cluster.global.mbarrier::complete_tx::bytes [%0], [%1], %2, [%3];"
                         :: "r"(sb + SM_KEYS), "l"(gs->keys + b * NPIECE), "r"(NPIECE * 16), "r"(mbarK) : "memory");
        }
        __syncwarp();
        bar_arrive(8, NT);
    } else {
        bar_arrive(7, NT);
        if (w < 8) {
            const uint32_t* wp = (const uint32_t*)(smem + SM_SMALL) + (t & 1) * 128 + 8 * w + g;
            const uint32_t wr0 = t < 2 ? wp[0] : 0, wr1 = t < 2 ? wp[64] : 0;
            *(uint2*)(smem + SM_AZ + (w >> 1) * 512 + lane * 16 + (w & 1) * 8) =
                make_uint2(pack2(0.5f * bf2f(wr0 & 0xFFFF), 0.5f * bf2f(wr1 & 0xFFFF)), pack2(0.5f * bf2f(wr0 >> 16), 0.5f * bf2f(wr1 >> 16)));
        }
        uint32_t el[7], big = 0;
#pragma unroll
        for (int j = 0; j < 7; j++) {
            const int cell = w + CW * j;
            cno[j] = cnt[cell];
            el[j] = (stage[cell * CELL + lane] & 0xFFF) * 8;
            big |= cno[j] > 32;
        }
        mbar_wait(mbarR, 0);
        TSTAMP(18);
#pragma unroll
        for (int j = 0; j < 7; j++) { yy[j] = lds64(sb + SM_RAWY + el[j]); ee[j] = lds64(sb + SM_RAWE + el[j]); }
        if (big) {
#pragma unroll 1
            for (int j = 0; j < 7; j++) {
                const int cell = w + CW * j;
                if (lane + 32 < min(cnt[cell], CELL)) {
                    const uint32_t e2 = (stage[cell * CELL + 32 + lane] & 0xFFF) * 8;
                    const uint2 y2 = *(const uint2*)(smem + SM_RAWY + e2), e3 = *(const uint2*)(smem + SM_RAWE + e2);
                    rp[j * (CW * NB * CELL) + 32] = make_uint4(y2.x, e3.x, y2.y, e3.y);
                }
            }
        }
        bar_sync(8, NT);
        recs_out(0, NB0);
    }
    __syncwarp();
    TSTAMP(2);
    uint32_t at[4];
    {
        const int o = g & 3, f = 2 * (t & 1);
#pragma unroll
        for (int i = 0; i < 4; i++) {
            const uint16_t* cp = (const uint16_t*)(smem + SM_SMALL + 1024) + i * 16 + f * 4 + o;
            at[i] = (t >> 1) == (g >> 2) ? cp[0] | ((uint32_t)cp[4] << 16) : 0;
        }
    }

    uint32_t key[2][6], ha[2][6], rk[2][6], kidx[2];
    int nk[2] = {0, 0};
    unsigned seenB = 0;
    if (w < CW) {
        uint32_t ka[2];
#pragma unroll
        for (int j = 0; j < 2; j++) {
            const int i0 = j ? 2 * 608 - 1 - tid : tid, i = min(i0, NPIECE - 1), r = i / NB, c = i - r * NB;
            ka[j] = sb + SM_KEYS + (c * 8 + ((r ^ c) & 7)) * 16;
            kidx[j] = (c * CELL + r * 6) << 17;
            nk[j] = i0 < NPIECE ? -6 * r : -1000;
        }
        mbar_wait(mbarK, 0);
        TSTAMP(3);
        const uint4 v[2] = {lds128(ka[0]), lds128(ka[1])};
#pragma unroll
        for (int j = 0; j < 2; j++) {
            const uint32_t hc = (v[j].y >> 28) | ((v[j].w >> 28) << 4);
            if (j == 0 && tid < NB) cnt2[tid] = hc;
            nk[j] += hc;
            if (nk[j] > 0) {
                key[j][0] = v[j].x & 0xFFFFF; key[j][1] = v[j].y & 0xFFFFF; key[j][2] = v[j].z & 0xFFFFF; key[j][3] = v[j].w & 0xFFFFF;
                key[j][4] = (v[j].x >> 20) | ((v[j].y >> 8) & 0xFF000); key[j][5] = (v[j].z >> 20) | ((v[j].w >> 8) & 0xFF000);
#pragma unroll
                for (int u = 0; u < 6; u++) {
                    ha[j][u] = __umulhi(key[j][u], 0xFFFFFFFFu / KB + 1);
                    rk[j][u] = atomicAdd(&hist[ha[j][u]], 1);
                    atomicAdd(&deg[ha[j][u] >> 5], 128);
                }
            }
        }
        recs_out(NB0, 7);
        bar_sync(10, NT);
        TSTAMP(20);
        const int n = tid >> 3, sub = tid & 7;
        const uint32_t me = deg[n];
        int r = 0;
#pragma unroll
        for (int k = 0; k < 5; k++) { const uint2 dd = *(const uint2*)(deg + sub * 10 + 2 * k); r += (dd.x > me) + (dd.y > me); }
        r += __shfl_xor_sync(0xffffffff, r, 1); r += __shfl_xor_sync(0xffffffff, r, 2); r += __shfl_xor_sync(0xffffffff, r, 4);
        if (sub == 0) order[r] = n;
    } else {
        bar_sync(10, NT);
        if (tid == NT - 1) { TSTAMPC(14); gbar_arrive(&gs->bar[1]); TSTAMPC(15); seenB = gbar_read(&gs->bar[1]); }
    }
    __syncwarp();
    bar_sync(1, NT);
    TSTAMP(22);
    const uint32_t cn = cnt2[min(w + NW * lane, NB)];
    if (cn > CELL) *flag = 1;
    auto recs_in = [&]() {
        const uint4* gp = gs->recs + (b * NB + w) * CELL + lane;
        const uint32_t sp = sb + SM_RECS + (w * CELL + lane) * 16;
#pragma unroll
        for (int j = 0; j < 7; j++)
            asm volatile("{.reg .pred p; setp.lt.u32 p, %2, %3; @p cp.async.cg.shared.global [%0], [%1], 16;}"
                         :: "r"(sp + j * (NW * CELL * 16)), "l"(gp + j * (NW * CELL)), "r"(lane), "r"(__shfl_sync(0xffffffff, cn, j)) : "memory");
        if (__any_sync(0xffffffff, cn > 32)) {
#pragma unroll 1
            for (int j = 0; j < 7; j++)
                if (lane + 32 < min(__shfl_sync(0xffffffff, cn, j), CELL))
                    asm volatile("cp.async.cg.shared.global [%0], [%1], 16;" :: "r"(sp + j * (NW * CELL * 16) + 512), "l"(gp + j * (NW * CELL) + 32) : "memory");
        }
        asm volatile("cp.async.commit_group;" ::: "memory");
    };
    int S, mylen;
    {
        const uint2 na = *(const uint2*)(order + 2 * w), nb = *(const uint2*)(order + 78 - 2 * w);
        const uint32_t ia0 = na.x * 32 + lane, ib0 = nb.y * 32 + lane, ia1 = na.y * 32 + lane, ib1 = nb.x * 32 + lane;
        const uint32_t ca = hist[ia0] + (hist[ia1] << 16), cab = ca + hist[ib0] + (hist[ib1] << 16);
        uint32_t inc = cab;
#pragma unroll
        for (int o = 1; o < 32; o <<= 1)
            asm volatile("{.reg .pred p; .reg .u32 u; shfl.sync.up.b32 u|p, %0, %1, 0, 0xffffffff; @p add.u32 %0, %0, u;}" : "+r"(inc) : "r"(o));
        const uint32_t ea = inc - cab, eb = ea + ca, base = sb + SM_LIST + w * 2048;
        uint2* pos = (uint2*)(smem + SM_POS);
        pos[ia0] = make_uint2(base + (ea & 0xFFFF) * 8, na.x * (0u - 4 * KN));
        pos[ib0] = make_uint2(base + (eb & 0xFFFF) * 8, nb.y * (0u - 4 * KN) + 0x10000);
        pos[ia1] = make_uint2(base + 4 + (ea >> 16) * 8, na.y * (0u - 4 * KN));
        pos[ib1] = make_uint2(base + 4 + (eb >> 16) * 8, nb.x * (0u - 4 * KN) + 0x10000);
        const uint32_t len = __shfl_sync(0xffffffff, inc, 31);
        S = (max(len & 0xFFFF, len >> 16) + 3) >> 2;
        mylen = (lane & 1) ? len >> 16 : len & 0xFFFF;
        if (S > CAP) *flag = 1;
        S = __shfl_sync(0xffffffff, max(S, DS + 1), 0);
    }
    if (tid == NT - 1) {
        TSTAMPC(16);
        if ((int)(seenB - tgt) < 0) gbar_wait(&gs->bar[1], tgt);
        else asm volatile("fence.acq_rel.cta;" ::: "memory");
        TSTAMPC(17);
    }
    bar_sync(1, NT);
    TSTAMP(21);
    if (*flag) {
        slow_path(smem, n0, nn, (const uint16_t*)x, (const int*)src4, (const int*)dst4, (const uint16_t*)Y, (const uint16_t*)ef, w_rad, cg,
                  (const uint16_t*)w_mix, (__nv_bfloat16*)out);
        return;
    }
    recs_in();
#pragma unroll
    for (int j = 0; j < 2; j++) {
        if (nk[j] > 0) {
            uint2 h[6];
#pragma unroll
            for (int u = 0; u < 6; u++) h[u] = lds64(sb + SM_POS + ha[j][u] * 8);
#pragma unroll
            for (int u = 0; u < 6; u++)
                asm volatile("{.reg .pred p; setp.gt.s32 p, %2, %3; @p st.shared.u32 [%0], %1;}"
                             :: "r"(h[u].x + rk[j][u] * 8), "r"(key[j][u] * 4 + h[u].y + (kidx[j] + (u << 17))), "r"(nk[j]), "r"(u) : "memory");
        }
    }
    bar_sync(1, NT);
    TSTAMP(4);
    constexpr int NRAW = (CAP + 3) / 4;
    uint32_t bits0 = 0, raw[NRAW];
    unsigned char* meta = smem + SM_META + w * (CAP * STEPB);
#pragma unroll
    for (int k = 0; k < NRAW; k++) raw[k] = mylen ? ((uint32_t*)(smem + SM_LIST + w * 2048))[min(k * 16 + (lane >> 1), mylen - 1) * 2 + (lane & 1)] : 4 * n0;
    const uint32_t sv0 = raw[0] & 0xFFFF;
    const int q = lane >> 3, c = lane & 7;
    const uint32_t ring0 = sb + SM_RING + w * 2048;
    uint32_t wdst = ring0 + q * 128 + ((c + 2 * q) & 7) * 16;
    uint32_t rsrc = ring0 + t * 128 + ((g + 2 * t) & 7) * 16;
    uint32_t recl = sb + SM_META + w * (CAP * STEPB) + g * 16 + (t & 1) * 8, srcl = sb + SM_META + w * (CAP * STEPB) + 128 + q * 8;
    uint32_t flg = sb + SM_MISC + (136 + 104 + 80 + 136) * 4;
    asm volatile("" : "+r"(wdst), "+r"(rsrc), "+r"(recl), "+r"(srcl), "+r"(flg));
    const unsigned char* pbase = x + c * 16;
    auto cpa2 = [&](uint32_t dstp, uint32_t sv) {
        asm volatile("cp.async.cg.shared.global [%0], [%1], 16; cp.async.cg.shared.global [%0+1024], [%1+128], 16;"
                     :: "r"(dstp), "l"(pbase + (size_t)sv * 256) : "memory");
    };
    auto fill = [&](int i) {
        cpa2(wdst + i * SLOTB, __shfl_sync(0xffffffff, sv0, 8 * i + 2 * q)); cpa2(wdst + i * SLOTB + 512, __shfl_sync(0xffffffff, sv0, 8 * i + 2 * q + 1));
        asm volatile("cp.async.commit_group;" ::: "memory");
    };
    fill(0);
    TSTAMP(5);
    if (w == 0) {
        unsigned long long tbase;
        asm volatile("mov.u64 %0, %%globaltimer;" : "=l"(tbase));
        tbase += POFF;
        flag[1] = (uint32_t)tbase; flag[2] = (uint32_t)tbase; flag[4] = (uint32_t)tbase; flag[5] = (uint32_t)(tbase >> 32);
        if (lane == 0) {
            asm volatile("red.max.relaxed.gpu.global.u64 [%0], %1;" :: "l"(&gs->t0), "l"(tbase) : "memory");
            if (b < 128) asm volatile("cp.async.bulk.prefetch.L2.global [%0], 256;" :: "l"(w_mix + b * 16));
        }
    }
    uint32_t ra[NRAW];
#pragma unroll
    for (int k = 0; k < NRAW; k++) {
        const uint32_t m = (__ballot_sync(0xffffffff, raw[k] & 0x10000) >> g) & 0x01010101u;
        bits0 |= ((m * 0x10204080u) >> 28) << (4 * k);
        ra[k] = sb + SM_RECS + (k * 16 + (lane >> 1) < mylen ? raw[k] >> 17 : NB * CELL) * 16;
    }
    if (t < 2) bits0 = ~bits0;
    fill(1);
    asm volatile("cp.async.wait_group 2;" ::: "memory");
    bar_sync(1, NT);
    TSTAMP(19);
    {
        uint4 rv[NRAW];
#pragma unroll
        for (int k = 0; k < NRAW - 1; k++) rv[k] = lds128(ra[k]);
        if ((NRAW - 1) * 4 < S) rv[NRAW - 1] = lds128(ra[NRAW - 1]);
        if (tid == 0) asm volatile("cp.async.cg.shared.global [%0], [%1], 16;" :: "r"(sb + SM_MISC + 1824 + 32), "l"(&gs->t0) : "memory");
        fill(2);
        bar_sync(1, NT);
        TSTAMP(12);
        unsigned char* mr = meta + (q - 1) * STEPB + c * 16;
        unsigned char* ms = meta + (q - DS - 1) * STEPB + 128 + c * 4;
#pragma unroll
        for (int k = 0; k < NRAW; k++) {
            if (k == 0) {
                *(uint4*)(mr + (q == 0 ? S * STEPB : 0)) = rv[k];
                *(uint32_t*)(ms + S * STEPB) = sv0 + F_WRAP;
            } else if (k * 4 + q < S) {
                *(uint4*)(mr + k * 4 * STEPB) = rv[k];
                *(uint32_t*)(ms + k * 4 * STEPB + (k == 1 && q == 0 ? S * STEPB : 0)) = raw[k] & 0xFFFF;
            }
        }
    }
    __syncwarp();
    const uint32_t tphase = PACE / 4;
    uint32_t dreg;
    {
        const int st = lane == 0 ? S - 1 : min(lane, S) - 1;
        const uint4 u0 = *(const uint4*)(meta + st * STEPB + 128), u1 = *(const uint4*)(meta + st * STEPB + 144);
        int pos = (u0.x + u0.y + u0.z + u0.w + u1.x + u1.y + u1.z + u1.w) >> 5;
        pos += ((u0.x & F_WRAP) ? NN : 0) + (lane == S ? NN : 0) - NN * (2 * DS + 1) / 32;
        dreg = pos * (int)tphase / NN;
    }
    fill(3);
    TSTAMP(6);

    uint32_t* stash = (uint32_t*)(gs->stash + (b * NW + w) * 256) + lane;
    float acc[4][4];
#pragma unroll
    for (int i = 0; i < 16; i++) acc[i / 4][i % 4] = 0.f;
    uint4 az = *(const uint4*)(smem + SM_AZ + lane * 16);
    uint32_t dcur = dreg, dl = 0, now = flag[1], tcur = 0;
    uint32_t mp = 0, smask = 1;
    const uint32_t mend = S * STEPB;
    uint2 r = lds64(mend - STEPB + recl), s0 = lds64(mend - STEPB + srcl);
    auto step = [&](const uint32_t off, const int mode) {
        auto tick = [&]() { if (mode == 0) { unsigned long long n64; asm volatile("mov.u64 %0, %%globaltimer;" : "=l"(n64)); now = (uint32_t)n64; } };
        if (TP == 0) tick();
        const uint2 rc = r, sc = s0;
        if (ORD & 1) { if (mode != 4) r = lds64(mp + recl); if (mode == 0) s0 = lds64(mp + srcl); }
        asm volatile("cp.async.wait_group %0;" :: "n"(DS - 1) : "memory");
        const uint4 xa = lds128(rsrc + off), xb = lds128(rsrc + off + 512), xc = lds128(rsrc + off + 1024), xd = lds128(rsrc + off + 1536);
        if (!(ORD & 1) && !(ORD & 4)) { if (mode != 4) r = lds64(mp + recl); if (mode == 0) s0 = lds64(mp + srcl); }
        if (mode == 0) {
            if (ORD & 2) {
                asm volatile("shfl.sync.idx.b32 %0, %1, 1, 31, 0xffffffff; shfl.sync.down.b32 %1, %1, 1, 31, 0xffffffff;\n"
                             "cp.async.cg.shared.global [%2], [%3], 16; cp.async.cg.shared.global [%2+512], [%4], 16;\n"
                             "cp.async.cg.shared.global [%2+1024], [%3+128], 16; cp.async.cg.shared.global [%2+1536], [%4+128], 16;"
                             : "=&r"(dl), "+r"(dcur) : "r"(wdst + off), "l"(pbase + (size_t)sc.x * 256), "l"(pbase + (size_t)sc.y * 256) : "memory");
            } else {
                dl = __shfl_sync(0xffffffff, dcur, 1); dcur = __shfl_down_sync(0xffffffff, dcur, 1);
                cpa2(wdst + off, sc.x); cpa2(wdst + off + 512, sc.y);
            }
        }
        if (mode == 1 && w < 16) {
#pragma unroll
            for (int j = 0; j < 4; j++) {
                const int kk = 4 * j + q, ch = 16 * (w & 7) + 2 * (kk & 7) + (kk >> 3);
                asm volatile("cp.async.cg.shared.global [%0], [%1], 16;" :: "r"(ring0 + kk * 128 + ((c ^ (kk & 7)) << 4)), "l"(w_mix + ch * 16 + (w >> 3) * 8 + c) : "memory");
            }
            asm volatile("cp.async.mbarrier.arrive.noinc.shared.b64 [%0];" :: "r"(mbarW) : "memory");
        }
        if (mode == 2 || mode == 3) {
#pragma unroll
            for (int j = 0; j < 4; j += mode - 1)
                asm volatile("cp.async.cg.shared.global [%0], [%1], 16;" :: "r"(ring0 + off + j * 512 + lane * 16), "l"(stash + (mode - 2) * 512 + j * 128 + lane * 3) : "memory");
        }
        asm volatile("cp.async.commit_group;" ::: "memory");
        if (ORD & 4) { if (mode != 4) r = lds64(mp + recl); if (mode == 0) s0 = lds64(mp + srcl); }
        float z[4], y[4], t1[4], t2[4];
        mma1688z(z, az.x, az.y, rc.y);
        mma1688z(y, az.z, az.w, rc.y);
        uint32_t bt;
        asm("{.reg .pred p; .reg .b32 m; and.b32 m, %2, %3; setp.ne.u32 p, m, 0; selp.b32 %0, %1, 0, p;}" : "=r"(bt) : "r"(rc.x), "r"(bits0), "r"(smask));
        mma1688z(t1, at[0], at[1], bt);
        mma1688z(t2, at[2], at[3], bt);
        if (TP == 1) tick();
        const uint32_t T0 = pack2(t1[0], t1[2]), T1 = pack2(t2[0], t2[2]), T2 = pack2(t1[1], t1[3]), T3 = pack2(t2[1], t2[3]);
        const uint32_t R0 = pack2(silu_h(z[0]), silu_h(z[2]));
        if (TP == 2) tick();
        const uint32_t R1 = pack2(silu_h(z[1]), silu_h(z[3]));
        if (TP == 3) tick();
        const uint32_t R2 = pack2(silu_h(y[0]), silu_h(y[2])), R3 = pack2(silu_h(y[1]), silu_h(y[3]));
        if (TP == 4) tick();
        mma16816(acc[0], mul_lo(xa.x, R0), mul_hi(xa.z, R0), mul_lo(xa.y, R0), mul_hi(xa.w, R0), T0, T1);
        mma16816(acc[1], mul_lo(xb.x, R1), mul_hi(xb.z, R1), mul_lo(xb.y, R1), mul_hi(xb.w, R1), T2, T3);
        mma16816(acc[2], mul_lo(xc.x, R2), mul_hi(xc.z, R2), mul_lo(xc.y, R2), mul_hi(xc.w, R2), T0, T1);
        mma16816(acc[3], mul_lo(xd.x, R3), mul_hi(xd.z, R3), mul_lo(xd.y, R3), mul_hi(xd.w, R3), T2, T3);
        mp += STEPB; smask <<= 1;
    };
    auto putacc = [&](uint32_t* p) {
        p[0] = pack2(acc[0][0], acc[0][1]); p[32] = pack2(acc[0][2], acc[0][3]); p[64] = pack2(acc[2][0], acc[2][1]); p[96] = pack2(acc[2][2], acc[2][3]);
        p[256] = pack2(acc[1][0], acc[1][1]); p[288] = pack2(acc[1][2], acc[1][3]); p[320] = pack2(acc[3][0], acc[3][1]); p[352] = pack2(acc[3][2], acc[3][3]);
    };
    int ph = 0;
    auto phase_end = [&]() {
        az = *(const uint4*)(smem + SM_AZ + (ph + 1) * 512 + lane * 16);
        putacc(stash + (ph >> 1) * 512 + (ph & 1) * 128);
#pragma unroll
        for (int i = 0; i < 16; i++) acc[i / 4][i % 4] = 0.f;
        pbase += 256; mp = 0; smask = 1; ph++;
        dreg += tphase; dcur = dreg + tcur;
        WSTAMP(ph - 1);
    };
    uint32_t t0 = now;
    const bool special = w == 0 || w == PW;
#pragma unroll 1
    for (int it = S - 1; it > 0; it--) {
        if (special) {
            if (w == PW) {
                asm volatile("st.shared.u32 [%0+8], %1;" :: "r"(flg), "r"(now - dl + tcur) : "memory");
            } else {
                uint32_t g0, g1, b0, b1, cand;
                asm volatile("ld.volatile.shared.v2.u32 {%0,%1}, [%5+32]; ld.volatile.shared.v2.u32 {%2,%3}, [%5+16]; ld.volatile.shared.u32 %4, [%5+8];"
                             : "=r"(g0), "=r"(g1), "=r"(b0), "=r"(b1), "=r"(cand) : "r"(flg) : "memory");
                const unsigned long long tb = ((unsigned long long)b1 << 32) | b0;
                const unsigned long long dg = (((unsigned long long)g1 << 32) | g0) - tb;
                const uint32_t t1 = (dg < 30000 && (int)(g0 - t0) > 0) ? g0 : t0;
                cand -= PTOL;
                asm volatile("{.reg .pred p, q; setp.eq.u32 p, %2, 0; setp.gt.and.s32 q, %3, 0, p; st.shared.u32 [%4+4], %5;\n"
                             "@q red.max.relaxed.gpu.global.u64 [%0], %1; @p cp.async.cg.shared.global [%4+32], [%0], 16;}"
                             :: "l"(&gs->t0), "l"(tb + (cand - b0)), "r"(lane), "r"(cand - t1), "r"(flg), "r"(t1) : "memory");
            }
        }
        dcur += t0 - tcur; tcur = t0;
#pragma unroll
        for (int k = 0; k < DS; k++) {
            if (k == DS - 1) asm volatile("ld.volatile.shared.u32 %0, [%1+4];" : "=r"(t0) : "r"(flg));
            step(k * SLOTB, 0);
            if (mp == mend || now < dl) {
                if (mp == mend) phase_end();
                asm volatile("{.reg .pred p; .reg .u32 d;\n"
                             "PACE_LOOP: mov.u32 d, %%globaltimer_lo; sub.u32 d, %0, d; setp.lt.u32 p, d, 32768; @p nanosleep.u32 32; @p bra.uni PACE_LOOP;}"
                             :: "r"(dl) : "memory");
            }
        }
    }
    __syncwarp();
    step(0, 1); step(SLOTB, 2); step(2 * SLOTB, 3); step(3 * SLOTB, 4);
    WSTAMP(3);

    {
        putacc((uint32_t*)(smem + SM_RING + 2 * SLOTB + w * 2048 + 512) + lane);
        asm volatile("cp.async.wait_all;" ::: "memory");
        mbar_wait(mbarW, 0);
        asm volatile("fence.proxy.async.shared::cta;" ::: "memory");
        const int wg = w >> 2, w4 = w & 3;
        TSTAMP(26);
        bar_sync(2 + wg, 128);
        TSTAMP(27);
        const uint64_t descA0 = (uint64_t)(((sb + SM_RING) & 0x3FFFF) >> 4) | ((uint64_t)1 << 16) | ((uint64_t)(1024 >> 4) << 32) | ((uint64_t)1 << 62);
        const uint64_t descB0 = (uint64_t)(((sb + SM_RING + SLOTB + wg * 8192) & 0x3FFFF) >> 4) | ((uint64_t)(128 >> 4) << 16) | ((uint64_t)(1024 >> 4) << 32);
        float d[2][32];
        asm volatile("wgmma.fence.sync.aligned;" ::: "memory");
#pragma unroll
        for (int mt = 0; mt < 2; mt++) {
#pragma unroll
            for (int ks = 0; ks < 8; ks++) {
                const uint64_t da = descA0 + (uint64_t)((ks * 2048 + mt * 16384) >> 4), db = descB0 + (uint64_t)(((ks & 3) * 256 + (ks >> 2) * SLOTB) >> 4);
                asm volatile("{.reg .pred p; setp.ne.b32 p, %34, 0;\n"
                    "wgmma.mma_async.sync.aligned.m64n64k16.f32.bf16.bf16 "
                    "{%0,%1,%2,%3,%4,%5,%6,%7,%8,%9,%10,%11,%12,%13,%14,%15,%16,%17,%18,%19,%20,%21,%22,%23,%24,%25,%26,%27,%28,%29,%30,%31}, %32, %33, p, 1, 1, 1, 1;}"
                    : "+f"(d[mt][0]), "+f"(d[mt][1]), "+f"(d[mt][2]), "+f"(d[mt][3]), "+f"(d[mt][4]), "+f"(d[mt][5]), "+f"(d[mt][6]), "+f"(d[mt][7]),
                      "+f"(d[mt][8]), "+f"(d[mt][9]), "+f"(d[mt][10]), "+f"(d[mt][11]), "+f"(d[mt][12]), "+f"(d[mt][13]), "+f"(d[mt][14]), "+f"(d[mt][15]),
                      "+f"(d[mt][16]), "+f"(d[mt][17]), "+f"(d[mt][18]), "+f"(d[mt][19]), "+f"(d[mt][20]), "+f"(d[mt][21]), "+f"(d[mt][22]), "+f"(d[mt][23]),
                      "+f"(d[mt][24]), "+f"(d[mt][25]), "+f"(d[mt][26]), "+f"(d[mt][27]), "+f"(d[mt][28]), "+f"(d[mt][29]), "+f"(d[mt][30]), "+f"(d[mt][31])
                    : "l"(da), "l"(db), "r"(ks));
            }
            asm volatile("wgmma.commit_group.sync.aligned;" ::: "memory");
        }
        int nd[8];
#pragma unroll
        for (int j = 0; j < 8; j++) { const int l = wg * 8 + j; nd[j] = order[(t >> 1) ? 79 - l : l]; }
        const bool odd = t & 1;
        uint2* ob = (uint2*)out + (size_t)n0 * 128 + w4 * 16 + g + (odd ? 8 : 0);
#pragma unroll
        for (int mt = 0; mt < 2; mt++) {
            if (mt == 0) asm volatile("wgmma.wait_group.sync.aligned 1;" ::: "memory");
            else asm volatile("wgmma.wait_group.sync.aligned 0;" ::: "memory");
            TSTAMP(23 + mt);
#pragma unroll
            for (int i = 0; i < 32; i++) asm volatile("" : "+f"(d[mt][i]) :: "memory");
#pragma unroll
            for (int j = 0; j < 8; j++) {
                const uint32_t v0 = pack2(d[mt][4 * j], d[mt][4 * j + 1]), v1 = pack2(d[mt][4 * j + 2], d[mt][4 * j + 3]);
                const uint32_t rv = __shfl_xor_sync(0xffffffff, odd ? v0 : v1, 1);
                if (nd[j] < nn) ob[nd[j] * 128 + mt * 64] = odd ? make_uint2(rv, v1) : make_uint2(v0, rv);
            }
        }
    }
    TSTAMP(8);
}

}

extern "C" void kernel_launch(void* const* d_in, const int* in_sizes, int n_in, void* d_out, int out_size) {
    (void)in_sizes; (void)n_in; (void)out_size;
    cudaFuncSetAttribute(tfn_kernel, cudaFuncAttributeMaxDynamicSharedMemorySize, SM_TOTAL);
    Scratch* gs = nullptr;
    cudaGetSymbolAddress((void**)&gs, g_scratch);
    cudaLaunchConfig_t cfg = {};
    cfg.gridDim = dim3(NB); cfg.blockDim = dim3(NT); cfg.dynamicSmemBytes = SM_TOTAL; cfg.stream = cudaStreamPerThread;
    cudaLaunchAttribute at[1];
    at[0].id = cudaLaunchAttributeCooperative; at[0].val.cooperative = 1;
    cfg.attrs = at; cfg.numAttrs = 1;
    cudaLaunchKernelEx(&cfg, tfn_kernel, (const unsigned char*)d_in[0], (const int4*)d_in[1], (const int4*)d_in[2],
                       (const uint4*)d_in[3], (const uint4*)d_in[4], (const uint16_t*)d_in[5], (const uint16_t*)d_in[6],
                       (const uint4*)d_in[7], (uint32_t*)d_out, gs);
}
```

```cpp
#include <cuda_runtime.h>
#include <cuda_bf16.h>
#include <stdint.h>

#define VOL
#define ORD 1
#define ABL 0
namespace {

constexpr int NN = 10000;
constexpr int NE = 320000;
constexpr int NB = 132;
constexpr int NW = 20;
constexpr int NT = NW * 32;
constexpr int CW = NW - 1;
constexpr int PW = 10;
constexpr int NPB = 76;
constexpr int CELL = 48;
constexpr int CAP = 19;
constexpr int DS = 4;
constexpr int STEPB = 160;
constexpr int NE4 = NE / 4;
constexpr int NPIECE = NB * 8;
constexpr int KB = 320, KN = 32 * KB;
constexpr uint32_t F_WRAP = 1;

constexpr int SLOTB = NW * 2048;
constexpr int SM_RING = 0;
constexpr int SM_META = SM_RING + DS * SLOTB;
constexpr int SM_AZ = SM_META + NW * CAP * STEPB;
constexpr int SM_MISC = SM_AZ + 2048;
constexpr int SM_TOTAL = SM_MISC + 2560;
constexpr int SM_STAGE = SM_RING;
constexpr int SM_HIST = SM_RING + 25600;
constexpr int SM_POS = SM_RING;
constexpr int SM_SMALL = SM_HIST + 13056;
constexpr int SM_LIST = SM_RING + 2 * SLOTB;
constexpr int SM_RECS = SM_RING + 3 * SLOTB;
constexpr int SM_RAWY = SM_META;
constexpr int SM_RAWE = SM_RAWY + 608 * 32;
constexpr int SM_KEYS = SM_RAWE + 608 * 32;
static_assert(SM_TOTAL <= 232448 && SM_KEYS + NPIECE * 16 <= SM_AZ, "smem");
static_assert(SM_RECS + NB * CELL * 16 + 16 <= SM_AZ && SM_KEYS + NPIECE * 16 <= SM_RECS + NB * CELL * 16 && SM_SMALL + 1152 <= SLOTB && DS == 4, "smem");

struct Scratch {
    uint4 keys[NB * NPIECE];
    uint4 recs[NB * NB * CELL];
    uint4 stash[NB * NW * 256];
    unsigned bar[4];
    unsigned long long t0, pad;
};
__device__ Scratch g_scratch;
#define TSTAMP(i)
#define TSTAMPC(i)
#define WSTAMP(i)

__device__ __forceinline__ void mma16816(float* d, uint32_t a0, uint32_t a1, uint32_t a2, uint32_t a3, uint32_t b0, uint32_t b1) {
    asm VOL("mma.sync.aligned.m16n8k16.row.col.f32.bf16.bf16.f32 {%0,%1,%2,%3}, {%4,%5,%6,%7}, {%8,%9}, {%0,%1,%2,%3};"
        : "+f"(d[0]), "+f"(d[1]), "+f"(d[2]), "+f"(d[3]) : "r"(a0), "r"(a1), "r"(a2), "r"(a3), "r"(b0), "r"(b1));
}
__device__ __forceinline__ void mma1688z(float* d, uint32_t a0, uint32_t a1, uint32_t b0) {
    asm VOL("mma.sync.aligned.m16n8k8.row.col.f32.bf16.bf16.f32 {%0,%1,%2,%3}, {%4,%5}, {%6}, {%7,%7,%7,%7};"
        : "=f"(d[0]), "=f"(d[1]), "=f"(d[2]), "=f"(d[3]) : "r"(a0), "r"(a1), "r"(b0), "f"(0.f));
}
__device__ __forceinline__ uint32_t pack2(float lo, float hi) {
    uint32_t r; asm VOL("cvt.rn.bf16x2.f32 %0, %1, %2;" : "=r"(r) : "f"(hi), "f"(lo)); return r;
}
__device__ __forceinline__ float silu_h(float h) {
    float t; asm VOL("tanh.approx.f32 %0, %1;" : "=f"(t) : "f"(h)); return fmaf(h, t, h);
}
__device__ __forceinline__ uint32_t mul_lo(uint32_t v, uint32_t r) {
    __nv_bfloat162 a = *(__nv_bfloat162*)&v, b = *(__nv_bfloat162*)&r; __nv_bfloat162 c = __hmul2(a, __low2bfloat162(b)); return *(uint32_t*)&c;
}
__device__ __forceinline__ uint32_t mul_hi(uint32_t v, uint32_t r) {
    __nv_bfloat162 a = *(__nv_bfloat162*)&v, b = *(__nv_bfloat162*)&r; __nv_bfloat162 c = __hmul2(a, __high2bfloat162(b)); return *(uint32_t*)&c;
}
__device__ __forceinline__ uint2 lds64(uint32_t a) {
    uint2 r; asm volatile("ld.shared.v2.u32 {%0,%1}, [%2];" : "=r"(r.x), "=r"(r.y) : "r"(a)); return r;
}
__device__ __forceinline__ uint4 lds128(uint32_t a) {
    uint4 r; asm volatile("ld.shared.v4.u32 {%0,%1,%2,%3}, [%4];" : "=r"(r.x), "=r"(r.y), "=r"(r.z), "=r"(r.w) : "r"(a) : "memory"); return r;
}
__device__ __forceinline__ void bar_sync(int id, int n) { asm volatile("bar.sync %0, %1;" :: "r"(id), "r"(n) : "memory"); }
__device__ __forceinline__ void bar_arrive(int id, int n) { asm volatile("bar.arrive %0, %1;" :: "r"(id), "r"(n) : "memory"); }
__device__ __forceinline__ void mbar_wait(uint32_t bar, uint32_t ph) {
    uint32_t done; int spins = 0;
    do {
        asm volatile("{.reg .pred p; mbarrier.try_wait.parity.shared.b64 p, [%1], %2; selp.u32 %0,1,0,p;}" : "=r"(done) : "r"(bar), "r"(ph) : "memory");
    } while (!done && ++spins < (1 << 22));
}
__device__ __forceinline__ unsigned gbar_read(const unsigned* ctr) {
    unsigned v; asm volatile("ld.relaxed.gpu.global.u32 %0, [%1];" : "=r"(v) : "l"(ctr) : "memory");
    return v;
}
__device__ __forceinline__ void gbar_arrive(unsigned* ctr) {
    asm volatile("red.add.release.gpu.global.u32 [%0], 1;" :: "l"(ctr) : "memory");
}
__device__ __forceinline__ void gbar_wait(const unsigned* ctr, unsigned target) {
    unsigned v; int spins = 0;
    do { asm volatile("ld.acquire.gpu.global.u32 %0, [%1];" : "=r"(v) : "l"(ctr) : "memory"); } while ((int)(v - target) < 0 && ++spins < (1 << 22));
}
__device__ __forceinline__ int chunk_start4(int c) { return (c * NE4) / NB; }
__device__ __forceinline__ float bf2f(uint32_t h) { return __uint_as_float(h << 16); }

__device__ __noinline__ void slow_path(unsigned char* smem, int n0, int nn, const uint16_t* x, const int* src, const int* dst,
                                       const uint16_t* Y, const uint16_t* ef, const uint16_t* w_rad, const uint16_t* cg,
                                       const uint16_t* w_mix, __nv_bfloat16* out) {
    float* agg = (float*)smem;
    const int tid = threadIdx.x, lane = tid & 31, w = tid >> 5;
    bar_sync(1, NT);
    for (int i = tid; i < NPB * 512; i += NT) agg[i] = 0.f;
    bar_sync(1, NT);
    for (int e0 = w * 32; e0 < NE; e0 += NT) {
        int dl = dst[e0 + lane] - n0;
        unsigned m = __ballot_sync(0xffffffff, dl >= 0 && dl < nn);
        while (m) {
            int l = __ffs(m) - 1; m &= m - 1;
            int e = e0 + l, d = __shfl_sync(0xffffffff, dl, l), s = src[e];
            float T[16];
            for (int i = 0; i < 4; i++) for (int o = 0; o < 4; o++) {
                float a = 0.f;
                for (int f = 0; f < 4; f++) a += bf2f(Y[e * 4 + f]) * bf2f(cg[i * 16 + f * 4 + o]);
                T[i * 4 + o] = a;
            }
            for (int k = 0; k < 4; k++) {
                int c = lane + 32 * k;
                float z = 0.f;
                for (int j = 0; j < 4; j++) z += bf2f(ef[e * 4 + j]) * bf2f(w_rad[j * 128 + c]);
                float R = z / (1.f + __expf(-z));
                for (int o = 0; o < 4; o++) {
                    float a = 0.f;
                    for (int i = 0; i < 4; i++) a += bf2f(x[(size_t)s * 512 + c * 4 + i]) * T[i * 4 + o];
                    atomicAdd(&agg[d * 512 + c * 4 + o], R * a);
                }
            }
        }
    }
    bar_sync(1, NT);
    for (int i = tid; i < nn * 512; i += NT) {
        int n = i >> 9, d = (i >> 2) & 127, o = i & 3;
        float a = 0.f;
        for (int c = 0; c < 128; c++) a += agg[n * 512 + c * 4 + o] * bf2f(w_mix[c * 128 + d]);
        out[(size_t)(n0 + n) * 512 + (i & 511)] = __float2bfloat16(a);
    }
}

#define PACE 24000
#define YDELAY 300
#define NB0 4
#define TP 0
#define EPI 2
#define LEAD 0
#define RELAT 2
#define MATCH 0
#define POFF 1700
#define PTOL 600
__global__ void __launch_bounds__(NT, 1)
tfn_kernel(const unsigned char* __restrict__ x, const int4* __restrict__ src4, const int4* __restrict__ dst4,
           const uint4* __restrict__ Y, const uint4* __restrict__ ef, const uint16_t* __restrict__ w_rad,
           const uint16_t* __restrict__ cg, const uint4* __restrict__ w_mix, uint32_t* __restrict__ out, Scratch* __restrict__ gs) {
    extern __shared__ __align__(1024) unsigned char smem[];
    const uint32_t sb = (uint32_t)__cvta_generic_to_shared(smem);
    const int b = blockIdx.x, tid = threadIdx.x, lane = tid & 31, g = lane >> 2, t = lane & 3;
    const int w = __shfl_sync(0xffffffff, tid >> 5, 0);
    uint32_t* stage = (uint32_t*)(smem + SM_STAGE);
    uint32_t* hist = (uint32_t*)(smem + SM_HIST);
    uint32_t* cnt = (uint32_t*)(smem + SM_MISC);
    uint32_t* deg = cnt + 136;
    uint32_t* order = deg + 104;
    uint32_t* cnt2 = order + 80;
    volatile uint32_t* flag = cnt2 + 136;
    const uint32_t mbarK = sb + SM_MISC + 1920, mbarR = mbarK + 8, mbarW = mbarK + 16;
    const int n0 = b * NPB, nn = min(NPB, NN - n0);
    TSTAMP(0);

    const int c0 = chunk_start4(b), c1 = chunk_start4(b + 1);
    const bool has4 = c0 + tid < c1;
    int4 d4 = make_int4(0, 0, 0, 0), s4 = d4;
    if (has4) { d4 = __ldg(dst4 + c0 + tid); s4 = __ldg(src4 + c0 + tid); }
    unsigned tgt = 0;
    if (tid == NT - 1) {
        tgt = gbar_read(&gs->bar[0]);
        asm volatile("mbarrier.init.shared.b64 [%0], 1;" :: "r"(mbarK));
        asm volatile("mbarrier.init.shared.b64 [%0], 1;" :: "r"(mbarR));
        asm volatile("mbarrier.init.shared.b64 [%0], 512;" :: "r"(mbarW));
        asm volatile("fence.mbarrier_init.release.cluster;" ::: "memory");
        flag[0] = 0; flag[12] = 0; flag[13] = 0;
    }
    if (w == CW) {
        asm volatile("cp.async.cg.shared.global [%0], [%1], 16;" :: "r"(sb + SM_SMALL + lane * 16), "l"(w_rad + lane * 8) : "memory");
        asm volatile("cp.async.cg.shared.global [%0], [%1], 16;" :: "r"(sb + SM_SMALL + 512 + lane * 16), "l"(w_rad + 256 + lane * 8) : "memory");
        if (lane < 8) asm volatile("cp.async.cg.shared.global [%0], [%1], 16;" :: "r"(sb + SM_SMALL + 1024 + lane * 16), "l"(cg + lane * 8) : "memory");
    }
    ((uint4*)hist)[tid] = make_uint4(0, 0, 0, 0);
    {
        const uint32_t dk = ((80 + b % 22) * KN + (b & 31) * KB) << 12;
#pragma unroll
        for (int j = 0; j < 3; j++) if (tid + j * NT < NB * CELL / 4) ((uint4*)stage)[tid + j * NT] = make_uint4(dk, dk, dk, dk);
    }
    if (tid < 136) cnt[tid] = 0;
    if (tid == 0) { *(uint4*)(smem + SM_MISC + 1824 + 32) = make_uint4(0, 0, 0, 0); cnt2[NB] = 0; *(uint4*)(smem + SM_RECS + NB * CELL * 16) = make_uint4(0, 0, 0, 0); }
    if (tid < 80) { deg[tid] = 127 - tid; order[tid] = tid; }
    __syncthreads();
    TSTAMP(9);
    if (tid == 64) {
        if (YDELAY) __nanosleep(YDELAY);
        asm volatile("mbarrier.arrive.expect_tx.shared.b64 _, [%0], %1;" :: "r"(mbarR), "r"((c1 - c0) * 64) : "memory");
        asm volatile("cp.async.bulk.shared::cluster.global.mbarrier::complete_tx::bytes [%0], [%1], %2, [%3];"
                     :: "r"(sb + SM_RAWY), "l"(Y + 2 * c0), "r"((c1 - c0) * 32), "r"(mbarR) : "memory");
        asm volatile("cp.async.bulk.shared::cluster.global.mbarrier::complete_tx::bytes [%0], [%1], %2, [%3];"
                     :: "r"(sb + SM_RAWE), "l"(ef + 2 * c0), "r"((c1 - c0) * 32), "r"(mbarR) : "memory");
    }

    if (has4) {
        const uint32_t dd[4] = {(uint32_t)d4.x, (uint32_t)d4.y, (uint32_t)d4.z, (uint32_t)d4.w}, ss[4] = {(uint32_t)s4.x, (uint32_t)s4.y, (uint32_t)s4.z, (uint32_t)s4.w};
        uint32_t bin[4], slot[4];
#pragma unroll
        for (int k = 0; k < 4; k++) { bin[k] = dd[k] / NPB; slot[k] = atomicAdd(&cnt[bin[k]], 1); }
#pragma unroll
        for (int k = 0; k < 4; k++)
            stage[bin[k] * CELL + min(slot[k], CELL - 1)] = (((dd[k] - bin[k] * NPB) * KN + ss[k]) << 12) + tid * 4 + k;
    }
    if (w == CW) asm volatile("cp.async.wait_all;" ::: "memory");
    bar_sync(1, NT);
    TSTAMP(1);
#pragma unroll
    for (int j = 0; j < 2; j++) {
        const int i = tid + j * NT;
        if (i < NPIECE) {
            const uint2 sa = *(const uint2*)(stage + i * 6), sc = *(const uint2*)(stage + i * 6 + 2), se = *(const uint2*)(stage + i * 6 + 4);
            const uint32_t cn = min(cnt[i >> 3], 255u);
            gs->keys[((i >> 3) * NB + b) * 8 + ((i ^ b) & 7)] =
                make_uint4(__funnelshift_r(sa.x, se.x >> 12, 12), __funnelshift_r(sa.y, __funnelshift_r(se.x, cn, 24), 12),
                           __funnelshift_r(sc.x, se.y >> 12, 12), __funnelshift_r(sc.y, __funnelshift_r(se.y, cn >> 4, 24), 12));
        }
    }
    uint2 yy[7], ee[7];
    uint32_t cno[7];
    uint4* rp = gs->recs + (w * NB + b) * CELL + lane;
    auto recs_out = [&](int j0, int j1) {
#pragma unroll
        for (int j = 0; j < 7; j++) if (j >= j0 && j < j1)
            asm volatile("{.reg .pred p; setp.lt.u32 p, %5, %6; @p st.global.v4.u32 [%0], {%1,%2,%3,%4};}"
                         :: "l"(rp + j * (CW * NB * CELL)), "r"(yy[j].x), "r"(ee[j].x), "r"(yy[j].y), "r"(ee[j].y), "r"(lane & ~1), "r"(cno[j]) : "memory");
    };
    if (w == CW) {
        bar_sync(7, NT);
        if (tid == NT - 1) {
            TSTAMPC(10);
            gbar_arrive(&gs->bar[0]);
            TSTAMPC(11);
            tgt = (tgt / NB + 1) * NB;
            asm volatile("mbarrier.arrive.expect_tx.shared.b64 _, [%0], %1;" :: "r"(mbarK), "r"(NPIECE * 16) : "memory");
            gbar_wait(&gs->bar[0], tgt);
            TSTAMPC(13);
            asm volatile("fence.proxy.async.global;" ::: "memory");
            asm volatile("cp.async.bulk.shared::cluster.global.mbarrier::complete_tx::bytes [%0], [%1], %2, [%3];"
                         :: "r"(sb + SM_KEYS), "l"(gs->keys + b * NPIECE), "r"(NPIECE * 16), "r"(mbarK) : "memory");
        }
        __syncwarp();
        bar_arrive(8, NT);
    } else {
        bar_arrive(7, NT);
        if (w < 8) {
            const uint32_t* wp = (const uint32_t*)(smem + SM_SMALL) + (t & 1) * 128 + 8 * w + g;
            const uint32_t wr0 = t < 2 ? wp[0] : 0, wr1 = t < 2 ? wp[64] : 0;
            *(uint2*)(smem + SM_AZ + (w >> 1) * 512 + lane * 16 + (w & 1) * 8) =
                make_uint2(pack2(0.5f * bf2f(wr0 & 0xFFFF), 0.5f * bf2f(wr1 & 0xFFFF)), pack2(0.5f * bf2f(wr0 >> 16), 0.5f * bf2f(wr1 >> 16)));
        }
        uint32_t el[7], big = 0;
#pragma unroll
        for (int j = 0; j < 7; j++) {
            const int cell = w + CW * j;
            cno[j] = cnt[cell];
            el[j] = (stage[cell * CELL + lane] & 0xFFF) * 8;
            big |= cno[j] > 32;
        }
        mbar_wait(mbarR, 0);
        TSTAMP(18);
#pragma unroll
        for (int j = 0; j < 7; j++) { yy[j] = lds64(sb + SM_RAWY + el[j]); ee[j] = lds64(sb + SM_RAWE + el[j]); }
        if (big) {
#pragma unroll 1
            for (int j = 0; j < 7; j++) {
                const int cell = w + CW * j;
                if (lane + 32 < min(cnt[cell], CELL)) {
                    const uint32_t e2 = (stage[cell * CELL + 32 + lane] & 0xFFF) * 8;
                    const uint2 y2 = *(const uint2*)(smem + SM_RAWY + e2), e3 = *(const uint2*)(smem + SM_RAWE + e2);
                    rp[j * (CW * NB * CELL) + 32] = make_uint4(y2.x, e3.x, y2.y, e3.y);
                }
            }
        }
        bar_sync(8, NT);
        recs_out(0, NB0);
    }
    __syncwarp();
    TSTAMP(2);
    uint32_t at[4];
    {
        const int o = g & 3, f = 2 * (t & 1);
#pragma unroll
        for (int i = 0; i < 4; i++) {
            const uint16_t* cp = (const uint16_t*)(smem + SM_SMALL + 1024) + i * 16 + f * 4 + o;
            at[i] = (t >> 1) == (g >> 2) ? cp[0] | ((uint32_t)cp[4] << 16) : 0;
        }
    }

    uint32_t key[2][6], ha[2][6], rk[2][6], kidx[2];
    int nk[2] = {0, 0};
    unsigned seenB = 0;
    if (w < CW) {
        uint32_t ka[2];
#pragma unroll
        for (int j = 0; j < 2; j++) {
            const int i0 = j ? 2 * 608 - 1 - tid : tid, i = min(i0, NPIECE - 1), r = i / NB, c = i - r * NB;
            ka[j] = sb + SM_KEYS + (c * 8 + ((r ^ c) & 7)) * 16;
            kidx[j] = (c * CELL + r * 6) << 17;
            nk[j] = i0 < NPIECE ? -6 * r : -1000;
        }
        mbar_wait(mbarK, 0);
        TSTAMP(3);
        const uint4 v[2] = {lds128(ka[0]), lds128(ka[1])};
#pragma unroll
        for (int j = 0; j < 2; j++) {
            const uint32_t hc = (v[j].y >> 28) | ((v[j].w >> 28) << 4);
            if (j == 0 && tid < NB) cnt2[tid] = hc;
            nk[j] += hc;
            if (nk[j] > 0) {
                key[j][0] = v[j].x & 0xFFFFF; key[j][1] = v[j].y & 0xFFFFF; key[j][2] = v[j].z & 0xFFFFF; key[j][3] = v[j].w & 0xFFFFF;
                key[j][4] = (v[j].x >> 20) | ((v[j].y >> 8) & 0xFF000); key[j][5] = (v[j].z >> 20) | ((v[j].w >> 8) & 0xFF000);
#pragma unroll
                for (int u = 0; u < 6; u++) {
                    ha[j][u] = __umulhi(key[j][u], 0xFFFFFFFFu / KB + 1);
                    rk[j][u] = atomicAdd(&hist[ha[j][u]], 1);
                    atomicAdd(&deg[ha[j][u] >> 5], 128);
                }
            }
        }
        recs_out(NB0, 7);
        bar_sync(10, NT);
        TSTAMP(20);
        const int n = tid >> 3, sub = tid & 7;
        const uint32_t me = deg[n];
        int r = 0;
#pragma unroll
        for (int k = 0; k < 5; k++) { const uint2 dd = *(const uint2*)(deg + sub * 10 + 2 * k); r += (dd.x > me) + (dd.y > me); }
        r += __shfl_xor_sync(0xffffffff, r, 1); r += __shfl_xor_sync(0xffffffff, r, 2); r += __shfl_xor_sync(0xffffffff, r, 4);
        if (sub == 0) order[r] = n;
    } else {
        bar_sync(10, NT);
        if (tid == NT - 1) { TSTAMPC(14); gbar_arrive(&gs->bar[1]); TSTAMPC(15); seenB = gbar_read(&gs->bar[1]); }
    }
    __syncwarp();
    bar_sync(1, NT);
    TSTAMP(22);
    const uint32_t cn = cnt2[min(w + NW * lane, NB)];
    if (cn > CELL) *flag = 1;
    auto recs_in = [&]() {
        const uint4* gp = gs->recs + (b * NB + w) * CELL + lane;
        const uint32_t sp = sb + SM_RECS + (w * CELL + lane) * 16;
#pragma unroll
        for (int j = 0; j < 7; j++)
            asm volatile("{.reg .pred p; setp.lt.u32 p, %2, %3; @p cp.async.cg.shared.global [%0], [%1], 16;}"
                         :: "r"(sp + j * (NW * CELL * 16)), "l"(gp + j * (NW * CELL)), "r"(lane), "r"(__shfl_sync(0xffffffff, cn, j)) : "memory");
        if (__any_sync(0xffffffff, cn > 32)) {
#pragma unroll 1
            for (int j = 0; j < 7; j++)
                if (lane + 32 < min(__shfl_sync(0xffffffff, cn, j), CELL))
                    asm volatile("cp.async.cg.shared.global [%0], [%1], 16;" :: "r"(sp + j * (NW * CELL * 16) + 512), "l"(gp + j * (NW * CELL) + 32) : "memory");
        }
        asm volatile("cp.async.commit_group;" ::: "memory");
    };
    int S, mylen;
    {
        const uint2 na = *(const uint2*)(order + 2 * w), nb = *(const uint2*)(order + 78 - 2 * w);
        const uint32_t ia0 = na.x * 32 + lane, ib0 = nb.y * 32 + lane, ia1 = na.y * 32 + lane, ib1 = nb.x * 32 + lane;
        const uint32_t ca = hist[ia0] + (hist[ia1] << 16), cab = ca + hist[ib0] + (hist[ib1] << 16);
        uint32_t inc = cab;
#pragma unroll
        for (int o = 1; o < 32; o <<= 1)
            asm volatile("{.reg .pred p; .reg .u32 u; shfl.sync.up.b32 u|p, %0, %1, 0, 0xffffffff; @p add.u32 %0, %0, u;}" : "+r"(inc) : "r"(o));
        const uint32_t ea = inc - cab, eb = ea + ca, base = sb + SM_LIST + w * 2048;
        uint2* pos = (uint2*)(smem + SM_POS);
        pos[ia0] = make_uint2(base + (ea & 0xFFFF) * 8, na.x * (0u - 4 * KN));
        pos[ib0] = make_uint2(base + (eb & 0xFFFF) * 8, nb.y * (0u - 4 * KN) + 0x10000);
        pos[ia1] = make_uint2(base + 4 + (ea >> 16) * 8, na.y * (0u - 4 * KN));
        pos[ib1] = make_uint2(base + 4 + (eb >> 16) * 8, nb.x * (0u - 4 * KN) + 0x10000);
        const uint32_t len = __shfl_sync(0xffffffff, inc, 31);
        S = (max(len & 0xFFFF, len >> 16) + 3) >> 2;
        mylen = (lane & 1) ? len >> 16 : len & 0xFFFF;
        if (S > CAP) *flag = 1;
        S = __shfl_sync(0xffffffff, max(S, DS + 1), 0);
    }
    if (tid == NT - 1) {
        TSTAMPC(16);
        if ((int)(seenB - tgt) < 0) gbar_wait(&gs->bar[1], tgt);
        else asm volatile("fence.acq_rel.cta;" ::: "memory");
        TSTAMPC(17);
    }
    bar_sync(1, NT);
    TSTAMP(21);
    if (*flag) {
        slow_path(smem, n0, nn, (const uint16_t*)x, (const int*)src4, (const int*)dst4, (const uint16_t*)Y, (const uint16_t*)ef, w_rad, cg,
                  (const uint16_t*)w_mix, (__nv_bfloat16*)out);
        return;
    }
    recs_in();
#pragma unroll
    for (int j = 0; j < 2; j++) {
        if (nk[j] > 0) {
            uint2 h[6];
#pragma unroll
            for (int u = 0; u < 6; u++) h[u] = lds64(sb + SM_POS + ha[j][u] * 8);
#pragma unroll
            for (int u = 0; u < 6; u++)
                asm volatile("{.reg .pred p; setp.gt.s32 p, %2, %3; @p st.shared.u32 [%0], %1;}"
                             :: "r"(h[u].x + rk[j][u] * 8), "r"(key[j][u] * 4 + h[u].y + (kidx[j] + (u << 17))), "r"(nk[j]), "r"(u) : "memory");
        }
    }
    bar_sync(1, NT);
    TSTAMP(4);
    constexpr int NRAW = (CAP + 3) / 4;
    uint32_t bits0 = 0, raw[NRAW];
    unsigned char* meta = smem + SM_META + w * (CAP * STEPB);
#pragma unroll
    for (int k = 0; k < NRAW; k++) raw[k] = mylen ? ((uint32_t*)(smem + SM_LIST + w * 2048))[min(k * 16 + (lane >> 1), mylen - 1) * 2 + (lane & 1)] : 4 * n0;
    const uint32_t sv0 = raw[0] & 0xFFFF;
    const int q = lane >> 3, c = lane & 7;
    const uint32_t ring0 = sb + SM_RING + w * 2048;
    uint32_t wdst = ring0 + q * 128 + ((c + 2 * q) & 7) * 16;
    uint32_t rsrc = ring0 + t * 128 + ((g + 2 * t) & 7) * 16;
    uint32_t recl = sb + SM_META + w * (CAP * STEPB) + g * 16 + (t & 1) * 8, srcl = sb + SM_META + w * (CAP * STEPB) + 128 + q * 8;
    uint32_t flg = sb + SM_MISC + (136 + 104 + 80 + 136) * 4;
    asm volatile("" : "+r"(wdst), "+r"(rsrc), "+r"(recl), "+r"(srcl), "+r"(flg));
    const unsigned char* pbase = x + c * 16;
    auto cpa2 = [&](uint32_t dstp, uint32_t sv) {
        asm volatile("cp.async.cg.shared.global [%0], [%1], 16; cp.async.cg.shared.global [%0+1024], [%1+128], 16;"
                     :: "r"(dstp), "l"(pbase + (size_t)sv * 256) : "memory");
    };
    auto fill = [&](int i) {
        cpa2(wdst + i * SLOTB, __shfl_sync(0xffffffff, sv0, 8 * i + 2 * q)); cpa2(wdst + i * SLOTB + 512, __shfl_sync(0xffffffff, sv0, 8 * i + 2 * q + 1));
        asm volatile("cp.async.commit_group;" ::: "memory");
    };
    fill(0);
    TSTAMP(5);
    if (w == 0) {
        unsigned long long tbase;
        asm volatile("mov.u64 %0, %%globaltimer;" : "=l"(tbase));
        tbase += POFF;
        flag[1] = (uint32_t)tbase; flag[2] = (uint32_t)tbase; flag[4] = (uint32_t)tbase; flag[5] = (uint32_t)(tbase >> 32);
        if (lane == 0) {
            asm volatile("red.max.relaxed.gpu.global.u64 [%0], %1;" :: "l"(&gs->t0), "l"(tbase) : "memory");
            if (b < 128) asm volatile("cp.async.bulk.prefetch.L2.global [%0], 256;" :: "l"(w_mix + b * 16));
        }
    }
    uint32_t ra[NRAW];
#pragma unroll
    for (int k = 0; k < NRAW; k++) {
        const uint32_t m = (__ballot_sync(0xffffffff, raw[k] & 0x10000) >> g) & 0x01010101u;
        bits0 |= ((m * 0x10204080u) >> 28) << (4 * k);
        ra[k] = sb + SM_RECS + (k * 16 + (lane >> 1) < mylen ? raw[k] >> 17 : NB * CELL) * 16;
    }
    if (t < 2) bits0 = ~bits0;
    fill(1);
    asm volatile("cp.async.wait_group 2;" ::: "memory");
    bar_sync(1, NT);
    TSTAMP(19);
    {
        uint4 rv[NRAW];
#pragma unroll
        for (int k = 0; k < NRAW - 1; k++) rv[k] = lds128(ra[k]);
        if ((NRAW - 1) * 4 < S) rv[NRAW - 1] = lds128(ra[NRAW - 1]);
        if (tid == 0) asm volatile("cp.async.cg.shared.global [%0], [%1], 16;" :: "r"(sb + SM_MISC + 1824 + 32), "l"(&gs->t0) : "memory");
        fill(2);
        bar_sync(1, NT);
        TSTAMP(12);
        unsigned char* mr = meta + (q - 1) * STEPB + c * 16;
        unsigned char* ms = meta + (q - DS - 1) * STEPB + 128 + c * 4;
#pragma unroll
        for (int k = 0; k < NRAW; k++) {
            if (k == 0) {
                *(uint4*)(mr + (q == 0 ? S * STEPB : 0)) = rv[k];
                *(uint32_t*)(ms + S * STEPB) = sv0 + F_WRAP;
            } else if (k * 4 + q < S) {
                *(uint4*)(mr + k * 4 * STEPB) = rv[k];
                *(uint32_t*)(ms + k * 4 * STEPB + (k == 1 && q == 0 ? S * STEPB : 0)) = raw[k] & 0xFFFF;
            }
        }
    }
    __syncwarp();
    const uint32_t tphase = PACE / 4;
    uint32_t dreg;
    {
        const int st = lane == 0 ? S - 1 : min(lane, S) - 1;
        const uint4 u0 = *(const uint4*)(meta + st * STEPB + 128), u1 = *(const uint4*)(meta + st * STEPB + 144);
        int pos = (u0.x + u0.y + u0.z + u0.w + u1.x + u1.y + u1.z + u1.w) >> 5;
        pos += ((u0.x & F_WRAP) ? NN : 0) + (lane == S ? NN : 0) - NN * (2 * DS + 1) / 32;
        dreg = pos * (int)tphase / NN;
    }
    fill(3);
    TSTAMP(6);

    uint32_t* stash = (uint32_t*)(gs->stash + (b * NW + w) * 256) + lane;
    float acc[4][4];
#pragma unroll
    for (int i = 0; i < 16; i++) acc[i / 4][i % 4] = 0.f;
    uint4 az = *(const uint4*)(smem + SM_AZ + lane * 16);
    uint32_t dcur = dreg, dl = 0, now = flag[1], tcur = 0;
    uint32_t mp = 0, smask = 1;
    const uint32_t mend = S * STEPB;
    uint2 r = lds64(mend - STEPB + recl), s0 = lds64(mend - STEPB + srcl);
    auto step = [&](const uint32_t off, const int mode) {
        auto tick = [&]() { if (mode == 0) { unsigned long long n64; asm volatile("mov.u64 %0, %%globaltimer;" : "=l"(n64)); now = (uint32_t)n64; } };
        if (TP == 0) tick();
        const uint2 rc = r, sc = s0;
        if (ORD & 1) { if (mode != 4) r = lds64(mp + recl); if (mode == 0) s0 = lds64(mp + srcl); }
        asm volatile("cp.async.wait_group %0;" :: "n"(DS - 1) : "memory");
        const uint4 xa = lds128(rsrc + off), xb = lds128(rsrc + off + 512), xc = lds128(rsrc + off + 1024), xd = lds128(rsrc + off + 1536);
        if (!(ORD & 1) && !(ORD & 4)) { if (mode != 4) r = lds64(mp + recl); if (mode == 0) s0 = lds64(mp + srcl); }
        if (mode == 0) {
            if (ORD & 2) {
                asm volatile("shfl.sync.idx.b32 %0, %1, 1, 31, 0xffffffff; shfl.sync.down.b32 %1, %1, 1, 31, 0xffffffff;\n"
                             "cp.async.cg.shared.global [%2], [%3], 16; cp.async.cg.shared.global [%2+512], [%4], 16;\n"
                             "cp.async.cg.shared.global [%2+1024], [%3+128], 16; cp.async.cg.shared.global [%2+1536], [%4+128], 16;"
                             : "=&r"(dl), "+r"(dcur) : "r"(wdst + off), "l"(pbase + (size_t)sc.x * 256), "l"(pbase + (size_t)sc.y * 256) : "memory");
            } else {
                dl = __shfl_sync(0xffffffff, dcur, 1); dcur = __shfl_down_sync(0xffffffff, dcur, 1);
                cpa2(wdst + off, sc.x); cpa2(wdst + off + 512, sc.y);
            }
        }
        if (mode == 1 && w < 16) {
#pragma unroll
            for (int j = 0; j < 4; j++) {
                const int kk = 4 * j + q, ch = 16 * (w & 7) + 2 * (kk & 7) + (kk >> 3);
                asm volatile("cp.async.cg.shared.global [%0], [%1], 16;" :: "r"(ring0 + kk * 128 + ((c ^ (kk & 7)) << 4)), "l"(w_mix + ch * 16 + (w >> 3) * 8 + c) : "memory");
            }
            asm volatile("cp.async.mbarrier.arrive.noinc.shared.b64 [%0];" :: "r"(mbarW) : "memory");
        }
        if (mode == 2 || mode == 3) {
#pragma unroll
            for (int j = 0; j < 4; j += mode - 1)
                asm volatile("cp.async.cg.shared.global [%0], [%1], 16;" :: "r"(ring0 + off + j * 512 + lane * 16), "l"(stash + (mode - 2) * 512 + j * 128 + lane * 3) : "memory");
        }
        asm volatile("cp.async.commit_group;" ::: "memory");
        if (ORD & 4) { if (mode != 4) r = lds64(mp + recl); if (mode == 0) s0 = lds64(mp + srcl); }
        float z[4], y[4], t1[4], t2[4];
        mma1688z(z, az.x, az.y, rc.y);
        mma1688z(y, az.z, az.w, rc.y);
        uint32_t bt;
        asm("{.reg .pred p; .reg .b32 m; and.b32 m, %2, %3; setp.ne.u32 p, m, 0; selp.b32 %0, %1, 0, p;}" : "=r"(bt) : "r"(rc.x), "r"(bits0), "r"(smask));
        mma1688z(t1, at[0], at[1], bt);
        mma1688z(t2, at[2], at[3], bt);
        if (TP == 1) tick();
        const uint32_t T0 = pack2(t1[0], t1[2]), T1 = pack2(t2[0], t2[2]), T2 = pack2(t1[1], t1[3]), T3 = pack2(t2[1], t2[3]);
        const uint32_t R0 = pack2(silu_h(z[0]), silu_h(z[2]));
        if (TP == 2) tick();
        const uint32_t R1 = pack2(silu_h(z[1]), silu_h(z[3]));
        if (TP == 3) tick();
        const uint32_t R2 = pack2(silu_h(y[0]), silu_h(y[2])), R3 = pack2(silu_h(y[1]), silu_h(y[3]));
        if (TP == 4) tick();
        mma16816(acc[0], mul_lo(xa.x, R0), mul_hi(xa.z, R0), mul_lo(xa.y, R0), mul_hi(xa.w, R0), T0, T1);
        mma16816(acc[1], mul_lo(xb.x, R1), mul_hi(xb.z, R1), mul_lo(xb.y, R1), mul_hi(xb.w, R1), T2, T3);
        mma16816(acc[2], mul_lo(xc.x, R2), mul_hi(xc.z, R2), mul_lo(xc.y, R2), mul_hi(xc.w, R2), T0, T1);
        mma16816(acc[3], mul_lo(xd.x, R3), mul_hi(xd.z, R3), mul_lo(xd.y, R3), mul_hi(xd.w, R3), T2, T3);
        mp += STEPB; smask <<= 1;
    };
    auto putacc = [&](uint32_t* p) {
        p[0] = pack2(acc[0][0], acc[0][1]); p[32] = pack2(acc[0][2], acc[0][3]); p[64] = pack2(acc[2][0], acc[2][1]); p[96] = pack2(acc[2][2], acc[2][3]);
        p[256] = pack2(acc[1][0], acc[1][1]); p[288] = pack2(acc[1][2], acc[1][3]); p[320] = pack2(acc[3][0], acc[3][1]); p[352] = pack2(acc[3][2], acc[3][3]);
    };
    int ph = 0;
    auto phase_end = [&]() {
        az = *(const uint4*)(smem + SM_AZ + (ph + 1) * 512 + lane * 16);
        putacc(stash + (ph >> 1) * 512 + (ph & 1) * 128);
#pragma unroll
        for (int i = 0; i < 16; i++) acc[i / 4][i % 4] = 0.f;
        pbase += 256; mp = 0; smask = 1; ph++;
        dreg += tphase; dcur = dreg + tcur;
        WSTAMP(ph - 1);
    };
    uint32_t t0 = now;
    const bool special = w == 0 || w == PW;
#pragma unroll 1
    for (int it = S - 1; it > 0; it--) {
        if (special) {
            if (w == PW) {
                asm volatile("st.shared.u32 [%0+8], %1;" :: "r"(flg), "r"(now - dl + tcur) : "memory");
            } else {
                uint32_t g0, g1, b0, b1, cand;
                asm volatile("ld.volatile.shared.v2.u32 {%0,%1}, [%5+32]; ld.volatile.shared.v2.u32 {%2,%3}, [%5+16]; ld.volatile.shared.u32 %4, [%5+8];"
                             : "=r"(g0), "=r"(g1), "=r"(b0), "=r"(b1), "=r"(cand) : "r"(flg) : "memory");
                const unsigned long long tb = ((unsigned long long)b1 << 32) | b0;
                const unsigned long long dg = (((unsigned long long)g1 << 32) | g0) - tb;
                const uint32_t t1 = (dg < 30000 && (int)(g0 - t0) > 0) ? g0 : t0;
                cand -= PTOL;
                asm volatile("{.reg .pred p, q; setp.eq.u32 p, %2, 0; setp.gt.and.s32 q, %3, 0, p; st.shared.u32 [%4+4], %5;\n"
                             "@q red.max.relaxed.gpu.global.u64 [%0], %1; @p cp.async.cg.shared.global [%4+32], [%0], 16;}"
                             :: "l"(&gs->t0), "l"(tb + (cand - b0)), "r"(lane), "r"(cand - t1), "r"(flg), "r"(t1) : "memory");
            }
        }
        dcur += t0 - tcur; tcur = t0;
#pragma unroll
        for (int k = 0; k < DS; k++) {
            if (k == DS - 1) asm volatile("ld.volatile.shared.u32 %0, [%1+4];" : "=r"(t0) : "r"(flg));
            step(k * SLOTB, 0);
            if (mp == mend || now < dl) {
                if (mp == mend) phase_end();
                asm volatile("{.reg .pred p; .reg .u32 d;\n"
                             "PACE_LOOP: mov.u32 d, %%globaltimer_lo; sub.u32 d, %0, d; setp.lt.u32 p, d, 32768; @p nanosleep.u32 32; @p bra.uni PACE_LOOP;}"
                             :: "r"(dl) : "memory");
            }
        }
    }
    __syncwarp();
    step(0, 1); step(SLOTB, 2); step(2 * SLOTB, 3); step(3 * SLOTB, 4);
    WSTAMP(3);

    {
        putacc((uint32_t*)(smem + SM_RING + 2 * SLOTB + w * 2048 + 512) + lane);
        const int wg = w >> 2, w4 = w & 3;
        int nd[8];
#pragma unroll
        for (int j = 0; j < 8; j++) { const int l = wg * 8 + j; nd[j] = order[(t >> 1) ? 79 - l : l]; asm volatile("" : "+r"(nd[j])); }
        const bool odd = t & 1;
        uint2* ob = (uint2*)out + (size_t)n0 * 128 + w4 * 16 + g + (odd ? 8 : 0);
        asm volatile("cp.async.wait_all;" ::: "memory");
        mbar_wait(mbarW, 0);
        asm volatile("fence.proxy.async.shared::cta;" ::: "memory");
        TSTAMP(26);
        bar_sync(2 + wg, 128);
        if ((tid & 127) == 0) {
            const uint32_t ticket = atomicAdd((uint32_t*)flag + 12, 1);
            int spins = 0;
            while (flag[13] + LEAD < ticket && ++spins < (1 << 16)) {}
        }
        bar_sync(2 + wg, 128);
        TSTAMP(27);
        const uint64_t descA0 = (uint64_t)(((sb + SM_RING) & 0x3FFFF) >> 4) | ((uint64_t)1 << 16) | ((uint64_t)(1024 >> 4) << 32) | ((uint64_t)1 << 62);
        const uint64_t descB0 = (uint64_t)(((sb + SM_RING + SLOTB + wg * 8192) & 0x3FFFF) >> 4) | ((uint64_t)(128 >> 4) << 16) | ((uint64_t)(1024 >> 4) << 32);
        float d[2][32];
        asm volatile("wgmma.fence.sync.aligned;" ::: "memory");
#pragma unroll
        for (int mt = 0; mt < 2; mt++) {
#pragma unroll
            for (int ks = 0; ks < 8; ks++) {
                const uint64_t da = descA0 + (uint64_t)((ks * 2048 + mt * 16384) >> 4), db = descB0 + (uint64_t)(((ks & 3) * 256 + (ks >> 2) * SLOTB) >> 4);
                asm volatile("{.reg .pred p; setp.ne.b32 p, %34, 0;\n"
                    "wgmma.mma_async.sync.aligned.m64n64k16.f32.bf16.bf16 "
                    "{%0,%1,%2,%3,%4,%5,%6,%7,%8,%9,%10,%11,%12,%13,%14,%15,%16,%17,%18,%19,%20,%21,%22,%23,%24,%25,%26,%27,%28,%29,%30,%31}, %32, %33, p, 1, 1, 1, 1;}"
                    : "+f"(d[mt][0]), "+f"(d[mt][1]), "+f"(d[mt][2]), "+f"(d[mt][3]), "+f"(d[mt][4]), "+f"(d[mt][5]), "+f"(d[mt][6]), "+f"(d[mt][7]),
                      "+f"(d[mt][8]), "+f"(d[mt][9]), "+f"(d[mt][10]), "+f"(d[mt][11]), "+f"(d[mt][12]), "+f"(d[mt][13]), "+f"(d[mt][14]), "+f"(d[mt][15]),
                      "+f"(d[mt][16]), "+f"(d[mt][17]), "+f"(d[mt][18]), "+f"(d[mt][19]), "+f"(d[mt][20]), "+f"(d[mt][21]), "+f"(d[mt][22]), "+f"(d[mt][23]),
                      "+f"(d[mt][24]), "+f"(d[mt][25]), "+f"(d[mt][26]), "+f"(d[mt][27]), "+f"(d[mt][28]), "+f"(d[mt][29]), "+f"(d[mt][30]), "+f"(d[mt][31])
                    : "l"(da), "l"(db), "r"(ks));
            }
            asm volatile("wgmma.commit_group.sync.aligned;" ::: "memory");
            if (mt == RELAT - 1) asm volatile("{.reg .pred p; setp.eq.u32 p, %1, 0; @p red.shared.add.u32 [%0+52], 1;}" :: "r"(flg), "r"(tid & 127) : "memory");
        }
#pragma unroll
        for (int mt = 0; mt < 2; mt++) {
            if (mt == 0) asm volatile("wgmma.wait_group.sync.aligned 1;" ::: "memory");
            else asm volatile("wgmma.wait_group.sync.aligned 0;" ::: "memory");
            if (RELAT == 0 && mt == 0 && (tid & 127) == 0) atomicAdd((uint32_t*)flag + 13, 1);
            TSTAMP(23 + mt);
#pragma unroll
            for (int i = 0; i < 32; i++) asm volatile("" : "+f"(d[mt][i]) :: "memory");
#pragma unroll
            for (int j = 0; j < 8; j++) {
                const uint32_t v0 = pack2(d[mt][4 * j], d[mt][4 * j + 1]), v1 = pack2(d[mt][4 * j + 2], d[mt][4 * j + 3]);
                const uint32_t rv = __shfl_xor_sync(0xffffffff, odd ? v0 : v1, 1);
                if (nd[j] < nn) ob[nd[j] * 128 + mt * 64] = odd ? make_uint2(rv, v1) : make_uint2(v0, rv);
            }
        }
    }
    TSTAMP(8);
}

}

extern "C" void kernel_launch(void* const* d_in, const int* in_sizes, int n_in, void* d_out, int out_size) {
    (void)in_sizes; (void)n_in; (void)out_size;
    cudaFuncSetAttribute(tfn_kernel, cudaFuncAttributeMaxDynamicSharedMemorySize, SM_TOTAL);
    Scratch* gs = nullptr;
    cudaGetSymbolAddress((void**)&gs, g_scratch);
    cudaLaunchConfig_t cfg = {};
    cfg.gridDim = dim3(NB); cfg.blockDim = dim3(NT); cfg.dynamicSmemBytes = SM_TOTAL; cfg.stream = cudaStreamPerThread;
    cudaLaunchAttribute at[1];
    at[0].id = cudaLaunchAttributeCooperative; at[0].val.cooperative = 1;
    cfg.attrs = at; cfg.numAttrs = 1;
    cudaLaunchKernelEx(&cfg, tfn_kernel, (const unsigned char*)d_in[0], (const int4*)d_in[1], (const int4*)d_in[2],
                       (const uint4*)d_in[3], (const uint4*)d_in[4], (const uint16_t*)d_in[5], (const uint16_t*)d_in[6],
                       (const uint4*)d_in[7], (uint32_t*)d_out, gs);
}
```

```cpp
#include <cuda_runtime.h>
#include <cuda_bf16.h>
#include <stdint.h>

#define VOL
#define ORD 1
#define ABL 0
namespace {

constexpr int NN = 10000;
constexpr int NE = 320000;
constexpr int NB = 132;
constexpr int NW = 20;
constexpr int NT = NW * 32;
constexpr int CW = NW - 1;
constexpr int PW = 10;
constexpr int NPB = 76;
constexpr int CELL = 48;
constexpr int CAP = 19;
constexpr int DS = 4;
constexpr int STEPB = 160;
constexpr int NE4 = NE / 4;
constexpr int NPIECE = NB * 8;
constexpr int KB = 320, KN = 32 * KB;
constexpr uint32_t F_WRAP = 1;

constexpr int SLOTB = NW * 2048;
constexpr int SM_RING = 0;
constexpr int SM_META = SM_RING + DS * SLOTB;
constexpr int SM_AZ = SM_META + NW * CAP * STEPB;
constexpr int SM_MISC = SM_AZ + 2048;
constexpr int SM_TOTAL = SM_MISC + 2048;
constexpr int SM_STAGE = SM_RING;
constexpr int SM_HIST = SM_RING + 25600;
constexpr int SM_POS = SM_RING;
constexpr int SM_SMALL = SM_HIST + 13056;
constexpr int SM_LIST = SM_RING + 2 * SLOTB;
constexpr int SM_RECS = SM_RING + 3 * SLOTB;
constexpr int SM_RAWY = SM_META;
constexpr int SM_RAWE = SM_RAWY + 608 * 32;
constexpr int SM_KEYS = SM_RAWE + 608 * 32;
static_assert(SM_TOTAL <= 232448 && SM_KEYS + NPIECE * 16 <= SM_AZ, "smem");
static_assert(SM_RECS + NB * CELL * 16 + 16 <= SM_AZ && SM_KEYS + NPIECE * 16 <= SM_RECS + NB * CELL * 16 && SM_SMALL + 1152 <= SLOTB && DS == 4, "smem");

struct Scratch {
    uint4 keys[NB * NPIECE];
    uint4 recs[NB * NB * CELL];
    uint4 stash[NB * NW * 256];
    unsigned bar[4];
    unsigned long long t0, pad;
};
__device__ Scratch g_scratch;
#define TSTAMP(i)
#define TSTAMPC(i)
#define WSTAMP(i)

__device__ __forceinline__ void mma16816(float* d, uint32_t a0, uint32_t a1, uint32_t a2, uint32_t a3, uint32_t b0, uint32_t b1) {
    asm VOL("mma.sync.aligned.m16n8k16.row.col.f32.bf16.bf16.f32 {%0,%1,%2,%3}, {%4,%5,%6,%7}, {%8,%9}, {%0,%1,%2,%3};"
        : "+f"(d[0]), "+f"(d[1]), "+f"(d[2]), "+f"(d[3]) : "r"(a0), "r"(a1), "r"(a2), "r"(a3), "r"(b0), "r"(b1));
}
__device__ __forceinline__ void mma1688z(float* d, uint32_t a0, uint32_t a1, uint32_t b0) {
    asm VOL("mma.sync.aligned.m16n8k8.row.col.f32.bf16.bf16.f32 {%0,%1,%2,%3}, {%4,%5}, {%6}, {%7,%7,%7,%7};"
        : "=f"(d[0]), "=f"(d[1]), "=f"(d[2]), "=f"(d[3]) : "r"(a0), "r"(a1), "r"(b0), "f"(0.f));
}
__device__ __forceinline__ uint32_t pack2(float lo, float hi) {
    uint32_t r; asm VOL("cvt.rn.bf16x2.f32 %0, %1, %2;" : "=r"(r) : "f"(hi), "f"(lo)); return r;
}
__device__ __forceinline__ float silu_h(float h) {
    float t; asm VOL("tanh.approx.f32 %0, %1;" : "=f"(t) : "f"(h)); return fmaf(h, t, h);
}
__device__ __forceinline__ uint32_t mul_lo(uint32_t v, uint32_t r) {
    __nv_bfloat162 a = *(__nv_bfloat162*)&v, b = *(__nv_bfloat162*)&r; __nv_bfloat162 c = __hmul2(a, __low2bfloat162(b)); return *(uint32_t*)&c;
}
__device__ __forceinline__ uint32_t mul_hi(uint32_t v, uint32_t r) {
    __nv_bfloat162 a = *(__nv_bfloat162*)&v, b = *(__nv_bfloat162*)&r; __nv_bfloat162 c = __hmul2(a, __high2bfloat162(b)); return *(uint32_t*)&c;
}
__device__ __forceinline__ uint2 lds64(uint32_t a) {
    uint2 r; asm volatile("ld.shared.v2.u32 {%0,%1}, [%2];" : "=r"(r.x), "=r"(r.y) : "r"(a)); return r;
}
__device__ __forceinline__ uint4 lds128(uint32_t a) {
    uint4 r; asm volatile("ld.shared.v4.u32 {%0,%1,%2,%3}, [%4];" : "=r"(r.x), "=r"(r.y), "=r"(r.z), "=r"(r.w) : "r"(a) : "memory"); return r;
}
__device__ __forceinline__ void bar_sync(int id, int n) { asm volatile("bar.sync %0, %1;" :: "r"(id), "r"(n) : "memory"); }
__device__ __forceinline__ void bar_arrive(int id, int n) { asm volatile("bar.arrive %0, %1;" :: "r"(id), "r"(n) : "memory"); }
__device__ __forceinline__ void mbar_wait(uint32_t bar, uint32_t ph) {
    uint32_t done; int spins = 0;
    do {
        asm volatile("{.reg .pred p; mbarrier.try_wait.parity.shared.b64 p, [%1], %2; selp.u32 %0,1,0,p;}" : "=r"(done) : "r"(bar), "r"(ph) : "memory");
    } while (!done && ++spins < (1 << 22));
}
__device__ __forceinline__ unsigned gbar_read(const unsigned* ctr) {
    unsigned v; asm volatile("ld.relaxed.gpu.global.u32 %0, [%1];" : "=r"(v) : "l"(ctr) : "memory");
    return v;
}
__device__ __forceinline__ void gbar_arrive(unsigned* ctr) {
    asm volatile("red.add.release.gpu.global.u32 [%0], 1;" :: "l"(ctr) : "memory");
}
__device__ __forceinline__ bool gbar_wait(const unsigned* ctr, unsigned target) {
    unsigned v; int spins = 0;
    do { asm volatile("ld.acquire.gpu.global.u32 %0, [%1];" : "=r"(v) : "l"(ctr) : "memory"); } while ((int)(v - target) < 0 && ++spins < (1 << 22));
    return (int)(v - target) >= 0;
}
__device__ __forceinline__ int chunk_start4(int c) { return (c * NE4) / NB; }
__device__ __forceinline__ float bf2f(uint32_t h) { return __uint_as_float(h << 16); }

__device__ __noinline__ void slow_path(unsigned char* smem, int n0, int nn, const uint16_t* x, const int* src, const int* dst,
                                       const uint16_t* Y, const uint16_t* ef, const uint16_t* w_rad, const uint16_t* cg,
                                       const uint16_t* w_mix, __nv_bfloat16* out) {
    float* agg = (float*)smem;
    const int tid = threadIdx.x, lane = tid & 31, w = tid >> 5;
    bar_sync(1, NT);
    for (int i = tid; i < NPB * 512; i += NT) agg[i] = 0.f;
    bar_sync(1, NT);
    for (int e0 = w * 32; e0 < NE; e0 += NT) {
        int dl = dst[e0 + lane] - n0;
        unsigned m = __ballot_sync(0xffffffff, dl >= 0 && dl < nn);
        while (m) {
            int l = __ffs(m) - 1; m &= m - 1;
            int e = e0 + l, d = __shfl_sync(0xffffffff, dl, l), s = src[e];
            float T[16];
            for (int i = 0; i < 4; i++) for (int o = 0; o < 4; o++) {
                float a = 0.f;
                for (int f = 0; f < 4; f++) a += bf2f(Y[e * 4 + f]) * bf2f(cg[i * 16 + f * 4 + o]);
                T[i * 4 + o] = a;
            }
            for (int k = 0; k < 4; k++) {
                int c = lane + 32 * k;
                float z = 0.f;
                for (int j = 0; j < 4; j++) z += bf2f(ef[e * 4 + j]) * bf2f(w_rad[j * 128 + c]);
                float R = z / (1.f + __expf(-z));
                for (int o = 0; o < 4; o++) {
                    float a = 0.f;
                    for (int i = 0; i < 4; i++) a += bf2f(x[(size_t)s * 512 + c * 4 + i]) * T[i * 4 + o];
                    atomicAdd(&agg[d * 512 + c * 4 + o], R * a);
                }
            }
        }
    }
    bar_sync(1, NT);
    for (int i = tid; i < nn * 512; i += NT) {
        int n = i >> 9, d = (i >> 2) & 127, o = i & 3;
        float a = 0.f;
        for (int c = 0; c < 128; c++) a += agg[n * 512 + c * 4 + o] * bf2f(w_mix[c * 128 + d]);
        out[(size_t)(n0 + n) * 512 + (i & 511)] = __float2bfloat16(a);
    }
}

#define PACE 24000
#define YDELAY 0
#define NB0 4
#define TP 0
#define EPI 2
#define LEAD 0
#define RELAT 2
#define KDELAY 0
#define POFF 1700
#define PTOL 600
__global__ void __launch_bounds__(NT, 1)
tfn_kernel(const unsigned char* __restrict__ x, const int4* __restrict__ src4, const int4* __restrict__ dst4,
           const uint4* __restrict__ Y, const uint4* __restrict__ ef, const uint16_t* __restrict__ w_rad,
           const uint16_t* __restrict__ cg, const uint4* __restrict__ w_mix, uint32_t* __restrict__ out, Scratch* __restrict__ gs) {
    extern __shared__ __align__(1024) unsigned char smem[];
    const uint32_t sb = (uint32_t)__cvta_generic_to_shared(smem);
    const int b = blockIdx.x, tid = threadIdx.x, lane = tid & 31, g = lane >> 2, t = lane & 3;
    const int w = __shfl_sync(0xffffffff, tid >> 5, 0);
    uint32_t* stage = (uint32_t*)(smem + SM_STAGE);
    uint32_t* hist = (uint32_t*)(smem + SM_HIST);
    uint32_t* cnt = (uint32_t*)(smem + SM_MISC);
    uint32_t* deg = cnt + 136;
    uint32_t* order = deg + 104;
    uint32_t* cnt2 = order + 80;
    volatile uint32_t* flag = cnt2 + 136;
    const uint32_t mbarK = sb + SM_MISC + 1920, mbarR = mbarK + 8, mbarW = mbarK + 16;
    const int n0 = b * NPB, nn = min(NPB, NN - n0);
    TSTAMP(0);

    const int c0 = chunk_start4(b), c1 = chunk_start4(b + 1);
    const bool has4 = c0 + tid < c1;
    int4 d4 = make_int4(0, 0, 0, 0), s4 = d4;
    if (has4) { d4 = __ldg(dst4 + c0 + tid); s4 = __ldg(src4 + c0 + tid); }
    unsigned tgt = 0;
    if (tid == NT - 1) {
        tgt = gbar_read(&gs->bar[0]);
        asm volatile("mbarrier.init.shared.b64 [%0], 1;" :: "r"(mbarK));
        asm volatile("mbarrier.init.shared.b64 [%0], 1;" :: "r"(mbarR));
        asm volatile("mbarrier.init.shared.b64 [%0], 512;" :: "r"(mbarW));
        asm volatile("fence.mbarrier_init.release.cluster;" ::: "memory");
        if (YDELAY) __nanosleep(YDELAY);
        asm volatile("mbarrier.arrive.expect_tx.shared.b64 _, [%0], %1;" :: "r"(mbarR), "r"((c1 - c0) * 64) : "memory");
        asm volatile("cp.async.bulk.shared::cluster.global.mbarrier::complete_tx::bytes [%0], [%1], %2, [%3];"
                     :: "r"(sb + SM_RAWY), "l"(Y + 2 * c0), "r"((c1 - c0) * 32), "r"(mbarR) : "memory");
        asm volatile("cp.async.bulk.shared::cluster.global.mbarrier::complete_tx::bytes [%0], [%1], %2, [%3];"
                     :: "r"(sb + SM_RAWE), "l"(ef + 2 * c0), "r"((c1 - c0) * 32), "r"(mbarR) : "memory");
        flag[0] = 0; flag[12] = 0; flag[13] = 0;
    }
    if (w == CW) {
        asm volatile("cp.async.cg.shared.global [%0], [%1], 16;" :: "r"(sb + SM_SMALL + lane * 16), "l"(w_rad + lane * 8) : "memory");
        asm volatile("cp.async.cg.shared.global [%0], [%1], 16;" :: "r"(sb + SM_SMALL + 512 + lane * 16), "l"(w_rad + 256 + lane * 8) : "memory");
        if (lane < 8) asm volatile("cp.async.cg.shared.global [%0], [%1], 16;" :: "r"(sb + SM_SMALL + 1024 + lane * 16), "l"(cg + lane * 8) : "memory");
    }
    ((uint4*)hist)[tid] = make_uint4(0, 0, 0, 0);
    {
        const uint32_t dk = ((80 + b % 22) * KN + (b & 31) * KB) << 12;
#pragma unroll
        for (int j = 0; j < 3; j++) if (tid + j * NT < NB * CELL / 4) ((uint4*)stage)[tid + j * NT] = make_uint4(dk, dk, dk, dk);
    }
    if (tid < 136) cnt[tid] = 0;
    if (tid == 0) { *(uint4*)(smem + SM_MISC + 1824 + 32) = make_uint4(0, 0, 0, 0); cnt2[NB] = 0; *(uint4*)(smem + SM_RECS + NB * CELL * 16) = make_uint4(0, 0, 0, 0); }
    if (tid < 80) { deg[tid] = 127 - tid; order[tid] = tid; }
    __syncthreads();
    TSTAMP(9);

    if (has4) {
        const uint32_t dd[4] = {(uint32_t)d4.x, (uint32_t)d4.y, (uint32_t)d4.z, (uint32_t)d4.w}, ss[4] = {(uint32_t)s4.x, (uint32_t)s4.y, (uint32_t)s4.z, (uint32_t)s4.w};
        uint32_t bin[4], slot[4];
#pragma unroll
        for (int k = 0; k < 4; k++) { bin[k] = dd[k] / NPB; slot[k] = atomicAdd(&cnt[bin[k]], 1); }
#pragma unroll
        for (int k = 0; k < 4; k++)
            stage[bin[k] * CELL + min(slot[k], CELL - 1)] = (((dd[k] - bin[k] * NPB) * KN + ss[k]) << 12) + tid * 4 + k;
    }
    if (w == CW) {
        if (tid == NT - 1) { tgt = tgt / NB + 1; flag[14] = (tgt & 1) * 8; tgt *= NB; }
        asm volatile("cp.async.wait_all;" ::: "memory");
    }
    bar_sync(1, NT);
    TSTAMP(1);
    const uint32_t tag = flag[14];
#pragma unroll
    for (int j = 0; j < 2; j++) {
        const int i = tid + j * NT;
        if (i < NPIECE) {
            const uint2 sa = *(const uint2*)(stage + i * 6), sc = *(const uint2*)(stage + i * 6 + 2), se = *(const uint2*)(stage + i * 6 + 4);
            const uint32_t cn = min(cnt[i >> 3], 63u);
            asm volatile("{.reg .b64 lo, hi; mov.b64 lo, {%1,%2}; mov.b64 hi, {%3,%4}; st.relaxed.gpu.global.v2.b64 [%0], {lo, hi};}"
                         :: "l"(gs->keys + ((i >> 3) * NB + b) * 8 + ((i ^ b) & 7)),
                            "r"(__funnelshift_r(sa.x, se.x >> 12, 12)), "r"(__funnelshift_r(sa.y, __funnelshift_r(se.x, (cn & 7) | tag, 24), 12)),
                            "r"(__funnelshift_r(sc.x, se.y >> 12, 12)), "r"(__funnelshift_r(sc.y, __funnelshift_r(se.y, (cn >> 3) | tag, 24), 12)) : "memory");
        }
    }
    uint2 yy[7], ee[7];
    uint32_t cno[7];
    uint4* rp = gs->recs + (w * NB + b) * CELL + lane;
    auto recs_out = [&](int j0, int j1) {
#pragma unroll
        for (int j = 0; j < 7; j++) if (j >= j0 && j < j1)
            asm volatile("{.reg .pred p; setp.lt.u32 p, %5, %6; @p st.global.v4.u32 [%0], {%1,%2,%3,%4};}"
                         :: "l"(rp + j * (CW * NB * CELL)), "r"(yy[j].x), "r"(ee[j].x), "r"(yy[j].y), "r"(ee[j].y), "r"(lane & ~1), "r"(cno[j]) : "memory");
    };
    if (w != CW) bar_arrive(7, NT);
    uint32_t at[4];
    {
        const int o = g & 3, f = 2 * (t & 1);
#pragma unroll
        for (int i = 0; i < 4; i++) {
            const uint16_t* cp = (const uint16_t*)(smem + SM_SMALL + 1024) + i * 16 + f * 4 + o;
            at[i] = (t >> 1) == (g >> 2) ? cp[0] | ((uint32_t)cp[4] << 16) : 0;
        }
    }

    uint32_t key[2][6], ha[2][6], rk[2][6], kidx[2], ka[2];
    int nk[2];
#pragma unroll
    for (int j = 0; j < 2; j++) {
        const int i0 = j ? 2 * 608 - 1 - tid : tid, i = min(i0, NPIECE - 1), r = i / NB, c = i - r * NB;
        ka[j] = sb + SM_KEYS + (c * 8 + ((r ^ c) & 7)) * 16;
        kidx[j] = (c * CELL + r * 6) << 17;
        nk[j] = i0 < NPIECE && w < CW ? -6 * r : -1000;
    }
    asm volatile("" : "+r"(at[0]), "+r"(at[1]), "+r"(at[2]), "+r"(at[3]), "+r"(ka[0]), "+r"(ka[1]), "+r"(kidx[0]), "+r"(kidx[1]), "+r"(nk[0]), "+r"(nk[1]));
    if (w == CW) {
        bar_sync(7, NT);
        if (tid == NT - 1) {
            TSTAMPC(10);
            asm volatile("red.add.relaxed.gpu.global.u32 [%0], 1;" :: "l"(&gs->bar[0]) : "memory");
            TSTAMPC(11);
            asm volatile("mbarrier.arrive.expect_tx.shared.b64 _, [%0], %1;" :: "r"(mbarK), "r"(NPIECE * 16) : "memory");
            gbar_wait(&gs->bar[0], tgt);
            if (KDELAY) __nanosleep(KDELAY);
            TSTAMPC(13);
            asm volatile("fence.proxy.async.global;" ::: "memory");
            asm volatile("cp.async.bulk.shared::cluster.global.mbarrier::complete_tx::bytes [%0], [%1], %2, [%3];"
                         :: "r"(sb + SM_KEYS), "l"(gs->keys + b * NPIECE), "r"(NPIECE * 16), "r"(mbarK) : "memory");
        }
        __syncwarp();
        bar_arrive(8, NT);
    } else {
        if (w < 8) {
            const uint32_t* wp = (const uint32_t*)(smem + SM_SMALL) + (t & 1) * 128 + 8 * w + g;
            const uint32_t wr0 = t < 2 ? wp[0] : 0, wr1 = t < 2 ? wp[64] : 0;
            *(uint2*)(smem + SM_AZ + (w >> 1) * 512 + lane * 16 + (w & 1) * 8) =
                make_uint2(pack2(0.5f * bf2f(wr0 & 0xFFFF), 0.5f * bf2f(wr1 & 0xFFFF)), pack2(0.5f * bf2f(wr0 >> 16), 0.5f * bf2f(wr1 >> 16)));
        }
        uint32_t el[7], big = 0;
#pragma unroll
        for (int j = 0; j < 7; j++) {
            const int cell = w + CW * j;
            cno[j] = cnt[cell];
            el[j] = (stage[cell * CELL + lane] & 0xFFF) * 8;
            big |= cno[j] > 32;
        }
        mbar_wait(mbarR, 0);
        TSTAMP(18);
#pragma unroll
        for (int j = 0; j < 7; j++) { yy[j] = lds64(sb + SM_RAWY + el[j]); ee[j] = lds64(sb + SM_RAWE + el[j]); }
        if (big) {
#pragma unroll 1
            for (int j = 0; j < 7; j++) {
                const int cell = w + CW * j;
                if (lane + 32 < min(cnt[cell], CELL)) {
                    const uint32_t e2 = (stage[cell * CELL + 32 + lane] & 0xFFF) * 8;
                    const uint2 y2 = *(const uint2*)(smem + SM_RAWY + e2), e3 = *(const uint2*)(smem + SM_RAWE + e2);
                    rp[j * (CW * NB * CELL) + 32] = make_uint4(y2.x, e3.x, y2.y, e3.y);
                }
            }
        }
        bar_sync(8, NT);
        recs_out(0, NB0);
    }
    __syncwarp();
    TSTAMP(2);
    if (w < CW) {
        mbar_wait(mbarK, 0);
        TSTAMP(3);
        uint4 v[2] = {lds128(ka[0]), lds128(ka[1])};
#pragma unroll
        for (int j = 0; j < 2; j++) {
            int spins = 0;
            while ((int)((v[j].y ^ (tag << 28)) | (v[j].w ^ (tag << 28))) < 0) {
                asm volatile("{.reg .b64 lo, hi; ld.relaxed.gpu.global.v2.b64 {lo, hi}, [%4]; mov.b64 {%0,%1}, lo; mov.b64 {%2,%3}, hi;}"
                             : "=r"(v[j].x), "=r"(v[j].y), "=r"(v[j].z), "=r"(v[j].w) : "l"((const unsigned char*)(gs->keys + b * NPIECE) + (ka[j] - sb - SM_KEYS)) : "memory");
                if (++spins > (1 << 20)) { *flag = 1; break; }
            }
            const uint32_t hc = ((v[j].y >> 28) & 7) | ((v[j].w >> 25) & 0x38);
            if (j == 0 && tid < NB) cnt2[tid] = hc;
            nk[j] += hc;
            if (nk[j] > 0) {
                key[j][0] = v[j].x & 0xFFFFF; key[j][1] = v[j].y & 0xFFFFF; key[j][2] = v[j].z & 0xFFFFF; key[j][3] = v[j].w & 0xFFFFF;
                key[j][4] = (v[j].x >> 20) | ((v[j].y >> 8) & 0xFF000); key[j][5] = (v[j].z >> 20) | ((v[j].w >> 8) & 0xFF000);
#pragma unroll
                for (int u = 0; u < 6; u++) {
                    ha[j][u] = __umulhi(key[j][u], 0xFFFFFFFFu / KB + 1);
                    rk[j][u] = atomicAdd(&hist[ha[j][u]], 1);
                    atomicAdd(&deg[ha[j][u] >> 5], 128);
                }
            }
        }
        recs_out(NB0, 7);
        bar_sync(10, NT);
        TSTAMP(20);
        const int n = tid >> 3, sub = tid & 7;
        const uint32_t me = deg[n];
        int r = 0;
#pragma unroll
        for (int k = 0; k < 5; k++) { const uint2 dd = *(const uint2*)(deg + sub * 10 + 2 * k); r += (dd.x > me) + (dd.y > me); }
        r += __shfl_xor_sync(0xffffffff, r, 1); r += __shfl_xor_sync(0xffffffff, r, 2); r += __shfl_xor_sync(0xffffffff, r, 4);
        if (sub == 0) order[r] = n;
    } else {
        bar_sync(10, NT);
        if (tid == NT - 1) { TSTAMPC(14); gbar_arrive(&gs->bar[1]); TSTAMPC(15); if (!gbar_wait(&gs->bar[1], tgt)) *flag = 1; TSTAMPC(17); }
    }
    __syncwarp();
    const uint32_t cn = cnt2[min(w + NW * lane, NB)];
    if (cn > CELL) *flag = 1;
    auto recs_in = [&]() {
        const uint4* gp = gs->recs + (b * NB + w) * CELL + lane;
        const uint32_t sp = sb + SM_RECS + (w * CELL + lane) * 16;
#pragma unroll
        for (int j = 0; j < 7; j++)
            asm volatile("{.reg .pred p; setp.lt.u32 p, %2, %3; @p cp.async.cg.shared.global [%0], [%1], 16;}"
                         :: "r"(sp + j * (NW * CELL * 16)), "l"(gp + j * (NW * CELL)), "r"(lane), "r"(__shfl_sync(0xffffffff, cn, j)) : "memory");
        if (__any_sync(0xffffffff, cn > 32)) {
#pragma unroll 1
            for (int j = 0; j < 7; j++)
                if (lane + 32 < min(__shfl_sync(0xffffffff, cn, j), CELL))
                    asm volatile("cp.async.cg.shared.global [%0], [%1], 16;" :: "r"(sp + j * (NW * CELL * 16) + 512), "l"(gp + j * (NW * CELL) + 32) : "memory");
        }
        asm volatile("cp.async.commit_group;" ::: "memory");
    };
    if (w < CW) {
        bar_sync(9, NT - 32);
        TSTAMP(22);
#pragma unroll 1
        for (int v = w; v < NW; v += (w == 1 ? CW - 1 : NW)) {
            const uint2 na = *(const uint2*)(order + 2 * v), nb = *(const uint2*)(order + 78 - 2 * v);
            const uint32_t ia0 = na.x * 32 + lane, ib0 = nb.y * 32 + lane, ia1 = na.y * 32 + lane, ib1 = nb.x * 32 + lane;
            const uint32_t ca = hist[ia0] + (hist[ia1] << 16), cab = ca + hist[ib0] + (hist[ib1] << 16);
            uint32_t inc = cab;
#pragma unroll
            for (int o = 1; o < 32; o <<= 1)
                asm volatile("{.reg .pred p; .reg .u32 u; shfl.sync.up.b32 u|p, %0, %1, 0, 0xffffffff; @p add.u32 %0, %0, u;}" : "+r"(inc) : "r"(o));
            const uint32_t ea = inc - cab, eb = ea + ca, base = sb + SM_LIST + v * 2048;
            uint2* pos = (uint2*)(smem + SM_POS);
            pos[ia0] = make_uint2(base + (ea & 0xFFFF) * 8, na.x * (0u - 4 * KN));
            pos[ib0] = make_uint2(base + (eb & 0xFFFF) * 8, nb.y * (0u - 4 * KN) + 0x10000);
            pos[ia1] = make_uint2(base + 4 + (ea >> 16) * 8, na.y * (0u - 4 * KN));
            pos[ib1] = make_uint2(base + 4 + (eb >> 16) * 8, nb.x * (0u - 4 * KN) + 0x10000);
            if (lane == 31) { cnt[v] = inc; if (max(inc & 0xFFFF, inc >> 16) > 4 * CAP) *flag = 1; }
        }
        bar_sync(9, NT - 32);
        TSTAMP(21);
#pragma unroll
        for (int j = 0; j < 2; j++) {
            if (nk[j] > 0) {
                uint2 h[6];
#pragma unroll
                for (int u = 0; u < 6; u++) h[u] = lds64(sb + SM_POS + ha[j][u] * 8);
#pragma unroll
                for (int u = 0; u < 6; u++)
                    asm volatile("{.reg .pred p; setp.gt.s32 p, %2, %3; @p st.shared.u32 [%0], %1;}"
                                 :: "r"(h[u].x + rk[j][u] * 8), "r"(key[j][u] * 4 + h[u].y + (kidx[j] + (u << 17))), "r"(nk[j]), "r"(u) : "memory");
            }
        }
    }
    bar_sync(1, NT);
    TSTAMP(4);
    if (*flag) {
        slow_path(smem, n0, nn, (const uint16_t*)x, (const int*)src4, (const int*)dst4, (const uint16_t*)Y, (const uint16_t*)ef, w_rad, cg,
                  (const uint16_t*)w_mix, (__nv_bfloat16*)out);
        return;
    }
    recs_in();
    const uint32_t len2 = cnt[w];
    const int S = __shfl_sync(0xffffffff, max((int)(max(len2 & 0xFFFF, len2 >> 16) + 3) >> 2, DS + 1), 0);
    const int mylen = (lane & 1) ? len2 >> 16 : len2 & 0xFFFF;
    constexpr int NRAW = (CAP + 3) / 4;
    uint32_t bits0 = 0, raw[NRAW];
    unsigned char* meta = smem + SM_META + w * (CAP * STEPB);
#pragma unroll
    for (int k = 0; k < NRAW; k++) raw[k] = mylen ? ((uint32_t*)(smem + SM_LIST + w * 2048))[min(k * 16 + (lane >> 1), mylen - 1) * 2 + (lane & 1)] : 4 * n0;
    const uint32_t sv0 = raw[0] & 0xFFFF;
    const int q = lane >> 3, c = lane & 7;
    const uint32_t ring0 = sb + SM_RING + w * 2048;
    uint32_t wdst = ring0 + q * 128 + ((c + 2 * q) & 7) * 16;
    uint32_t rsrc = ring0 + t * 128 + ((g + 2 * t) & 7) * 16;
    uint32_t recl = sb + SM_META + w * (CAP * STEPB) + g * 16 + (t & 1) * 8, srcl = sb + SM_META + w * (CAP * STEPB) + 128 + q * 8;
    uint32_t flg = sb + SM_MISC + (136 + 104 + 80 + 136) * 4;
    asm volatile("" : "+r"(wdst), "+r"(rsrc), "+r"(recl), "+r"(srcl), "+r"(flg));
    const unsigned char* pbase = x + c * 16;
    auto cpa2 = [&](uint32_t dstp, uint32_t sv) {
        asm volatile("cp.async.cg.shared.global [%0], [%1], 16; cp.async.cg.shared.global [%0+1024], [%1+128], 16;"
                     :: "r"(dstp), "l"(pbase + (size_t)sv * 256) : "memory");
    };
    auto fill = [&](int i) {
        cpa2(wdst + i * SLOTB, __shfl_sync(0xffffffff, sv0, 8 * i + 2 * q)); cpa2(wdst + i * SLOTB + 512, __shfl_sync(0xffffffff, sv0, 8 * i + 2 * q + 1));
        asm volatile("cp.async.commit_group;" ::: "memory");
    };
    fill(0);
    TSTAMP(5);
    if (w == 0) {
        unsigned long long tbase;
        asm volatile("mov.u64 %0, %%globaltimer;" : "=l"(tbase));
        tbase += POFF;
        flag[1] = (uint32_t)tbase; flag[2] = (uint32_t)tbase; flag[4] = (uint32_t)tbase; flag[5] = (uint32_t)(tbase >> 32);
        if (lane == 0) {
            asm volatile("red.max.relaxed.gpu.global.u64 [%0], %1;" :: "l"(&gs->t0), "l"(tbase) : "memory");
            if (b < 128) asm volatile("cp.async.bulk.prefetch.L2.global [%0], 256;" :: "l"(w_mix + b * 16));
        }
    }
    uint32_t ra[NRAW];
#pragma unroll
    for (int k = 0; k < NRAW; k++) {
        const uint32_t m = (__ballot_sync(0xffffffff, raw[k] & 0x10000) >> g) & 0x01010101u;
        bits0 |= ((m * 0x10204080u) >> 28) << (4 * k);
        ra[k] = sb + SM_RECS + (k * 16 + (lane >> 1) < mylen ? raw[k] >> 17 : NB * CELL) * 16;
    }
    if (t < 2) bits0 = ~bits0;
    fill(1);
    asm volatile("cp.async.wait_group 2;" ::: "memory");
    bar_sync(1, NT);
    TSTAMP(19);
    {
        uint4 rv[NRAW];
#pragma unroll
        for (int k = 0; k < NRAW - 1; k++) rv[k] = lds128(ra[k]);
        if ((NRAW - 1) * 4 < S) rv[NRAW - 1] = lds128(ra[NRAW - 1]);
        if (tid == 0) asm volatile("cp.async.cg.shared.global [%0], [%1], 16;" :: "r"(sb + SM_MISC + 1824 + 32), "l"(&gs->t0) : "memory");
        fill(2);
        bar_sync(1, NT);
        TSTAMP(12);
        unsigned char* mr = meta + (q - 1) * STEPB + c * 16;
        unsigned char* ms = meta + (q - DS - 1) * STEPB + 128 + c * 4;
#pragma unroll
        for (int k = 0; k < NRAW; k++) {
            if (k == 0) {
                *(uint4*)(mr + (q == 0 ? S * STEPB : 0)) = rv[k];
                *(uint32_t*)(ms + S * STEPB) = sv0 + F_WRAP;
            } else if (k * 4 + q < S) {
                *(uint4*)(mr + k * 4 * STEPB) = rv[k];
                *(uint32_t*)(ms + k * 4 * STEPB + (k == 1 && q == 0 ? S * STEPB : 0)) = raw[k] & 0xFFFF;
            }
        }
    }
    __syncwarp();
    const uint32_t tphase = PACE / 4;
    uint32_t dreg;
    {
        const int st = lane == 0 ? S - 1 : min(lane, S) - 1;
        const uint4 u0 = *(const uint4*)(meta + st * STEPB + 128), u1 = *(const uint4*)(meta + st * STEPB + 144);
        int pos = (u0.x + u0.y + u0.z + u0.w + u1.x + u1.y + u1.z + u1.w) >> 5;
        pos += ((u0.x & F_WRAP) ? NN : 0) + (lane == S ? NN : 0) - NN * (2 * DS + 1) / 32;
        dreg = pos * (int)tphase / NN;
    }
    fill(3);
    TSTAMP(6);

    uint32_t* stash = (uint32_t*)(gs->stash + (b * NW + w) * 256) + lane;
    float acc[4][4];
#pragma unroll
    for (int i = 0; i < 16; i++) acc[i / 4][i % 4] = 0.f;
    uint4 az = *(const uint4*)(smem + SM_AZ + lane * 16);
    uint32_t dcur = dreg, dl = 0, now = flag[1], tcur = 0;
    uint32_t mp = 0, smask = 1;
    const uint32_t mend = S * STEPB;
    uint2 r = lds64(mend - STEPB + recl), s0 = lds64(mend - STEPB + srcl);
    auto step = [&](const uint32_t off, const int mode) {
        auto tick = [&]() { if (mode == 0) { unsigned long long n64; asm volatile("mov.u64 %0, %%globaltimer;" : "=l"(n64)); now = (uint32_t)n64; } };
        if (TP == 0) tick();
        const uint2 rc = r, sc = s0;
        if (ORD & 1) { if (mode != 4) r = lds64(mp + recl); if (mode == 0) s0 = lds64(mp + srcl); }
        asm volatile("cp.async.wait_group %0;" :: "n"(DS - 1) : "memory");
        const uint4 xa = lds128(rsrc + off), xb = lds128(rsrc + off + 512), xc = lds128(rsrc + off + 1024), xd = lds128(rsrc + off + 1536);
        if (!(ORD & 1) && !(ORD & 4)) { if (mode != 4) r = lds64(mp + recl); if (mode == 0) s0 = lds64(mp + srcl); }
        if (mode == 0) {
            if (ORD & 2) {
                asm volatile("shfl.sync.idx.b32 %0, %1, 1, 31, 0xffffffff; shfl.sync.down.b32 %1, %1, 1, 31, 0xffffffff;\n"
                             "cp.async.cg.shared.global [%2], [%3], 16; cp.async.cg.shared.global [%2+512], [%4], 16;\n"
                             "cp.async.cg.shared.global [%2+1024], [%3+128], 16; cp.async.cg.shared.global [%2+1536], [%4+128], 16;"
                             : "=&r"(dl), "+r"(dcur) : "r"(wdst + off), "l"(pbase + (size_t)sc.x * 256), "l"(pbase + (size_t)sc.y * 256) : "memory");
            } else {
                dl = __shfl_sync(0xffffffff, dcur, 1); dcur = __shfl_down_sync(0xffffffff, dcur, 1);
                cpa2(wdst + off, sc.x); cpa2(wdst + off + 512, sc.y);
            }
        }
        if (mode == 1 && w < 16) {
#pragma unroll
            for (int j = 0; j < 4; j++) {
                const int kk = 4 * j + q, ch = 16 * (w & 7) + 2 * (kk & 7) + (kk >> 3);
                asm volatile("cp.async.cg.shared.global [%0], [%1], 16;" :: "r"(ring0 + kk * 128 + ((c ^ (kk & 7)) << 4)), "l"(w_mix + ch * 16 + (w >> 3) * 8 + c) : "memory");
            }
            asm volatile("cp.async.mbarrier.arrive.noinc.shared.b64 [%0];" :: "r"(mbarW) : "memory");
        }
        if (mode == 2 || mode == 3) {
#pragma unroll
            for (int j = 0; j < 4; j += mode - 1)
                asm volatile("cp.async.cg.shared.global [%0], [%1], 16;" :: "r"(ring0 + off + j * 512 + lane * 16), "l"(stash + (mode - 2) * 512 + j * 128 + lane * 3) : "memory");
        }
        asm volatile("cp.async.commit_group;" ::: "memory");
        if (ORD & 4) { if (mode != 4) r = lds64(mp + recl); if (mode == 0) s0 = lds64(mp + srcl); }
        float z[4], y[4], t1[4], t2[4];
        mma1688z(z, az.x, az.y, rc.y);
        mma1688z(y, az.z, az.w, rc.y);
        uint32_t bt;
        asm("{.reg .pred p; .reg .b32 m; and.b32 m, %2, %3; setp.ne.u32 p, m, 0; selp.b32 %0, %1, 0, p;}" : "=r"(bt) : "r"(rc.x), "r"(bits0), "r"(smask));
        mma1688z(t1, at[0], at[1], bt);
        mma1688z(t2, at[2], at[3], bt);
        if (TP == 1) tick();
        const uint32_t T0 = pack2(t1[0], t1[2]), T1 = pack2(t2[0], t2[2]), T2 = pack2(t1[1], t1[3]), T3 = pack2(t2[1], t2[3]);
        const uint32_t R0 = pack2(silu_h(z[0]), silu_h(z[2]));
        if (TP == 2) tick();
        const uint32_t R1 = pack2(silu_h(z[1]), silu_h(z[3]));
        if (TP == 3) tick();
        const uint32_t R2 = pack2(silu_h(y[0]), silu_h(y[2])), R3 = pack2(silu_h(y[1]), silu_h(y[3]));
        if (TP == 4) tick();
        mma16816(acc[0], mul_lo(xa.x, R0), mul_hi(xa.z, R0), mul_lo(xa.y, R0), mul_hi(xa.w, R0), T0, T1);
        mma16816(acc[1], mul_lo(xb.x, R1), mul_hi(xb.z, R1), mul_lo(xb.y, R1), mul_hi(xb.w, R1), T2, T3);
        mma16816(acc[2], mul_lo(xc.x, R2), mul_hi(xc.z, R2), mul_lo(xc.y, R2), mul_hi(xc.w, R2), T0, T1);
        mma16816(acc[3], mul_lo(xd.x, R3), mul_hi(xd.z, R3), mul_lo(xd.y, R3), mul_hi(xd.w, R3), T2, T3);
        mp += STEPB; smask <<= 1;
    };
    auto putacc = [&](uint32_t* p) {
        p[0] = pack2(acc[0][0], acc[0][1]); p[32] = pack2(acc[0][2], acc[0][3]); p[64] = pack2(acc[2][0], acc[2][1]); p[96] = pack2(acc[2][2], acc[2][3]);
        p[256] = pack2(acc[1][0], acc[1][1]); p[288] = pack2(acc[1][2], acc[1][3]); p[320] = pack2(acc[3][0], acc[3][1]); p[352] = pack2(acc[3][2], acc[3][3]);
    };
    int ph = 0;
    auto phase_end = [&]() {
        az = *(const uint4*)(smem + SM_AZ + (ph + 1) * 512 + lane * 16);
        putacc(stash + (ph >> 1) * 512 + (ph & 1) * 128);
#pragma unroll
        for (int i = 0; i < 16; i++) acc[i / 4][i % 4] = 0.f;
        pbase += 256; mp = 0; smask = 1; ph++;
        dreg += tphase; dcur = dreg + tcur;
        WSTAMP(ph - 1);
    };
    uint32_t t0 = now;
    const bool special = w == 0 || w == PW;
#pragma unroll 1
    for (int it = S - 1; it > 0; it--) {
        if (special) {
            if (w == PW) {
                asm volatile("st.shared.u32 [%0+8], %1;" :: "r"(flg), "r"(now - dl + tcur) : "memory");
            } else {
                uint32_t g0, g1, b0, b1, cand;
                asm volatile("ld.volatile.shared.v2.u32 {%0,%1}, [%5+32]; ld.volatile.shared.v2.u32 {%2,%3}, [%5+16]; ld.volatile.shared.u32 %4, [%5+8];"
                             : "=r"(g0), "=r"(g1), "=r"(b0), "=r"(b1), "=r"(cand) : "r"(flg) : "memory");
                const unsigned long long tb = ((unsigned long long)b1 << 32) | b0;
                const unsigned long long dg = (((unsigned long long)g1 << 32) | g0) - tb;
                const uint32_t t1 = (dg < 30000 && (int)(g0 - t0) > 0) ? g0 : t0;
                cand -= PTOL;
                asm volatile("{.reg .pred p, q; setp.eq.u32 p, %2, 0; setp.gt.and.s32 q, %3, 0, p; st.shared.u32 [%4+4], %5;\n"
                             "@q red.max.relaxed.gpu.global.u64 [%0], %1; @p cp.async.cg.shared.global [%4+32], [%0], 16;}"
                             :: "l"(&gs->t0), "l"(tb + (cand - b0)), "r"(lane), "r"(cand - t1), "r"(flg), "r"(t1) : "memory");
            }
        }
        dcur += t0 - tcur; tcur = t0;
#pragma unroll
        for (int k = 0; k < DS; k++) {
            if (k == DS - 1) asm volatile("ld.volatile.shared.u32 %0, [%1+4];" : "=r"(t0) : "r"(flg));
            step(k * SLOTB, 0);
            if (mp == mend || now < dl) {
                if (mp == mend) phase_end();
                asm volatile("{.reg .pred p; .reg .u32 d;\n"
                             "PACE_LOOP: mov.u32 d, %%globaltimer_lo; sub.u32 d, %0, d; setp.lt.u32 p, d, 32768; @p nanosleep.u32 32; @p bra.uni PACE_LOOP;}"
                             :: "r"(dl) : "memory");
            }
        }
    }
    __syncwarp();
    step(0, 1); step(SLOTB, 2); step(2 * SLOTB, 3); step(3 * SLOTB, 4);
    WSTAMP(3);

    {
        putacc((uint32_t*)(smem + SM_RING + 2 * SLOTB + w * 2048 + 512) + lane);
        const int wg = w >> 2, w4 = w & 3;
        int nd[8];
#pragma unroll
        for (int j = 0; j < 8; j++) { const int l = wg * 8 + j; nd[j] = order[(t >> 1) ? 79 - l : l]; asm volatile("" : "+r"(nd[j])); }
        const bool odd = t & 1;
        uint2* ob = (uint2*)out + (size_t)n0 * 128 + w4 * 16 + g + (odd ? 8 : 0);
        asm volatile("cp.async.wait_all;" ::: "memory");
        mbar_wait(mbarW, 0);
        asm volatile("fence.proxy.async.shared::cta;" ::: "memory");
        TSTAMP(26);
        bar_sync(2 + wg, 128);
        if ((tid & 127) == 0) {
            const uint32_t ticket = atomicAdd((uint32_t*)flag + 12, 1);
            int spins = 0;
            while (flag[13] + LEAD < ticket && ++spins < (1 << 16)) {}
        }
        bar_sync(2 + wg, 128);
        TSTAMP(27);
        const uint64_t descA0 = (uint64_t)(((sb + SM_RING) & 0x3FFFF) >> 4) | ((uint64_t)1 << 16) | ((uint64_t)(1024 >> 4) << 32) | ((uint64_t)1 << 62);
        const uint64_t descB0 = (uint64_t)(((sb + SM_RING + SLOTB + wg * 8192) & 0x3FFFF) >> 4) | ((uint64_t)(128 >> 4) << 16) | ((uint64_t)(1024 >> 4) << 32);
        float d[2][32];
        asm volatile("wgmma.fence.sync.aligned;" ::: "memory");
#pragma unroll
        for (int mt = 0; mt < 2; mt++) {
#pragma unroll
            for (int ks = 0; ks < 8; ks++) {
                const uint64_t da = descA0 + (uint64_t)((ks * 2048 + mt * 16384) >> 4), db = descB0 + (uint64_t)(((ks & 3) * 256 + (ks >> 2) * SLOTB) >> 4);
                asm volatile("{.reg .pred p; setp.ne.b32 p, %34, 0;\n"
                    "wgmma.mma_async.sync.aligned.m64n64k16.f32.bf16.bf16 "
                    "{%0,%1,%2,%3,%4,%5,%6,%7,%8,%9,%10,%11,%12,%13,%14,%15,%16,%17,%18,%19,%20,%21,%22,%23,%24,%25,%26,%27,%28,%29,%30,%31}, %32, %33, p, 1, 1, 1, 1;}"
                    : "+f"(d[mt][0]), "+f"(d[mt][1]), "+f"(d[mt][2]), "+f"(d[mt][3]), "+f"(d[mt][4]), "+f"(d[mt][5]), "+f"(d[mt][6]), "+f"(d[mt][7]),
                      "+f"(d[mt][8]), "+f"(d[mt][9]), "+f"(d[mt][10]), "+f"(d[mt][11]), "+f"(d[mt][12]), "+f"(d[mt][13]), "+f"(d[mt][14]), "+f"(d[mt][15]),
                      "+f"(d[mt][16]), "+f"(d[mt][17]), "+f"(d[mt][18]), "+f"(d[mt][19]), "+f"(d[mt][20]), "+f"(d[mt][21]), "+f"(d[mt][22]), "+f"(d[mt][23]),
                      "+f"(d[mt][24]), "+f"(d[mt][25]), "+f"(d[mt][26]), "+f"(d[mt][27]), "+f"(d[mt][28]), "+f"(d[mt][29]), "+f"(d[mt][30]), "+f"(d[mt][31])
                    : "l"(da), "l"(db), "r"(ks));
            }
            asm volatile("wgmma.commit_group.sync.aligned;" ::: "memory");
            if (mt == RELAT - 1) asm volatile("{.reg .pred p; setp.eq.u32 p, %1, 0; @p red.shared.add.u32 [%0+52], 1;}" :: "r"(flg), "r"(tid & 127) : "memory");
        }
#pragma unroll
        for (int mt = 0; mt < 2; mt++) {
            if (mt == 0) asm volatile("wgmma.wait_group.sync.aligned 1;" ::: "memory");
            else asm volatile("wgmma.wait_group.sync.aligned 0;" ::: "memory");
            if (RELAT == 0 && mt == 0 && (tid & 127) == 0) atomicAdd((uint32_t*)flag + 13, 1);
            TSTAMP(23 + mt);
#pragma unroll
            for (int i = 0; i < 32; i++) asm volatile("" : "+f"(d[mt][i]) :: "memory");
#pragma unroll
            for (int j = 0; j < 8; j++) {
                const uint32_t v0 = pack2(d[mt][4 * j], d[mt][4 * j + 1]), v1 = pack2(d[mt][4 * j + 2], d[mt][4 * j + 3]);
                const uint32_t rv = __shfl_xor_sync(0xffffffff, odd ? v0 : v1, 1);
                if (nd[j] < nn) ob[nd[j] * 128 + mt * 64] = odd ? make_uint2(rv, v1) : make_uint2(v0, rv);
            }
        }
    }
    TSTAMP(8);
}

}

extern "C" void kernel_launch(void* const* d_in, const int* in_sizes, int n_in, void* d_out, int out_size) {
    (void)in_sizes; (void)n_in; (void)out_size;
    cudaFuncSetAttribute(tfn_kernel, cudaFuncAttributeMaxDynamicSharedMemorySize, SM_TOTAL);
    Scratch* gs = nullptr;
    cudaGetSymbolAddress((void**)&gs, g_scratch);
    cudaLaunchConfig_t cfg = {};
    cfg.gridDim = dim3(NB); cfg.blockDim = dim3(NT); cfg.dynamicSmemBytes = SM_TOTAL; cfg.stream = cudaStreamPerThread;
    cudaLaunchAttribute at[1];
    at[0].id = cudaLaunchAttributeCooperative; at[0].val.cooperative = 1;
    cfg.attrs = at; cfg.numAttrs = 1;
    cudaLaunchKernelEx(&cfg, tfn_kernel, (const unsigned char*)d_in[0], (const int4*)d_in[1], (const int4*)d_in[2],
                       (const uint4*)d_in[3], (const uint4*)d_in[4], (const uint16_t*)d_in[5], (const uint16_t*)d_in[6],
                       (const uint4*)d_in[7], (uint32_t*)d_out, gs);
}
```

```cpp
#include <cuda_runtime.h>
#include <cuda_bf16.h>
#include <stdint.h>

#define VOL
#define ORD 1
#define ABL 0
namespace {

constexpr int NN = 10000;
constexpr int NE = 320000;
constexpr int NB = 132;
constexpr int NW = 20;
constexpr int NT = NW * 32;
constexpr int CW = NW - 1;
constexpr int PW = 10;
constexpr int NPB = 76;
constexpr int CELL = 48;
constexpr int RCH = 2880;
constexpr int CAP = 19;
constexpr int DS = 4;
constexpr int STEPB = 160;
constexpr int NE4 = NE / 4;
constexpr int NPIECE = NB * 8;
constexpr int KB = 320, KN = 32 * KB;
constexpr uint32_t F_WRAP = 1;

constexpr int SLOTB = NW * 2048;
constexpr int SM_RING = 0;
constexpr int SM_META = SM_RING + DS * SLOTB;
constexpr int SM_AZ = SM_META + NW * CAP * STEPB;
constexpr int SM_MISC = SM_AZ + 2048;
constexpr int SM_TOTAL = SM_MISC + 2048;
constexpr int SM_STAGE = SM_RING;
constexpr int SM_HIST = SM_RING + 25600;
constexpr int SM_POS = SM_RING;
constexpr int SM_SMALL = SM_HIST + 13056;
constexpr int SM_LIST = SM_RING + SLOTB;
constexpr int SM_ROUT = SM_RING + 2 * SLOTB;
constexpr int SM_RECS = SM_RING + 3 * SLOTB;
constexpr int SM_RAWY = SM_META;
constexpr int SM_RAWE = SM_RAWY + 608 * 32;
constexpr int SM_KEYS = SM_RAWE + 608 * 32;
static_assert(SM_TOTAL <= 232448 && SM_KEYS + NPIECE * 16 <= SM_AZ, "smem");
static_assert(SM_RECS + NB * CELL * 16 + 16 <= SM_AZ && SM_KEYS + NPIECE * 16 <= SM_RECS + NB * CELL * 16 && SM_SMALL + 1152 <= SLOTB && DS == 4, "smem");

struct Scratch {
    uint4 keys[NB * NPIECE];
    uint4 recs[NB * RCH];
    uint4 stash[NB * NW * 256];
    unsigned bar[4];
    unsigned long long t0, pad;
};
__device__ Scratch g_scratch;
#define TSTAMP(i)
#define TSTAMPC(i)
#define WSTAMP(i)

__device__ __forceinline__ void mma16816(float* d, uint32_t a0, uint32_t a1, uint32_t a2, uint32_t a3, uint32_t b0, uint32_t b1) {
    asm VOL("mma.sync.aligned.m16n8k16.row.col.f32.bf16.bf16.f32 {%0,%1,%2,%3}, {%4,%5,%6,%7}, {%8,%9}, {%0,%1,%2,%3};"
        : "+f"(d[0]), "+f"(d[1]), "+f"(d[2]), "+f"(d[3]) : "r"(a0), "r"(a1), "r"(a2), "r"(a3), "r"(b0), "r"(b1));
}
__device__ __forceinline__ void mma1688z(float* d, uint32_t a0, uint32_t a1, uint32_t b0) {
    asm VOL("mma.sync.aligned.m16n8k8.row.col.f32.bf16.bf16.f32 {%0,%1,%2,%3}, {%4,%5}, {%6}, {%7,%7,%7,%7};"
        : "=f"(d[0]), "=f"(d[1]), "=f"(d[2]), "=f"(d[3]) : "r"(a0), "r"(a1), "r"(b0), "f"(0.f));
}
__device__ __forceinline__ uint32_t pack2(float lo, float hi) {
    uint32_t r; asm VOL("cvt.rn.bf16x2.f32 %0, %1, %2;" : "=r"(r) : "f"(hi), "f"(lo)); return r;
}
__device__ __forceinline__ float silu_h(float h) {
    float t; asm VOL("tanh.approx.f32 %0, %1;" : "=f"(t) : "f"(h)); return fmaf(h, t, h);
}
__device__ __forceinline__ uint32_t mul_lo(uint32_t v, uint32_t r) {
    __nv_bfloat162 a = *(__nv_bfloat162*)&v, b = *(__nv_bfloat162*)&r; __nv_bfloat162 c = __hmul2(a, __low2bfloat162(b)); return *(uint32_t*)&c;
}
__device__ __forceinline__ uint32_t mul_hi(uint32_t v, uint32_t r) {
    __nv_bfloat162 a = *(__nv_bfloat162*)&v, b = *(__nv_bfloat162*)&r; __nv_bfloat162 c = __hmul2(a, __high2bfloat162(b)); return *(uint32_t*)&c;
}
__device__ __forceinline__ uint2 lds64(uint32_t a) {
    uint2 r; asm volatile("ld.shared.v2.u32 {%0,%1}, [%2];" : "=r"(r.x), "=r"(r.y) : "r"(a)); return r;
}
__device__ __forceinline__ uint4 lds128(uint32_t a) {
    uint4 r; asm volatile("ld.shared.v4.u32 {%0,%1,%2,%3}, [%4];" : "=r"(r.x), "=r"(r.y), "=r"(r.z), "=r"(r.w) : "r"(a) : "memory"); return r;
}
__device__ __forceinline__ void bar_sync(int id, int n) { asm volatile("bar.sync %0, %1;" :: "r"(id), "r"(n) : "memory"); }
__device__ __forceinline__ void bar_arrive(int id, int n) { asm volatile("bar.arrive %0, %1;" :: "r"(id), "r"(n) : "memory"); }
__device__ __forceinline__ void mbar_wait(uint32_t bar, uint32_t ph) {
    uint32_t done; int spins = 0;
    do {
        asm volatile("{.reg .pred p; mbarrier.try_wait.parity.shared.b64 p, [%1], %2; selp.u32 %0,1,0,p;}" : "=r"(done) : "r"(bar), "r"(ph) : "memory");
    } while (!done && ++spins < (1 << 22));
}
__device__ __forceinline__ unsigned gbar_read(const unsigned* ctr) {
    unsigned v; asm volatile("ld.relaxed.gpu.global.u32 %0, [%1];" : "=r"(v) : "l"(ctr) : "memory");
    return v;
}
__device__ __forceinline__ void gbar_arrive(unsigned* ctr) {
    asm volatile("red.add.release.gpu.global.u32 [%0], 1;" :: "l"(ctr) : "memory");
}
__device__ __forceinline__ bool gbar_wait(const unsigned* ctr, unsigned target) {
    unsigned v; int spins = 0;
    do { asm volatile("ld.acquire.gpu.global.u32 %0, [%1];" : "=r"(v) : "l"(ctr) : "memory"); } while ((int)(v - target) < 0 && ++spins < (1 << 22));
    return (int)(v - target) >= 0;
}
__device__ __forceinline__ int chunk_start4(int c) { return (c * NE4) / NB; }
__device__ __forceinline__ float bf2f(uint32_t h) { return __uint_as_float(h << 16); }

__device__ __noinline__ void slow_path(unsigned char* smem, int n0, int nn, const uint16_t* x, const int* src, const int* dst,
                                       const uint16_t* Y, const uint16_t* ef, const uint16_t* w_rad, const uint16_t* cg,
                                       const uint16_t* w_mix, __nv_bfloat16* out) {
    float* agg = (float*)smem;
    const int tid = threadIdx.x, lane = tid & 31, w = tid >> 5;
    bar_sync(1, NT);
    for (int i = tid; i < NPB * 512; i += NT) agg[i] = 0.f;
    bar_sync(1, NT);
    for (int e0 = w * 32; e0 < NE; e0 += NT) {
        int dl = dst[e0 + lane] - n0;
        unsigned m = __ballot_sync(0xffffffff, dl >= 0 && dl < nn);
        while (m) {
            int l = __ffs(m) - 1; m &= m - 1;
            int e = e0 + l, d = __shfl_sync(0xffffffff, dl, l), s = src[e];
            float T[16];
            for (int i = 0; i < 4; i++) for (int o = 0; o < 4; o++) {
                float a = 0.f;
                for (int f = 0; f < 4; f++) a += bf2f(Y[e * 4 + f]) * bf2f(cg[i * 16 + f * 4 + o]);
                T[i * 4 + o] = a;
            }
            for (int k = 0; k < 4; k++) {
                int c = lane + 32 * k;
                float z = 0.f;
                for (int j = 0; j < 4; j++) z += bf2f(ef[e * 4 + j]) * bf2f(w_rad[j * 128 + c]);
                float R = z / (1.f + __expf(-z));
                for (int o = 0; o < 4; o++) {
                    float a = 0.f;
                    for (int i = 0; i < 4; i++) a += bf2f(x[(size_t)s * 512 + c * 4 + i]) * T[i * 4 + o];
                    atomicAdd(&agg[d * 512 + c * 4 + o], R * a);
                }
            }
        }
    }
    bar_sync(1, NT);
    for (int i = tid; i < nn * 512; i += NT) {
        int n = i >> 9, d = (i >> 2) & 127, o = i & 3;
        float a = 0.f;
        for (int c = 0; c < 128; c++) a += agg[n * 512 + c * 4 + o] * bf2f(w_mix[c * 128 + d]);
        out[(size_t)(n0 + n) * 512 + (i & 511)] = __float2bfloat16(a);
    }
}

#define PACE 24000
#define YDELAY 300
#define TP 0
#define BFENCE 0
#define EPI 2
#define LEAD 0
#define RELAT 2
#define POFF 1700
#define PTOL 600
__global__ void __launch_bounds__(NT, 1)
tfn_kernel(const unsigned char* __restrict__ x, const int4* __restrict__ src4, const int4* __restrict__ dst4,
           const uint4* __restrict__ Y, const uint4* __restrict__ ef, const uint16_t* __restrict__ w_rad,
           const uint16_t* __restrict__ cg, const uint4* __restrict__ w_mix, uint32_t* __restrict__ out, Scratch* __restrict__ gs) {
    extern __shared__ __align__(1024) unsigned char smem[];
    const uint32_t sb = (uint32_t)__cvta_generic_to_shared(smem);
    const int b = blockIdx.x, tid = threadIdx.x, lane = tid & 31, g = lane >> 2, t = lane & 3;
    const int w = __shfl_sync(0xffffffff, tid >> 5, 0);
    uint32_t* stage = (uint32_t*)(smem + SM_STAGE);
    uint32_t* hist = (uint32_t*)(smem + SM_HIST);
    uint32_t* cnt = (uint32_t*)(smem + SM_MISC);
    uint32_t* deg = cnt + 136;
    uint32_t* order = deg + 104;
    uint32_t* cnt2 = order + 80;
    volatile uint32_t* flag = cnt2 + 136;
    const uint32_t mbarK = sb + SM_MISC + 1920, mbarR = mbarK + 8, mbarW = mbarK + 16;
    const int n0 = b * NPB, nn = min(NPB, NN - n0);
    TSTAMP(0);

    const int c0 = chunk_start4(b), c1 = chunk_start4(b + 1);
    const bool has4 = c0 + tid < c1;
    int4 d4 = make_int4(0, 0, 0, 0), s4 = d4;
    if (has4) { d4 = __ldg(dst4 + c0 + tid); s4 = __ldg(src4 + c0 + tid); }
    unsigned tgt = 0;
    if (tid == NT - 1) {
        tgt = gbar_read(&gs->bar[0]);
        asm volatile("mbarrier.init.shared.b64 [%0], 1;" :: "r"(mbarK));
        asm volatile("mbarrier.init.shared.b64 [%0], 1;" :: "r"(mbarR));
        asm volatile("mbarrier.init.shared.b64 [%0], 512;" :: "r"(mbarW));
        asm volatile("fence.mbarrier_init.release.cluster;" ::: "memory");
        flag[0] = 0; flag[12] = 0; flag[13] = 0; flag[15] = 0;
    }
    if (w == CW) {
        asm volatile("cp.async.cg.shared.global [%0], [%1], 16;" :: "r"(sb + SM_SMALL + lane * 16), "l"(w_rad + lane * 8) : "memory");
        asm volatile("cp.async.cg.shared.global [%0], [%1], 16;" :: "r"(sb + SM_SMALL + 512 + lane * 16), "l"(w_rad + 256 + lane * 8) : "memory");
        if (lane < 8) asm volatile("cp.async.cg.shared.global [%0], [%1], 16;" :: "r"(sb + SM_SMALL + 1024 + lane * 16), "l"(cg + lane * 8) : "memory");
    }
    ((uint4*)hist)[tid] = make_uint4(0, 0, 0, 0);
    {
        const uint32_t dk = (80 + b % 22) * KN + (b & 31) * KB;
#pragma unroll
        for (int j = 0; j < 3; j++) if (tid + j * NT < NB * CELL / 4) ((uint4*)stage)[tid + j * NT] = make_uint4(dk, dk, dk, dk);
    }
    if (tid < 136) cnt[tid] = 0;
    if (tid == 0) { *(uint4*)(smem + SM_MISC + 1824 + 32) = make_uint4(0, 0, 0, 0); *(uint4*)(smem + SM_RECS + NB * CELL * 16) = make_uint4(0, 0, 0, 0); }
    if (tid < 80) { deg[tid] = 127 - tid; order[tid] = tid; }
    __syncthreads();
    TSTAMP(9);
    if (tid == 64) {
        if (YDELAY) __nanosleep(YDELAY);
        asm volatile("mbarrier.arrive.expect_tx.shared.b64 _, [%0], %1;" :: "r"(mbarR), "r"((c1 - c0) * 64) : "memory");
        asm volatile("cp.async.bulk.shared::cluster.global.mbarrier::complete_tx::bytes [%0], [%1], %2, [%3];"
                     :: "r"(sb + SM_RAWY), "l"(Y + 2 * c0), "r"((c1 - c0) * 32), "r"(mbarR) : "memory");
        asm volatile("cp.async.bulk.shared::cluster.global.mbarrier::complete_tx::bytes [%0], [%1], %2, [%3];"
                     :: "r"(sb + SM_RAWE), "l"(ef + 2 * c0), "r"((c1 - c0) * 32), "r"(mbarR) : "memory");
    }

    uint32_t bin[4] = {0, 0, 0, 0}, slot[4] = {0, 0, 0, 0};
    if (has4) {
        const uint32_t dd[4] = {(uint32_t)d4.x, (uint32_t)d4.y, (uint32_t)d4.z, (uint32_t)d4.w}, ss[4] = {(uint32_t)s4.x, (uint32_t)s4.y, (uint32_t)s4.z, (uint32_t)s4.w};
#pragma unroll
        for (int k = 0; k < 4; k++) { bin[k] = dd[k] / NPB; slot[k] = atomicAdd(&cnt[bin[k]], 1); }
#pragma unroll
        for (int k = 0; k < 4; k++) stage[bin[k] * CELL + min(slot[k], CELL - 1)] = (dd[k] - bin[k] * NPB) * KN + ss[k];
    }
    if (w == CW) {
        if (tid == NT - 1) { tgt = tgt / NB + 1; flag[14] = (tgt & 1) << 31; tgt *= NB; }
        asm volatile("cp.async.wait_all;" ::: "memory");
    }
    bar_sync(1, NT);
    TSTAMP(1);
    const uint32_t tag = flag[14];
#pragma unroll
    for (int j = 0; j < 2; j++) {
        const int i = tid + j * NT;
        if (i < NPIECE) {
            const uint2 sa = *(const uint2*)(stage + i * 6), sc = *(const uint2*)(stage + i * 6 + 2);
            uint2 se = *(const uint2*)(stage + i * 6 + 4);
            const uint32_t cf = cnt[i >> 3], cn = min(cf, 63u);
            if ((i & 7) == 7) {
                const uint32_t al = cf > CELL - 8 ? 7 : 0;
                se.y = (atomicAdd((uint32_t*)flag + 15, cf + al) + al) & ~al;
                cnt2[i >> 3] = se.y;
            }
            asm volatile("{.reg .b64 lo, hi; mov.b64 lo, {%1,%2}; mov.b64 hi, {%3,%4}; st.relaxed.gpu.global.v2.b64 [%0], {lo, hi};}"
                         :: "l"(gs->keys + ((i >> 3) * NB + b) * 8 + ((i ^ b) & 7)),
                            "r"(sa.x | (se.x << 20)), "r"(sa.y | ((se.x >> 12) << 20) | ((cn & 7) << 28) | tag),
                            "r"(sc.x | (se.y << 20)), "r"(sc.y | ((se.y >> 12) << 20) | ((cn >> 3) << 28) | tag) : "memory");
        }
    }
    bar_sync(1, NT);
    if (tid == NT - 1) {
        TSTAMPC(10);
        asm volatile("red.add.relaxed.gpu.global.u32 [%0], 1;" :: "l"(&gs->bar[0]) : "memory");
    }
    uint32_t at[4];
    {
        const int o = g & 3, f = 2 * (t & 1);
#pragma unroll
        for (int i = 0; i < 4; i++) {
            const uint16_t* cp = (const uint16_t*)(smem + SM_SMALL + 1024) + i * 16 + f * 4 + o;
            at[i] = (t >> 1) == (g >> 2) ? cp[0] | ((uint32_t)cp[4] << 16) : 0;
        }
    }

    uint32_t key[2][6], ha[2][6], rk[2][6], kidx[2], ka[2];
    int nk[2];
#pragma unroll
    for (int j = 0; j < 2; j++) {
        const int i0 = j ? 2 * 608 - 1 - tid : tid, i = min(i0, NPIECE - 1), r = i / NB, c = i - r * NB;
        ka[j] = sb + SM_KEYS + (c * 8 + ((r ^ c) & 7)) * 16;
        kidx[j] = (c * CELL + r * 6) << 17;
        nk[j] = i0 < NPIECE && w < CW ? -6 * r : -1000;
    }
    asm volatile("" : "+r"(at[0]), "+r"(at[1]), "+r"(at[2]), "+r"(at[3]), "+r"(ka[0]), "+r"(ka[1]), "+r"(kidx[0]), "+r"(kidx[1]), "+r"(nk[0]), "+r"(nk[1]));
    if (w == CW) {
        if (tid == NT - 1) {
            asm volatile("mbarrier.arrive.expect_tx.shared.b64 _, [%0], %1;" :: "r"(mbarK), "r"(NPIECE * 16) : "memory");
            gbar_wait(&gs->bar[0], tgt);
            TSTAMPC(13);
            asm volatile("fence.proxy.async.global;" ::: "memory");
            asm volatile("cp.async.bulk.shared::cluster.global.mbarrier::complete_tx::bytes [%0], [%1], %2, [%3];"
                         :: "r"(sb + SM_KEYS), "l"(gs->keys + b * NPIECE), "r"(NPIECE * 16), "r"(mbarK) : "memory");
        }
        __syncwarp();
        bar_sync(7, NT);
        if (tid == NT - 1) {
            TSTAMPC(11);
            asm volatile("cp.async.bulk.global.shared::cta.bulk_group [%0], [%1], %2;"
                         :: "l"(gs->recs + b * RCH), "r"(sb + SM_ROUT), "r"(((flag[15] + 1) & ~1u) * 16) : "memory");
            asm volatile("cp.async.bulk.commit_group; cp.async.bulk.wait_group 0;" ::: "memory");
            TSTAMPC(14);
            asm volatile("red.add.relaxed.gpu.global.u32 [%0], 1;" :: "l"(&gs->bar[1]) : "memory");
            TSTAMPC(15);
            if (!gbar_wait(&gs->bar[1], tgt)) *flag = 1;
            TSTAMPC(17);
        }
    } else {
        if (w < 8) {
            const uint32_t* wp = (const uint32_t*)(smem + SM_SMALL) + (t & 1) * 128 + 8 * w + g;
            const uint32_t wr0 = t < 2 ? wp[0] : 0, wr1 = t < 2 ? wp[64] : 0;
            *(uint2*)(smem + SM_AZ + (w >> 1) * 512 + lane * 16 + (w & 1) * 8) =
                make_uint2(pack2(0.5f * bf2f(wr0 & 0xFFFF), 0.5f * bf2f(wr1 & 0xFFFF)), pack2(0.5f * bf2f(wr0 >> 16), 0.5f * bf2f(wr1 >> 16)));
        }
        const bool sw = g & 1;
        uint32_t rp[4];
#pragma unroll
        for (int k = 0; k < 4; k++) rp[k] = cnt2[bin[k]] + slot[k];
        uint4* ro = (uint4*)(smem + SM_ROUT);
        uint4 *p0 = ro + (sw ? rp[2] : rp[0]), *p1 = ro + (sw ? rp[3] : rp[1]), *p2 = ro + (sw ? rp[0] : rp[2]), *p3 = ro + (sw ? rp[1] : rp[3]);
        const uint32_t ya = sb + SM_RAWY + tid * 32 + (sw ? 16 : 0);
        mbar_wait(mbarR, 0);
        TSTAMP(18);
        if (has4) {
            const uint4 y0 = lds128(ya), e0 = lds128(ya + (SM_RAWE - SM_RAWY)), y1 = lds128(ya ^ 16), e1 = lds128((ya ^ 16) + (SM_RAWE - SM_RAWY));
            *p0 = make_uint4(y0.x, e0.x, y0.y, e0.y); *p1 = make_uint4(y0.z, e0.z, y0.w, e0.w);
            *p2 = make_uint4(y1.x, e1.x, y1.y, e1.y); *p3 = make_uint4(y1.z, e1.z, y1.w, e1.w);
        }
        asm volatile("fence.proxy.async.shared::cta;" ::: "memory");
        bar_arrive(7, NT);
    }
    __syncwarp();
    TSTAMP(2);

    if (w < CW) {
        mbar_wait(mbarK, 0);
        TSTAMP(3);
        uint4 v[2] = {lds128(ka[0]), lds128(ka[1])};
#pragma unroll
        for (int j = 0; j < 2; j++) {
            int spins = 0;
            while ((int)((v[j].y ^ tag) | (v[j].w ^ tag)) < 0) {
                asm volatile("{.reg .b64 lo, hi; ld.relaxed.gpu.global.v2.b64 {lo, hi}, [%4]; mov.b64 {%0,%1}, lo; mov.b64 {%2,%3}, hi;}"
                             : "=r"(v[j].x), "=r"(v[j].y), "=r"(v[j].z), "=r"(v[j].w) : "l"((const unsigned char*)(gs->keys + b * NPIECE) + (ka[j] - sb - SM_KEYS)) : "memory");
                if (++spins > (1 << 20)) { *flag = 1; break; }
            }
            const uint32_t hc = ((v[j].y >> 28) & 7) | ((v[j].w >> 25) & 0x38);
            if (j == 1 && nk[j] == -42) {
                cnt[kidx[j] / (CELL << 17)] = hc | ((v[j].z >> 20) << 8);
                v[j].w |= ((80 * KN) >> 12) << 20;
            }
            if (hc > CELL - 1) *flag = 1;
            nk[j] += hc;
            if (nk[j] > 0) {
                key[j][0] = v[j].x & 0xFFFFF; key[j][1] = v[j].y & 0xFFFFF; key[j][2] = v[j].z & 0xFFFFF; key[j][3] = v[j].w & 0xFFFFF;
                key[j][4] = (v[j].x >> 20) | ((v[j].y >> 8) & 0xFF000); key[j][5] = (v[j].z >> 20) | ((v[j].w >> 8) & 0xFF000);
#pragma unroll
                for (int u = 0; u < 6; u++) {
                    ha[j][u] = __umulhi(key[j][u], 0xFFFFFFFFu / KB + 1);
                    rk[j][u] = atomicAdd(&hist[ha[j][u]], 1);
                    atomicAdd(&deg[ha[j][u] >> 5], 128);
                }
            }
        }
        bar_sync(9, NT - 32);
        TSTAMP(20);
#pragma unroll
        for (int j = 0; j < 2; j++) kidx[j] += ((cnt[kidx[j] / (CELL << 17)] >> 8) & 7) << 17;
        const int n = tid >> 3, sub = tid & 7;
        const uint32_t me = deg[n];
        int r = 0;
#pragma unroll
        for (int k = 0; k < 5; k++) { const uint2 dd = *(const uint2*)(deg + sub * 10 + 2 * k); r += (dd.x > me) + (dd.y > me); }
        r += __shfl_xor_sync(0xffffffff, r, 1); r += __shfl_xor_sync(0xffffffff, r, 2); r += __shfl_xor_sync(0xffffffff, r, 4);
        if (sub == 0) order[r] = n;
    }
    if (w < CW) {
        bar_sync(9, NT - 32);
        TSTAMP(22);
#pragma unroll 1
        for (int v = w; v < NW; v += (w == 1 ? CW - 1 : NW)) {
            const uint2 na = *(const uint2*)(order + 2 * v), nb = *(const uint2*)(order + 78 - 2 * v);
            const uint32_t ia0 = na.x * 32 + lane, ib0 = nb.y * 32 + lane, ia1 = na.y * 32 + lane, ib1 = nb.x * 32 + lane;
            const uint32_t ca = hist[ia0] + (hist[ia1] << 16), cab = ca + hist[ib0] + (hist[ib1] << 16);
            uint32_t inc = cab;
#pragma unroll
            for (int o = 1; o < 32; o <<= 1)
                asm volatile("{.reg .pred p; .reg .u32 u; shfl.sync.up.b32 u|p, %0, %1, 0, 0xffffffff; @p add.u32 %0, %0, u;}" : "+r"(inc) : "r"(o));
            const uint32_t ea = inc - cab, eb = ea + ca, base = sb + SM_LIST + v * 2048;
            uint2* pos = (uint2*)(smem + SM_POS);
            pos[ia0] = make_uint2(base + (ea & 0xFFFF) * 8, na.x * (0u - 4 * KN));
            pos[ib0] = make_uint2(base + (eb & 0xFFFF) * 8, nb.y * (0u - 4 * KN) + 0x10000);
            pos[ia1] = make_uint2(base + 4 + (ea >> 16) * 8, na.y * (0u - 4 * KN));
            pos[ib1] = make_uint2(base + 4 + (eb >> 16) * 8, nb.x * (0u - 4 * KN) + 0x10000);
            if (lane == 31) { cnt2[v] = inc; if (max(inc & 0xFFFF, inc >> 16) > 4 * CAP) *flag = 1; }
        }
        bar_sync(9, NT - 32);
        TSTAMP(21);
        const uint32_t over = *flag;
#pragma unroll
        for (int j = 0; j < 2; j++) {
            if (nk[j] > 0) {
                uint2 h[6];
#pragma unroll
                for (int u = 0; u < 6; u++) h[u] = lds64(sb + SM_POS + ha[j][u] * 8);
                if (over) nk[j] = 0;
#pragma unroll
                for (int u = 0; u < 6; u++)
                    asm volatile("{.reg .pred p; setp.gt.s32 p, %2, %3; @p st.shared.u32 [%0], %1;}"
                                 :: "r"(h[u].x + rk[j][u] * 8), "r"(key[j][u] * 4 + h[u].y + (kidx[j] + (u << 17))), "r"(nk[j]), "r"(u) : "memory");
            }
        }
    }
    bar_sync(1, NT);
    TSTAMP(4);
    if (*flag) {
        slow_path(smem, n0, nn, (const uint16_t*)x, (const int*)src4, (const int*)dst4, (const uint16_t*)Y, (const uint16_t*)ef, w_rad, cg,
                  (const uint16_t*)w_mix, (__nv_bfloat16*)out);
        return;
    }
    {
        const uint32_t ci = cnt[min(w + NW * lane, NB)];
        const uint4* gp = gs->recs + w * RCH + lane;
        const uint32_t sp = sb + SM_RECS + (w * CELL + lane) * 16;
#pragma unroll
        for (int j = 0; j < 7; j++) {
            const uint32_t cj = __shfl_sync(0xffffffff, ci, j);
            asm volatile("{.reg .pred p; setp.lt.u32 p, %2, %3; @p cp.async.cg.shared.global [%0], [%1], 16;}"
                         :: "r"(sp + j * (NW * CELL * 16) + ((cj >> 4) & 0x70)), "l"(gp + j * (NW * RCH) + (cj >> 8)), "r"(lane), "r"(cj & 0xFF) : "memory");
        }
        if (__any_sync(0xffffffff, (ci & 0xFF) > 32)) {
#pragma unroll 1
            for (int j = 0; j < 7; j++) {
                const uint32_t cj = __shfl_sync(0xffffffff, ci, j);
                if (lane + 32 < (cj & 0xFF))
                    asm volatile("cp.async.cg.shared.global [%0], [%1], 16;"
                                 :: "r"(sp + j * (NW * CELL * 16) + ((cj >> 4) & 0x70) + 512), "l"(gp + j * (NW * RCH) + (cj >> 8) + 32) : "memory");
            }
        }
        asm volatile("cp.async.commit_group;" ::: "memory");
    }
    const uint32_t len2 = cnt2[w];
    const int S = __shfl_sync(0xffffffff, max((int)(max(len2 & 0xFFFF, len2 >> 16) + 3) >> 2, DS + 1), 0);
    const int mylen = (lane & 1) ? len2 >> 16 : len2 & 0xFFFF;
    constexpr int NRAW = (CAP + 3) / 4;
    uint32_t bits0 = 0, raw[NRAW];
    unsigned char* meta = smem + SM_META + w * (CAP * STEPB);
#pragma unroll
    for (int k = 0; k < NRAW; k++) raw[k] = mylen ? ((uint32_t*)(smem + SM_LIST + w * 2048))[min(k * 16 + (lane >> 1), mylen - 1) * 2 + (lane & 1)] : 4 * n0;
    const uint32_t sv0 = raw[0] & 0xFFFF;
    const int q = lane >> 3, c = lane & 7;
    const uint32_t ring0 = sb + SM_RING + w * 2048;
    uint32_t wdst = ring0 + q * 128 + ((c + 2 * q) & 7) * 16;
    uint32_t rsrc = ring0 + t * 128 + ((g + 2 * t) & 7) * 16;
    uint32_t recl = sb + SM_META + w * (CAP * STEPB) + g * 16 + (t & 1) * 8, srcl = sb + SM_META + w * (CAP * STEPB) + 128 + q * 8;
    uint32_t flg = sb + SM_MISC + (136 + 104 + 80 + 136) * 4;
    asm volatile("" : "+r"(wdst), "+r"(rsrc), "+r"(recl), "+r"(srcl), "+r"(flg));
    const unsigned char* pbase = x + c * 16;
    auto cpa2 = [&](uint32_t dstp, uint32_t sv) {
        asm volatile("cp.async.cg.shared.global [%0], [%1], 16; cp.async.cg.shared.global [%0+1024], [%1+128], 16;"
                     :: "r"(dstp), "l"(pbase + (size_t)sv * 256) : "memory");
    };
    auto fill = [&](int i) {
        cpa2(wdst + i * SLOTB, __shfl_sync(0xffffffff, sv0, 8 * i + 2 * q)); cpa2(wdst + i * SLOTB + 512, __shfl_sync(0xffffffff, sv0, 8 * i + 2 * q + 1));
        asm volatile("cp.async.commit_group;" ::: "memory");
    };
    fill(0);
    TSTAMP(5);
    if (w == 0) {
        unsigned long long tbase;
        asm volatile("mov.u64 %0, %%globaltimer;" : "=l"(tbase));
        tbase += POFF;
        flag[1] = (uint32_t)tbase; flag[2] = (uint32_t)tbase; flag[4] = (uint32_t)tbase; flag[5] = (uint32_t)(tbase >> 32);
        if (lane == 0) {
            asm volatile("red.max.relaxed.gpu.global.u64 [%0], %1;" :: "l"(&gs->t0), "l"(tbase) : "memory");
            if (b < 128) asm volatile("cp.async.bulk.prefetch.L2.global [%0], 256;" :: "l"(w_mix + b * 16));
        }
    }
    uint32_t ra[NRAW];
#pragma unroll
    for (int k = 0; k < NRAW; k++) {
        const uint32_t m = (__ballot_sync(0xffffffff, raw[k] & 0x10000) >> g) & 0x01010101u;
        bits0 |= ((m * 0x10204080u) >> 28) << (4 * k);
        ra[k] = sb + SM_RECS + (k * 16 + (lane >> 1) < mylen ? raw[k] >> 17 : NB * CELL) * 16;
    }
    if (t < 2) bits0 = ~bits0;
    fill(1);
    asm volatile("cp.async.wait_group 2;" ::: "memory");
    bar_sync(1, NT);
    TSTAMP(19);
    {
        uint4 rv[NRAW];
#pragma unroll
        for (int k = 0; k < NRAW - 1; k++) rv[k] = lds128(ra[k]);
        if ((NRAW - 1) * 4 < S) rv[NRAW - 1] = lds128(ra[NRAW - 1]);
        if (tid == 0) asm volatile("cp.async.cg.shared.global [%0], [%1], 16;" :: "r"(sb + SM_MISC + 1824 + 32), "l"(&gs->t0) : "memory");
        fill(2);
        bar_sync(1, NT);
        TSTAMP(12);
        unsigned char* mr = meta + (q - 1) * STEPB + c * 16;
        unsigned char* ms = meta + (q - DS - 1) * STEPB + 128 + c * 4;
#pragma unroll
        for (int k = 0; k < NRAW; k++) {
            if (k == 0) {
                *(uint4*)(mr + (q == 0 ? S * STEPB : 0)) = rv[k];
                *(uint32_t*)(ms + S * STEPB) = sv0 + F_WRAP;
            } else if (k * 4 + q < S) {
                *(uint4*)(mr + k * 4 * STEPB) = rv[k];
                *(uint32_t*)(ms + k * 4 * STEPB + (k == 1 && q == 0 ? S * STEPB : 0)) = raw[k] & 0xFFFF;
            }
        }
    }
    __syncwarp();
    const uint32_t tphase = PACE / 4;
    uint32_t dreg;
    {
        const int st = lane == 0 ? S - 1 : min(lane, S) - 1;
        const uint4 u0 = *(const uint4*)(meta + st * STEPB + 128), u1 = *(const uint4*)(meta + st * STEPB + 144);
        int pos = (u0.x + u0.y + u0.z + u0.w + u1.x + u1.y + u1.z + u1.w) >> 5;
        pos += ((u0.x & F_WRAP) ? NN : 0) + (lane == S ? NN : 0) - NN * (2 * DS + 1) / 32;
        dreg = pos * (int)tphase / NN;
    }
    fill(3);
    TSTAMP(6);

    uint32_t* stash = (uint32_t*)(gs->stash + (b * NW + w) * 256) + lane;
    float acc[4][4];
#pragma unroll
    for (int i = 0; i < 16; i++) acc[i / 4][i % 4] = 0.f;
    uint4 az = *(const uint4*)(smem + SM_AZ + lane * 16);
    uint32_t dcur = dreg, dl = 0, now = flag[1], tcur = 0;
    uint32_t mp = 0, smask = 1;
    const uint32_t mend = S * STEPB;
    uint2 r = lds64(mend - STEPB + recl), s0 = lds64(mend - STEPB + srcl);
    auto step = [&](const uint32_t off, const int mode) {
        auto tick = [&]() { if (mode == 0) { unsigned long long n64; asm volatile("mov.u64 %0, %%globaltimer;" : "=l"(n64)); now = (uint32_t)n64; } };
        if (TP == 0) tick();
        const uint2 rc = r, sc = s0;
        if (ORD & 1) { if (mode != 4) r = lds64(mp + recl); if (mode == 0) s0 = lds64(mp + srcl); }
        asm volatile("cp.async.wait_group %0;" :: "n"(DS - 1) : "memory");
        const uint4 xa = lds128(rsrc + off), xb = lds128(rsrc + off + 512), xc = lds128(rsrc + off + 1024), xd = lds128(rsrc + off + 1536);
        if (!(ORD & 1) && !(ORD & 4)) { if (mode != 4) r = lds64(mp + recl); if (mode == 0) s0 = lds64(mp + srcl); }
        if (mode == 0) {
            if (ORD & 2) {
                asm volatile("shfl.sync.idx.b32 %0, %1, 1, 31, 0xffffffff; shfl.sync.down.b32 %1, %1, 1, 31, 0xffffffff;\n"
                             "cp.async.cg.shared.global [%2], [%3], 16; cp.async.cg.shared.global [%2+512], [%4], 16;\n"
                             "cp.async.cg.shared.global [%2+1024], [%3+128], 16; cp.async.cg.shared.global [%2+1536], [%4+128], 16;"
                             : "=&r"(dl), "+r"(dcur) : "r"(wdst + off), "l"(pbase + (size_t)sc.x * 256), "l"(pbase + (size_t)sc.y * 256) : "memory");
            } else {
                dl = __shfl_sync(0xffffffff, dcur, 1); dcur = __shfl_down_sync(0xffffffff, dcur, 1);
                cpa2(wdst + off, sc.x); cpa2(wdst + off + 512, sc.y);
            }
        }
        if (mode == 1 && w < 16) {
#pragma unroll
            for (int j = 0; j < 4; j++) {
                const int kk = 4 * j + q, ch = 16 * (w & 7) + 2 * (kk & 7) + (kk >> 3);
                asm volatile("cp.async.cg.shared.global [%0], [%1], 16;" :: "r"(ring0 + kk * 128 + ((c ^ (kk & 7)) << 4)), "l"(w_mix + ch * 16 + (w >> 3) * 8 + c) : "memory");
            }
            asm volatile("cp.async.mbarrier.arrive.noinc.shared.b64 [%0];" :: "r"(mbarW) : "memory");
        }
        if (mode == 2 || mode == 3) {
#pragma unroll
            for (int j = 0; j < 4; j += mode - 1)
                asm volatile("cp.async.cg.shared.global [%0], [%1], 16;" :: "r"(ring0 + off + j * 512 + lane * 16), "l"(stash + (mode - 2) * 512 + j * 128 + lane * 3) : "memory");
        }
        asm volatile("cp.async.commit_group;" ::: "memory");
        if (ORD & 4) { if (mode != 4) r = lds64(mp + recl); if (mode == 0) s0 = lds64(mp + srcl); }
        float z[4], y[4], t1[4], t2[4];
        mma1688z(z, az.x, az.y, rc.y);
        mma1688z(y, az.z, az.w, rc.y);
        uint32_t bt;
        asm("{.reg .pred p; .reg .b32 m; and.b32 m, %2, %3; setp.ne.u32 p, m, 0; selp.b32 %0, %1, 0, p;}" : "=r"(bt) : "r"(rc.x), "r"(bits0), "r"(smask));
        mma1688z(t1, at[0], at[1], bt);
        mma1688z(t2, at[2], at[3], bt);
        if (TP == 1) tick();
        const uint32_t T0 = pack2(t1[0], t1[2]), T1 = pack2(t2[0], t2[2]), T2 = pack2(t1[1], t1[3]), T3 = pack2(t2[1], t2[3]);
        const uint32_t R0 = pack2(silu_h(z[0]), silu_h(z[2]));
        if (TP == 2) tick();
        const uint32_t R1 = pack2(silu_h(z[1]), silu_h(z[3]));
        if (TP == 3) tick();
        const uint32_t R2 = pack2(silu_h(y[0]), silu_h(y[2])), R3 = pack2(silu_h(y[1]), silu_h(y[3]));
        if (TP == 4) tick();
        mma16816(acc[0], mul_lo(xa.x, R0), mul_hi(xa.z, R0), mul_lo(xa.y, R0), mul_hi(xa.w, R0), T0, T1);
        mma16816(acc[1], mul_lo(xb.x, R1), mul_hi(xb.z, R1), mul_lo(xb.y, R1), mul_hi(xb.w, R1), T2, T3);
        mma16816(acc[2], mul_lo(xc.x, R2), mul_hi(xc.z, R2), mul_lo(xc.y, R2), mul_hi(xc.w, R2), T0, T1);
        mma16816(acc[3], mul_lo(xd.x, R3), mul_hi(xd.z, R3), mul_lo(xd.y, R3), mul_hi(xd.w, R3), T2, T3);
        mp += STEPB; smask <<= 1;
    };
    auto putacc = [&](uint32_t* p) {
        p[0] = pack2(acc[0][0], acc[0][1]); p[32] = pack2(acc[0][2], acc[0][3]); p[64] = pack2(acc[2][0], acc[2][1]); p[96] = pack2(acc[2][2], acc[2][3]);
        p[256] = pack2(acc[1][0], acc[1][1]); p[288] = pack2(acc[1][2], acc[1][3]); p[320] = pack2(acc[3][0], acc[3][1]); p[352] = pack2(acc[3][2], acc[3][3]);
    };
    int ph = 0;
    auto phase_end = [&]() {
        az = *(const uint4*)(smem + SM_AZ + (ph + 1) * 512 + lane * 16);
        putacc(stash + (ph >> 1) * 512 + (ph & 1) * 128);
#pragma unroll
        for (int i = 0; i < 16; i++) acc[i / 4][i % 4] = 0.f;
        pbase += 256; mp = 0; smask = 1; ph++;
        dreg += tphase; dcur = dreg + tcur;
        WSTAMP(ph - 1);
    };
    uint32_t t0 = now;
    const bool special = w == 0 || w == PW;
#pragma unroll 1
    for (int it = S - 1; it > 0; it--) {
        if (special) {
            if (w == PW) {
                asm volatile("st.shared.u32 [%0+8], %1;" :: "r"(flg), "r"(now - dl + tcur) : "memory");
            } else {
                uint32_t g0, g1, b0, b1, cand;
                asm volatile("ld.volatile.shared.v2.u32 {%0,%1}, [%5+32]; ld.volatile.shared.v2.u32 {%2,%3}, [%5+16]; ld.volatile.shared.u32 %4, [%5+8];"
                             : "=r"(g0), "=r"(g1), "=r"(b0), "=r"(b1), "=r"(cand) : "r"(flg) : "memory");
                const unsigned long long tb = ((unsigned long long)b1 << 32) | b0;
                const unsigned long long dg = (((unsigned long long)g1 << 32) | g0) - tb;
                const uint32_t t1 = (dg < 30000 && (int)(g0 - t0) > 0) ? g0 : t0;
                cand -= PTOL;
                asm volatile("{.reg .pred p, q; setp.eq.u32 p, %2, 0; setp.gt.and.s32 q, %3, 0, p; st.shared.u32 [%4+4], %5;\n"
                             "@q red.max.relaxed.gpu.global.u64 [%0], %1; @p cp.async.cg.shared.global [%4+32], [%0], 16;}"
                             :: "l"(&gs->t0), "l"(tb + (cand - b0)), "r"(lane), "r"(cand - t1), "r"(flg), "r"(t1) : "memory");
            }
        }
        dcur += t0 - tcur; tcur = t0;
#pragma unroll
        for (int k = 0; k < DS; k++) {
            if (k == DS - 1) asm volatile("ld.volatile.shared.u32 %0, [%1+4];" : "=r"(t0) : "r"(flg));
            step(k * SLOTB, 0);
            if (mp == mend || now < dl) {
                if (mp == mend) phase_end();
                asm volatile("{.reg .pred p; .reg .u32 d;\n"
                             "PACE_LOOP: mov.u32 d, %%globaltimer_lo; sub.u32 d, %0, d; setp.lt.u32 p, d, 32768; @p nanosleep.u32 32; @p bra.uni PACE_LOOP;}"
                             :: "r"(dl) : "memory");
            }
        }
    }
    __syncwarp();
    step(0, 1); step(SLOTB, 2); step(2 * SLOTB, 3); step(3 * SLOTB, 4);
    WSTAMP(3);

    {
        putacc((uint32_t*)(smem + SM_RING + 2 * SLOTB + w * 2048 + 512) + lane);
        const int wg = w >> 2, w4 = w & 3;
        int nd[8];
#pragma unroll
        for (int j = 0; j < 8; j++) { const int l = wg * 8 + j; nd[j] = order[(t >> 1) ? 79 - l : l]; asm volatile("" : "+r"(nd[j])); }
        const bool odd = t & 1;
        uint2* ob = (uint2*)out + (size_t)n0 * 128 + w4 * 16 + g + (odd ? 8 : 0);
        asm volatile("cp.async.wait_all;" ::: "memory");
        mbar_wait(mbarW, 0);
        asm volatile("fence.proxy.async.shared::cta;" ::: "memory");
        TSTAMP(26);
        bar_sync(2 + wg, 128);
        if ((tid & 127) == 0) {
            const uint32_t ticket = atomicAdd((uint32_t*)flag + 12, 1);
            int spins = 0;
            while (flag[13] + LEAD < ticket && ++spins < (1 << 16)) {}
        }
        bar_sync(2 + wg, 128);
        TSTAMP(27);
        const uint64_t descA0 = (uint64_t)(((sb + SM_RING) & 0x3FFFF) >> 4) | ((uint64_t)1 << 16) | ((uint64_t)(1024 >> 4) << 32) | ((uint64_t)1 << 62);
        const uint64_t descB0 = (uint64_t)(((sb + SM_RING + SLOTB + wg * 8192) & 0x3FFFF) >> 4) | ((uint64_t)(128 >> 4) << 16) | ((uint64_t)(1024 >> 4) << 32);
        float d[2][32];
        asm volatile("wgmma.fence.sync.aligned;" ::: "memory");
#pragma unroll
        for (int mt = 0; mt < 2; mt++) {
#pragma unroll
            for (int ks = 0; ks < 8; ks++) {
                const uint64_t da = descA0 + (uint64_t)((ks * 2048 + mt * 16384) >> 4), db = descB0 + (uint64_t)(((ks & 3) * 256 + (ks >> 2) * SLOTB) >> 4);
                asm volatile("{.reg .pred p; setp.ne.b32 p, %34, 0;\n"
                    "wgmma.mma_async.sync.aligned.m64n64k16.f32.bf16.bf16 "
                    "{%0,%1,%2,%3,%4,%5,%6,%7,%8,%9,%10,%11,%12,%13,%14,%15,%16,%17,%18,%19,%20,%21,%22,%23,%24,%25,%26,%27,%28,%29,%30,%31}, %32, %33, p, 1, 1, 1, 1;}"
                    : "+f"(d[mt][0]), "+f"(d[mt][1]), "+f"(d[mt][2]), "+f"(d[mt][3]), "+f"(d[mt][4]), "+f"(d[mt][5]), "+f"(d[mt][6]), "+f"(d[mt][7]),
                      "+f"(d[mt][8]), "+f"(d[mt][9]), "+f"(d[mt][10]), "+f"(d[mt][11]), "+f"(d[mt][12]), "+f"(d[mt][13]), "+f"(d[mt][14]), "+f"(d[mt][15]),
                      "+f"(d[mt][16]), "+f"(d[mt][17]), "+f"(d[mt][18]), "+f"(d[mt][19]), "+f"(d[mt][20]), "+f"(d[mt][21]), "+f"(d[mt][22]), "+f"(d[mt][23]),
                      "+f"(d[mt][24]), "+f"(d[mt][25]), "+f"(d[mt][26]), "+f"(d[mt][27]), "+f"(d[mt][28]), "+f"(d[mt][29]), "+f"(d[mt][30]), "+f"(d[mt][31])
                    : "l"(da), "l"(db), "r"(ks));
            }
            asm volatile("wgmma.commit_group.sync.aligned;" ::: "memory");
            if (mt == RELAT - 1) asm volatile("{.reg .pred p; setp.eq.u32 p, %1, 0; @p red.shared.add.u32 [%0+52], 1;}" :: "r"(flg), "r"(tid & 127) : "memory");
        }
#pragma unroll
        for (int mt = 0; mt < 2; mt++) {
            if (mt == 0) asm volatile("wgmma.wait_group.sync.aligned 1;" ::: "memory");
            else asm volatile("wgmma.wait_group.sync.aligned 0;" ::: "memory");
            if (RELAT == 0 && mt == 0 && (tid & 127) == 0) atomicAdd((uint32_t*)flag + 13, 1);
            TSTAMP(23 + mt);
#pragma unroll
            for (int i = 0; i < 32; i++) asm volatile("" : "+f"(d[mt][i]) :: "memory");
#pragma unroll
            for (int j = 0; j < 8; j++) {
                const uint32_t v0 = pack2(d[mt][4 * j], d[mt][4 * j + 1]), v1 = pack2(d[mt][4 * j + 2], d[mt][4 * j + 3]);
                const uint32_t rv = __shfl_xor_sync(0xffffffff, odd ? v0 : v1, 1);
                if (nd[j] < nn) ob[nd[j] * 128 + mt * 64] = odd ? make_uint2(rv, v1) : make_uint2(v0, rv);
            }
        }
    }
    TSTAMP(8);
}

}

extern "C" void kernel_launch(void* const* d_in, const int* in_sizes, int n_in, void* d_out, int out_size) {
    (void)in_sizes; (void)n_in; (void)out_size;
    cudaFuncSetAttribute(tfn_kernel, cudaFuncAttributeMaxDynamicSharedMemorySize, SM_TOTAL);
    Scratch* gs = nullptr;
    cudaGetSymbolAddress((void**)&gs, g_scratch);
    cudaLaunchConfig_t cfg = {};
    cfg.gridDim = dim3(NB); cfg.blockDim = dim3(NT); cfg.dynamicSmemBytes = SM_TOTAL; cfg.stream = cudaStreamPerThread;
    cudaLaunchAttribute at[1];
    at[0].id = cudaLaunchAttributeCooperative; at[0].val.cooperative = 1;
    cfg.attrs = at; cfg.numAttrs = 1;
    cudaLaunchKernelEx(&cfg, tfn_kernel, (const unsigned char*)d_in[0], (const int4*)d_in[1], (const int4*)d_in[2],
                       (const uint4*)d_in[3], (const uint4*)d_in[4], (const uint16_t*)d_in[5], (const uint16_t*)d_in[6],
                       (const uint4*)d_in[7], (uint32_t*)d_out, gs);
}
```

```cpp
#include <cuda_runtime.h>
#include <cuda_bf16.h>
#include <stdint.h>

#define VOL
#define ORD 1
#define ABL 0
namespace {

constexpr int NN = 10000;
constexpr int NE = 320000;
constexpr int NB = 132;
constexpr int NW = 20;
constexpr int NT = NW * 32;
constexpr int CW = NW - 1;
constexpr int PW = 10;
constexpr int NPB = 76;
constexpr int CELL = 48;
constexpr int RCH = 2880;
constexpr int CAP = 19;
constexpr int DS = 4;
constexpr int STEPB = 160;
constexpr int NE4 = NE / 4;
constexpr int NPIECE = NB * 8;
constexpr int KB = 320, KN = 32 * KB;
constexpr uint32_t F_WRAP = 1;

constexpr int SLOTB = NW * 2048;
constexpr int SM_RING = 0;
constexpr int SM_META = SM_RING + DS * SLOTB;
constexpr int SM_AZ = SM_META + NW * CAP * STEPB;
constexpr int SM_MISC = SM_AZ + 2048;
constexpr int SM_TOTAL = SM_MISC + 2048;
constexpr int SM_STAGE = SM_RING;
constexpr int SM_HIST = SM_RING + 25600;
constexpr int SM_POS = SM_RING;
constexpr int SM_SMALL = SM_HIST + 13056;
constexpr int SM_LIST = SM_RING + SLOTB;
constexpr int SM_ROUT = SM_RING + 2 * SLOTB;
constexpr int SM_RECS = SM_RING + 3 * SLOTB;
constexpr int SM_RAWY = SM_META;
constexpr int SM_RAWE = SM_RAWY + 608 * 32;
constexpr int SM_KEYS = SM_RAWE + 608 * 32;
static_assert(SM_TOTAL <= 232448 && SM_KEYS + NPIECE * 16 <= SM_AZ, "smem");
static_assert(SM_RECS + NB * CELL * 16 + 16 <= SM_AZ && SM_KEYS + NPIECE * 16 <= SM_RECS + NB * CELL * 16 && SM_SMALL + 1152 <= SLOTB && DS == 4, "smem");

struct Scratch {
    uint4 keys[NB * NPIECE];
    uint4 recs[NB * RCH];
    uint4 stash[NB * NW * 256];
    unsigned bar[4];
    unsigned long long t0, pad;
};
__device__ Scratch g_scratch;
#define TSTAMP(i)
#define TSTAMPC(i)
#define WSTAMP(i)

__device__ __forceinline__ void mma16816(float* d, uint32_t a0, uint32_t a1, uint32_t a2, uint32_t a3, uint32_t b0, uint32_t b1) {
    asm VOL("mma.sync.aligned.m16n8k16.row.col.f32.bf16.bf16.f32 {%0,%1,%2,%3}, {%4,%5,%6,%7}, {%8,%9}, {%0,%1,%2,%3};"
        : "+f"(d[0]), "+f"(d[1]), "+f"(d[2]), "+f"(d[3]) : "r"(a0), "r"(a1), "r"(a2), "r"(a3), "r"(b0), "r"(b1));
}
__device__ __forceinline__ void mma1688z(float* d, uint32_t a0, uint32_t a1, uint32_t b0) {
    asm VOL("mma.sync.aligned.m16n8k8.row.col.f32.bf16.bf16.f32 {%0,%1,%2,%3}, {%4,%5}, {%6}, {%7,%7,%7,%7};"
        : "=f"(d[0]), "=f"(d[1]), "=f"(d[2]), "=f"(d[3]) : "r"(a0), "r"(a1), "r"(b0), "f"(0.f));
}
__device__ __forceinline__ uint32_t pack2(float lo, float hi) {
    uint32_t r; asm VOL("cvt.rn.bf16x2.f32 %0, %1, %2;" : "=r"(r) : "f"(hi), "f"(lo)); return r;
}
__device__ __forceinline__ float silu_h(float h) {
    float t; asm VOL("tanh.approx.f32 %0, %1;" : "=f"(t) : "f"(h)); return fmaf(h, t, h);
}
__device__ __forceinline__ uint32_t mul_lo(uint32_t v, uint32_t r) {
    __nv_bfloat162 a = *(__nv_bfloat162*)&v, b = *(__nv_bfloat162*)&r; __nv_bfloat162 c = __hmul2(a, __low2bfloat162(b)); return *(uint32_t*)&c;
}
__device__ __forceinline__ uint32_t mul_hi(uint32_t v, uint32_t r) {
    __nv_bfloat162 a = *(__nv_bfloat162*)&v, b = *(__nv_bfloat162*)&r; __nv_bfloat162 c = __hmul2(a, __high2bfloat162(b)); return *(uint32_t*)&c;
}
__device__ __forceinline__ uint2 lds64(uint32_t a) {
    uint2 r; asm volatile("ld.shared.v2.u32 {%0,%1}, [%2];" : "=r"(r.x), "=r"(r.y) : "r"(a)); return r;
}
__device__ __forceinline__ uint4 lds128(uint32_t a) {
    uint4 r; asm volatile("ld.shared.v4.u32 {%0,%1,%2,%3}, [%4];" : "=r"(r.x), "=r"(r.y), "=r"(r.z), "=r"(r.w) : "r"(a) : "memory"); return r;
}
__device__ __forceinline__ void bar_sync(int id, int n) { asm volatile("bar.sync %0, %1;" :: "r"(id), "r"(n) : "memory"); }
__device__ __forceinline__ void bar_arrive(int id, int n) { asm volatile("bar.arrive %0, %1;" :: "r"(id), "r"(n) : "memory"); }
__device__ __forceinline__ void mbar_wait(uint32_t bar, uint32_t ph) {
    uint32_t done; int spins = 0;
    do {
        asm volatile("{.reg .pred p; mbarrier.try_wait.parity.shared.b64 p, [%1], %2; selp.u32 %0,1,0,p;}" : "=r"(done) : "r"(bar), "r"(ph) : "memory");
    } while (!done && ++spins < (1 << 22));
}
__device__ __forceinline__ unsigned gbar_read(const unsigned* ctr) {
    unsigned v; asm volatile("ld.relaxed.gpu.global.u32 %0, [%1];" : "=r"(v) : "l"(ctr) : "memory");
    return v;
}
__device__ __forceinline__ void gbar_arrive(unsigned* ctr) {
    asm volatile("red.add.release.gpu.global.u32 [%0], 1;" :: "l"(ctr) : "memory");
}
__device__ __forceinline__ bool gbar_wait(const unsigned* ctr, unsigned target) {
    unsigned v; int spins = 0;
    do { asm volatile("ld.acquire.gpu.global.u32 %0, [%1];" : "=r"(v) : "l"(ctr) : "memory"); } while ((int)(v - target) < 0 && ++spins < (1 << 22));
    return (int)(v - target) >= 0;
}
__device__ __forceinline__ int chunk_start4(int c) { return (c * NE4) / NB; }
__device__ __forceinline__ float bf2f(uint32_t h) { return __uint_as_float(h << 16); }

__device__ __noinline__ void slow_path(unsigned char* smem, int n0, int nn, const uint16_t* x, const int* src, const int* dst,
                                       const uint16_t* Y, const uint16_t* ef, const uint16_t* w_rad, const uint16_t* cg,
                                       const uint16_t* w_mix, __nv_bfloat16* out) {
    float* agg = (float*)smem;
    const int tid = threadIdx.x, lane = tid & 31, w = tid >> 5;
    bar_sync(1, NT);
    for (int i = tid; i < NPB * 512; i += NT) agg[i] = 0.f;
    bar_sync(1, NT);
    for (int e0 = w * 32; e0 < NE; e0 += NT) {
        int dl = dst[e0 + lane] - n0;
        unsigned m = __ballot_sync(0xffffffff, dl >= 0 && dl < nn);
        while (m) {
            int l = __ffs(m) - 1; m &= m - 1;
            int e = e0 + l, d = __shfl_sync(0xffffffff, dl, l), s = src[e];
            float T[16];
            for (int i = 0; i < 4; i++) for (int o = 0; o < 4; o++) {
                float a = 0.f;
                for (int f = 0; f < 4; f++) a += bf2f(Y[e * 4 + f]) * bf2f(cg[i * 16 + f * 4 + o]);
                T[i * 4 + o] = a;
            }
            for (int k = 0; k < 4; k++) {
                int c = lane + 32 * k;
                float z = 0.f;
                for (int j = 0; j < 4; j++) z += bf2f(ef[e * 4 + j]) * bf2f(w_rad[j * 128 + c]);
                float R = z / (1.f + __expf(-z));
                for (int o = 0; o < 4; o++) {
                    float a = 0.f;
                    for (int i = 0; i < 4; i++) a += bf2f(x[(size_t)s * 512 + c * 4 + i]) * T[i * 4 + o];
                    atomicAdd(&agg[d * 512 + c * 4 + o], R * a);
                }
            }
        }
    }
    bar_sync(1, NT);
    for (int i = tid; i < nn * 512; i += NT) {
        int n = i >> 9, d = (i >> 2) & 127, o = i & 3;
        float a = 0.f;
        for (int c = 0; c < 128; c++) a += agg[n * 512 + c * 4 + o] * bf2f(w_mix[c * 128 + d]);
        out[(size_t)(n0 + n) * 512 + (i & 511)] = __float2bfloat16(a);
    }
}

#define PACE 24000
#define YDELAY 300
#define TP 0
#define BFENCE 0
#define EPI 2
#define LEAD 0
#define RELAT 2
#define POFF 1700
#define RELAY 7
#define PSLEEP 32
#define PTOL0 300
#define PTOL 800
__global__ void __launch_bounds__(NT, 1)
tfn_kernel(const unsigned char* __restrict__ x, const int4* __restrict__ src4, const int4* __restrict__ dst4,
           const uint4* __restrict__ Y, const uint4* __restrict__ ef, const uint16_t* __restrict__ w_rad,
           const uint16_t* __restrict__ cg, const uint4* __restrict__ w_mix, uint32_t* __restrict__ out, Scratch* __restrict__ gs) {
    extern __shared__ __align__(1024) unsigned char smem[];
    const uint32_t sb = (uint32_t)__cvta_generic_to_shared(smem);
    const int b = blockIdx.x, tid = threadIdx.x, lane = tid & 31, g = lane >> 2, t = lane & 3;
    const int w = __shfl_sync(0xffffffff, tid >> 5, 0);
    uint32_t* stage = (uint32_t*)(smem + SM_STAGE);
    uint32_t* hist = (uint32_t*)(smem + SM_HIST);
    uint32_t* cnt = (uint32_t*)(smem + SM_MISC);
    uint32_t* deg = cnt + 136;
    uint32_t* order = deg + 104;
    uint32_t* cnt2 = order + 80;
    volatile uint32_t* flag = cnt2 + 136;
    const uint32_t mbarK = sb + SM_MISC + 1920, mbarR = mbarK + 8, mbarW = mbarK + 16;
    const int n0 = b * NPB, nn = min(NPB, NN - n0);
    TSTAMP(0);

    const int c0 = chunk_start4(b), c1 = chunk_start4(b + 1);
    const bool has4 = c0 + tid < c1;
    int4 d4 = make_int4(0, 0, 0, 0), s4 = d4;
    if (has4) { d4 = __ldg(dst4 + c0 + tid); s4 = __ldg(src4 + c0 + tid); }
    unsigned tgt = 0;
    if (tid == NT - 1) {
        tgt = gbar_read(&gs->bar[0]);
        asm volatile("mbarrier.init.shared.b64 [%0], 1;" :: "r"(mbarK));
        asm volatile("mbarrier.init.shared.b64 [%0], 1;" :: "r"(mbarR));
        asm volatile("mbarrier.init.shared.b64 [%0], 512;" :: "r"(mbarW));
        asm volatile("fence.mbarrier_init.release.cluster;" ::: "memory");
        flag[0] = 0; flag[12] = 0; flag[13] = 0; flag[15] = 0;
    }
    if (w == CW) {
        asm volatile("cp.async.cg.shared.global [%0], [%1], 16;" :: "r"(sb + SM_SMALL + lane * 16), "l"(w_rad + lane * 8) : "memory");
        asm volatile("cp.async.cg.shared.global [%0], [%1], 16;" :: "r"(sb + SM_SMALL + 512 + lane * 16), "l"(w_rad + 256 + lane * 8) : "memory");
        if (lane < 8) asm volatile("cp.async.cg.shared.global [%0], [%1], 16;" :: "r"(sb + SM_SMALL + 1024 + lane * 16), "l"(cg + lane * 8) : "memory");
    }
    ((uint4*)hist)[tid] = make_uint4(0, 0, 0, 0);
    {
        const uint32_t dk = (80 + b % 22) * KN + (b & 31) * KB;
#pragma unroll
        for (int j = 0; j < 3; j++) if (tid + j * NT < NB * CELL / 4) ((uint4*)stage)[tid + j * NT] = make_uint4(dk, dk, dk, dk);
    }
    if (tid < 136) cnt[tid] = 0;
    if (tid == 0) { *(uint4*)(smem + SM_MISC + 1824 + 32) = make_uint4(0, 0, 0, 0); *(uint4*)(smem + SM_RECS + NB * CELL * 16) = make_uint4(0, 0, 0, 0); }
    if (tid < 80) { deg[tid] = 127 - tid; order[tid] = tid; }
    __syncthreads();
    TSTAMP(9);
    if (tid == 64) {
        if (YDELAY) __nanosleep(YDELAY);
        asm volatile("mbarrier.arrive.expect_tx.shared.b64 _, [%0], %1;" :: "r"(mbarR), "r"((c1 - c0) * 64) : "memory");
        asm volatile("cp.async.bulk.shared::cluster.global.mbarrier::complete_tx::bytes [%0], [%1], %2, [%3];"
                     :: "r"(sb + SM_RAWY), "l"(Y + 2 * c0), "r"((c1 - c0) * 32), "r"(mbarR) : "memory");
        asm volatile("cp.async.bulk.shared::cluster.global.mbarrier::complete_tx::bytes [%0], [%1], %2, [%3];"
                     :: "r"(sb + SM_RAWE), "l"(ef + 2 * c0), "r"((c1 - c0) * 32), "r"(mbarR) : "memory");
    }

    uint32_t bin[4] = {0, 0, 0, 0}, slot[4] = {0, 0, 0, 0};
    if (has4) {
        const uint32_t dd[4] = {(uint32_t)d4.x, (uint32_t)d4.y, (uint32_t)d4.z, (uint32_t)d4.w}, ss[4] = {(uint32_t)s4.x, (uint32_t)s4.y, (uint32_t)s4.z, (uint32_t)s4.w};
#pragma unroll
        for (int k = 0; k < 4; k++) { bin[k] = dd[k] / NPB; slot[k] = atomicAdd(&cnt[bin[k]], 1); }
#pragma unroll
        for (int k = 0; k < 4; k++) stage[bin[k] * CELL + min(slot[k], CELL - 1)] = (dd[k] - bin[k] * NPB) * KN + ss[k];
    }
    if (w == CW) {
        if (tid == NT - 1) { tgt = tgt / NB + 1; flag[14] = (tgt & 1) << 31; tgt *= NB; }
        asm volatile("cp.async.wait_all;" ::: "memory");
    }
    bar_sync(1, NT);
    TSTAMP(1);
    const uint32_t tag = flag[14];
#pragma unroll
    for (int j = 0; j < 2; j++) {
        const int i = tid + j * NT;
        if (i < NPIECE) {
            const uint2 sa = *(const uint2*)(stage + i * 6), sc = *(const uint2*)(stage + i * 6 + 2);
            uint2 se = *(const uint2*)(stage + i * 6 + 4);
            const uint32_t cf = cnt[i >> 3], cn = min(cf, 63u);
            if ((i & 7) == 7) {
                const uint32_t al = cf > CELL - 8 ? 7 : 0;
                se.y = (atomicAdd((uint32_t*)flag + 15, cf + al) + al) & ~al;
                cnt2[i >> 3] = se.y;
            }
            asm volatile("{.reg .b64 lo, hi; mov.b64 lo, {%1,%2}; mov.b64 hi, {%3,%4}; st.relaxed.gpu.global.v2.b64 [%0], {lo, hi};}"
                         :: "l"(gs->keys + ((i >> 3) * NB + b) * 8 + ((i ^ b) & 7)),
                            "r"(sa.x | (se.x << 20)), "r"(sa.y | ((se.x >> 12) << 20) | ((cn & 7) << 28) | tag),
                            "r"(sc.x | (se.y << 20)), "r"(sc.y | ((se.y >> 12) << 20) | ((cn >> 3) << 28) | tag) : "memory");
        }
    }
    bar_sync(1, NT);
    if (tid == NT - 1) {
        TSTAMPC(10);
        asm volatile("red.add.relaxed.gpu.global.u32 [%0], 1;" :: "l"(&gs->bar[0]) : "memory");
    }
    uint32_t at[4];
    {
        const int o = g & 3, f = 2 * (t & 1);
#pragma unroll
        for (int i = 0; i < 4; i++) {
            const uint16_t* cp = (const uint16_t*)(smem + SM_SMALL + 1024) + i * 16 + f * 4 + o;
            at[i] = (t >> 1) == (g >> 2) ? cp[0] | ((uint32_t)cp[4] << 16) : 0;
        }
    }

    uint32_t key[2][6], ha[2][6], rk[2][6], kidx[2], ka[2];
    int nk[2];
#pragma unroll
    for (int j = 0; j < 2; j++) {
        const int i0 = j ? 2 * 608 - 1 - tid : tid, i = min(i0, NPIECE - 1), r = i / NB, c = i - r * NB;
        ka[j] = sb + SM_KEYS + (c * 8 + ((r ^ c) & 7)) * 16;
        kidx[j] = (c * CELL + r * 6) << 17;
        nk[j] = i0 < NPIECE && w < CW ? -6 * r : -1000;
    }
    asm volatile("" : "+r"(at[0]), "+r"(at[1]), "+r"(at[2]), "+r"(at[3]), "+r"(ka[0]), "+r"(ka[1]), "+r"(kidx[0]), "+r"(kidx[1]), "+r"(nk[0]), "+r"(nk[1]));
    if (w == CW) {
        if (tid == NT - 1) {
            asm volatile("mbarrier.arrive.expect_tx.shared.b64 _, [%0], %1;" :: "r"(mbarK), "r"(NPIECE * 16) : "memory");
            gbar_wait(&gs->bar[0], tgt);
            TSTAMPC(13);
            asm volatile("fence.proxy.async.global;" ::: "memory");
            asm volatile("cp.async.bulk.shared::cluster.global.mbarrier::complete_tx::bytes [%0], [%1], %2, [%3];"
                         :: "r"(sb + SM_KEYS), "l"(gs->keys + b * NPIECE), "r"(NPIECE * 16), "r"(mbarK) : "memory");
        }
        __syncwarp();
        bar_sync(7, NT);
        if (tid == NT - 1) {
            TSTAMPC(11);
            asm volatile("cp.async.bulk.global.shared::cta.bulk_group [%0], [%1], %2;"
                         :: "l"(gs->recs + b * RCH), "r"(sb + SM_ROUT), "r"(((flag[15] + 1) & ~1u) * 16) : "memory");
            asm volatile("cp.async.bulk.commit_group; cp.async.bulk.wait_group 0;" ::: "memory");
            TSTAMPC(14);
            asm volatile("red.add.relaxed.gpu.global.u32 [%0], 1;" :: "l"(&gs->bar[1]) : "memory");
            TSTAMPC(15);
            if (!gbar_wait(&gs->bar[1], tgt)) *flag = 1;
            TSTAMPC(17);
        }
    } else {
        if (w < 8) {
            const uint32_t* wp = (const uint32_t*)(smem + SM_SMALL) + (t & 1) * 128 + 8 * w + g;
            const uint32_t wr0 = t < 2 ? wp[0] : 0, wr1 = t < 2 ? wp[64] : 0;
            *(uint2*)(smem + SM_AZ + (w >> 1) * 512 + lane * 16 + (w & 1) * 8) =
                make_uint2(pack2(0.5f * bf2f(wr0 & 0xFFFF), 0.5f * bf2f(wr1 & 0xFFFF)), pack2(0.5f * bf2f(wr0 >> 16), 0.5f * bf2f(wr1 >> 16)));
        }
        const bool sw = g & 1;
        uint32_t rp[4];
#pragma unroll
        for (int k = 0; k < 4; k++) rp[k] = cnt2[bin[k]] + slot[k];
        uint4* ro = (uint4*)(smem + SM_ROUT);
        uint4 *p0 = ro + (sw ? rp[2] : rp[0]), *p1 = ro + (sw ? rp[3] : rp[1]), *p2 = ro + (sw ? rp[0] : rp[2]), *p3 = ro + (sw ? rp[1] : rp[3]);
        const uint32_t ya = sb + SM_RAWY + tid * 32 + (sw ? 16 : 0);
        mbar_wait(mbarR, 0);
        TSTAMP(18);
        if (has4) {
            const uint4 y0 = lds128(ya), e0 = lds128(ya + (SM_RAWE - SM_RAWY)), y1 = lds128(ya ^ 16), e1 = lds128((ya ^ 16) + (SM_RAWE - SM_RAWY));
            *p0 = make_uint4(y0.x, e0.x, y0.y, e0.y); *p1 = make_uint4(y0.z, e0.z, y0.w, e0.w);
            *p2 = make_uint4(y1.x, e1.x, y1.y, e1.y); *p3 = make_uint4(y1.z, e1.z, y1.w, e1.w);
        }
        asm volatile("fence.proxy.async.shared::cta;" ::: "memory");
        bar_arrive(7, NT);
    }
    __syncwarp();
    TSTAMP(2);

    if (w < CW) {
        mbar_wait(mbarK, 0);
        TSTAMP(3);
        uint4 v[2] = {lds128(ka[0]), lds128(ka[1])};
#pragma unroll
        for (int j = 0; j < 2; j++) {
            int spins = 0;
            while ((int)((v[j].y ^ tag) | (v[j].w ^ tag)) < 0) {
                asm volatile("{.reg .b64 lo, hi; ld.relaxed.gpu.global.v2.b64 {lo, hi}, [%4]; mov.b64 {%0,%1}, lo; mov.b64 {%2,%3}, hi;}"
                             : "=r"(v[j].x), "=r"(v[j].y), "=r"(v[j].z), "=r"(v[j].w) : "l"((const unsigned char*)(gs->keys + b * NPIECE) + (ka[j] - sb - SM_KEYS)) : "memory");
                if (++spins > (1 << 20)) { *flag = 1; break; }
            }
            const uint32_t hc = ((v[j].y >> 28) & 7) | ((v[j].w >> 25) & 0x38);
            if (j == 1 && nk[j] == -42) {
                cnt[kidx[j] / (CELL << 17)] = hc | ((v[j].z >> 20) << 8);
                v[j].w |= ((80 * KN) >> 12) << 20;
            }
            if (hc > CELL - 1) *flag = 1;
            nk[j] += hc;
            if (nk[j] > 0) {
                key[j][0] = v[j].x & 0xFFFFF; key[j][1] = v[j].y & 0xFFFFF; key[j][2] = v[j].z & 0xFFFFF; key[j][3] = v[j].w & 0xFFFFF;
                key[j][4] = (v[j].x >> 20) | ((v[j].y >> 8) & 0xFF000); key[j][5] = (v[j].z >> 20) | ((v[j].w >> 8) & 0xFF000);
#pragma unroll
                for (int u = 0; u < 6; u++) {
                    ha[j][u] = __umulhi(key[j][u], 0xFFFFFFFFu / KB + 1);
                    rk[j][u] = atomicAdd(&hist[ha[j][u]], 1);
                    atomicAdd(&deg[ha[j][u] >> 5], 128);
                }
            }
        }
        bar_sync(9, NT - 32);
        TSTAMP(20);
#pragma unroll
        for (int j = 0; j < 2; j++) kidx[j] += ((cnt[kidx[j] / (CELL << 17)] >> 8) & 7) << 17;
        const int n = tid >> 3, sub = tid & 7;
        const uint32_t me = deg[n];
        int r = 0;
#pragma unroll
        for (int k = 0; k < 5; k++) { const uint2 dd = *(const uint2*)(deg + sub * 10 + 2 * k); r += (dd.x > me) + (dd.y > me); }
        r += __shfl_xor_sync(0xffffffff, r, 1); r += __shfl_xor_sync(0xffffffff, r, 2); r += __shfl_xor_sync(0xffffffff, r, 4);
        if (sub == 0) order[r] = n;
    }
    if (w < CW) {
        bar_sync(9, NT - 32);
        TSTAMP(22);
#pragma unroll 1
        for (int v = w; v < NW; v += (w == 1 ? CW - 1 : NW)) {
            const uint2 na = *(const uint2*)(order + 2 * v), nb = *(const uint2*)(order + 78 - 2 * v);
            const uint32_t ia0 = na.x * 32 + lane, ib0 = nb.y * 32 + lane, ia1 = na.y * 32 + lane, ib1 = nb.x * 32 + lane;
            const uint32_t ca = hist[ia0] + (hist[ia1] << 16), cab = ca + hist[ib0] + (hist[ib1] << 16);
            uint32_t inc = cab;
#pragma unroll
            for (int o = 1; o < 32; o <<= 1)
                asm volatile("{.reg .pred p; .reg .u32 u; shfl.sync.up.b32 u|p, %0, %1, 0, 0xffffffff; @p add.u32 %0, %0, u;}" : "+r"(inc) : "r"(o));
            const uint32_t ea = inc - cab, eb = ea + ca, base = sb + SM_LIST + v * 2048;
            uint2* pos = (uint2*)(smem + SM_POS);
            pos[ia0] = make_uint2(base + (ea & 0xFFFF) * 8, na.x * (0u - 4 * KN));
            pos[ib0] = make_uint2(base + (eb & 0xFFFF) * 8, nb.y * (0u - 4 * KN) + 0x10000);
            pos[ia1] = make_uint2(base + 4 + (ea >> 16) * 8, na.y * (0u - 4 * KN));
            pos[ib1] = make_uint2(base + 4 + (eb >> 16) * 8, nb.x * (0u - 4 * KN) + 0x10000);
            if (lane == 31) { cnt2[v] = inc; if (max(inc & 0xFFFF, inc >> 16) > 4 * CAP) *flag = 1; }
        }
        bar_sync(9, NT - 32);
        TSTAMP(21);
        const uint32_t over = *flag;
#pragma unroll
        for (int j = 0; j < 2; j++) {
            if (nk[j] > 0) {
                uint2 h[6];
#pragma unroll
                for (int u = 0; u < 6; u++) h[u] = lds64(sb + SM_POS + ha[j][u] * 8);
                if (over) nk[j] = 0;
#pragma unroll
                for (int u = 0; u < 6; u++)
                    asm volatile("{.reg .pred p; setp.gt.s32 p, %2, %3; @p st.shared.u32 [%0], %1;}"
                                 :: "r"(h[u].x + rk[j][u] * 8), "r"(key[j][u] * 4 + h[u].y + (kidx[j] + (u << 17))), "r"(nk[j]), "r"(u) : "memory");
            }
        }
    }
    bar_sync(1, NT);
    TSTAMP(4);
    if (*flag) {
        slow_path(smem, n0, nn, (const uint16_t*)x, (const int*)src4, (const int*)dst4, (const uint16_t*)Y, (const uint16_t*)ef, w_rad, cg,
                  (const uint16_t*)w_mix, (__nv_bfloat16*)out);
        return;
    }
    {
        const uint32_t ci = cnt[min(w + NW * lane, NB)];
        const uint4* gp = gs->recs + w * RCH + lane;
        const uint32_t sp = sb + SM_RECS + (w * CELL + lane) * 16;
#pragma unroll
        for (int j = 0; j < 7; j++) {
            const uint32_t cj = __shfl_sync(0xffffffff, ci, j);
            asm volatile("{.reg .pred p; setp.lt.u32 p, %2, %3; @p cp.async.cg.shared.global [%0], [%1], 16;}"
                         :: "r"(sp + j * (NW * CELL * 16) + ((cj >> 4) & 0x70)), "l"(gp + j * (NW * RCH) + (cj >> 8)), "r"(lane), "r"(cj & 0xFF) : "memory");
        }
        if (__any_sync(0xffffffff, (ci & 0xFF) > 32)) {
#pragma unroll 1
            for (int j = 0; j < 7; j++) {
                const uint32_t cj = __shfl_sync(0xffffffff, ci, j);
                if (lane + 32 < (cj & 0xFF))
                    asm volatile("cp.async.cg.shared.global [%0], [%1], 16;"
                                 :: "r"(sp + j * (NW * CELL * 16) + ((cj >> 4) & 0x70) + 512), "l"(gp + j * (NW * RCH) + (cj >> 8) + 32) : "memory");
            }
        }
        asm volatile("cp.async.commit_group;" ::: "memory");
    }
    const uint32_t len2 = cnt2[w];
    const int S = __shfl_sync(0xffffffff, max((int)(max(len2 & 0xFFFF, len2 >> 16) + 3) >> 2, DS + 1), 0);
    const int mylen = (lane & 1) ? len2 >> 16 : len2 & 0xFFFF;
    constexpr int NRAW = (CAP + 3) / 4;
    uint32_t bits0 = 0, raw[NRAW];
    unsigned char* meta = smem + SM_META + w * (CAP * STEPB);
#pragma unroll
    for (int k = 0; k < NRAW; k++) raw[k] = mylen ? ((uint32_t*)(smem + SM_LIST + w * 2048))[min(k * 16 + (lane >> 1), mylen - 1) * 2 + (lane & 1)] : 4 * n0;
    const uint32_t sv0 = raw[0] & 0xFFFF;
    const int q = lane >> 3, c = lane & 7;
    const uint32_t ring0 = sb + SM_RING + w * 2048;
    uint32_t wdst = ring0 + q * 128 + ((c + 2 * q) & 7) * 16;
    uint32_t rsrc = ring0 + t * 128 + ((g + 2 * t) & 7) * 16;
    uint32_t recl = sb + SM_META + w * (CAP * STEPB) + g * 16 + (t & 1) * 8, srcl = sb + SM_META + w * (CAP * STEPB) + 128 + q * 8;
    uint32_t flg = sb + SM_MISC + (136 + 104 + 80 + 136) * 4;
    asm volatile("" : "+r"(wdst), "+r"(rsrc), "+r"(recl), "+r"(srcl), "+r"(flg));
    const unsigned char* pbase = x + c * 16;
    auto cpa2 = [&](uint32_t dstp, uint32_t sv) {
        asm volatile("cp.async.cg.shared.global [%0], [%1], 16; cp.async.cg.shared.global [%0+1024], [%1+128], 16;"
                     :: "r"(dstp), "l"(pbase + (size_t)sv * 256) : "memory");
    };
    auto fill = [&](int i) {
        cpa2(wdst + i * SLOTB, __shfl_sync(0xffffffff, sv0, 8 * i + 2 * q)); cpa2(wdst + i * SLOTB + 512, __shfl_sync(0xffffffff, sv0, 8 * i + 2 * q + 1));
        asm volatile("cp.async.commit_group;" ::: "memory");
    };
    fill(0);
    TSTAMP(5);
    if (w == 0) {
        unsigned long long tbase;
        asm volatile("mov.u64 %0, %%globaltimer;" : "=l"(tbase));
        tbase += POFF;
        flag[1] = (uint32_t)tbase; flag[4] = (uint32_t)tbase; flag[5] = (uint32_t)(tbase >> 32);
        if (lane == 0) {
            asm volatile("red.max.relaxed.gpu.global.u64 [%0], %1;" :: "l"(&gs->t0), "l"(tbase) : "memory");
            if (b < 128) asm volatile("cp.async.bulk.prefetch.L2.global [%0], 256;" :: "l"(w_mix + b * 16));
        }
    }
    uint32_t ra[NRAW];
#pragma unroll
    for (int k = 0; k < NRAW; k++) {
        const uint32_t m = (__ballot_sync(0xffffffff, raw[k] & 0x10000) >> g) & 0x01010101u;
        bits0 |= ((m * 0x10204080u) >> 28) << (4 * k);
        ra[k] = sb + SM_RECS + (k * 16 + (lane >> 1) < mylen ? raw[k] >> 17 : NB * CELL) * 16;
    }
    if (t < 2) bits0 = ~bits0;
    fill(1);
    asm volatile("cp.async.wait_group 2;" ::: "memory");
    bar_sync(1, NT);
    TSTAMP(19);
    {
        uint4 rv[NRAW];
#pragma unroll
        for (int k = 0; k < NRAW - 1; k++) rv[k] = lds128(ra[k]);
        if ((NRAW - 1) * 4 < S) rv[NRAW - 1] = lds128(ra[NRAW - 1]);
        if (tid == 0) asm volatile("cp.async.cg.shared.global [%0], [%1], 16;" :: "r"(sb + SM_MISC + 1824 + 32), "l"(&gs->t0) : "memory");
        fill(2);
        bar_sync(1, NT);
        TSTAMP(12);
        unsigned char* mr = meta + (q - 1) * STEPB + c * 16;
        unsigned char* ms = meta + (q - DS - 1) * STEPB + 128 + c * 4;
#pragma unroll
        for (int k = 0; k < NRAW; k++) {
            if (k == 0) {
                *(uint4*)(mr + (q == 0 ? S * STEPB : 0)) = rv[k];
                *(uint32_t*)(ms + S * STEPB) = sv0 + F_WRAP;
            } else if (k * 4 + q < S) {
                *(uint4*)(mr + k * 4 * STEPB) = rv[k];
                *(uint32_t*)(ms + k * 4 * STEPB + (k == 1 && q == 0 ? S * STEPB : 0)) = raw[k] & 0xFFFF;
            }
        }
    }
    __syncwarp();
    const uint32_t tphase = PACE / 4;
    uint32_t dreg;
    {
        const int st = lane == 0 ? S - 1 : min(lane, S) - 1;
        const uint4 u0 = *(const uint4*)(meta + st * STEPB + 128), u1 = *(const uint4*)(meta + st * STEPB + 144);
        int pos = (u0.x + u0.y + u0.z + u0.w + u1.x + u1.y + u1.z + u1.w) >> 5;
        pos += ((u0.x & F_WRAP) ? NN : 0) + (lane == S ? NN : 0) - NN * (2 * DS + 1) / 32;
        dreg = pos * (int)tphase / NN;
    }
    fill(3);
    TSTAMP(6);

    uint32_t* stash = (uint32_t*)(gs->stash + (b * NW + w) * 256) + lane;
    float acc[4][4];
#pragma unroll
    for (int i = 0; i < 16; i++) acc[i / 4][i % 4] = 0.f;
    uint4 az = *(const uint4*)(smem + SM_AZ + lane * 16);
    uint32_t dcur = dreg, dl = 0, now = flag[1], tcur = 0;
    uint32_t mp = 0, smask = 1;
    const uint32_t mend = S * STEPB;
    uint2 r = lds64(mend - STEPB + recl), s0 = lds64(mend - STEPB + srcl);
    auto step = [&](const uint32_t off, const int mode) {
        auto tick = [&]() { if (mode == 0) { unsigned long long n64; asm volatile("mov.u64 %0, %%globaltimer;" : "=l"(n64)); now = (uint32_t)n64; } };
        if (TP == 0) tick();
        const uint2 rc = r, sc = s0;
        if (ORD & 1) { if (mode != 4) r = lds64(mp + recl); if (mode == 0) s0 = lds64(mp + srcl); }
        asm volatile("cp.async.wait_group %0;" :: "n"(DS - 1) : "memory");
        const uint4 xa = lds128(rsrc + off), xb = lds128(rsrc + off + 512), xc = lds128(rsrc + off + 1024), xd = lds128(rsrc + off + 1536);
        if (!(ORD & 1) && !(ORD & 4)) { if (mode != 4) r = lds64(mp + recl); if (mode == 0) s0 = lds64(mp + srcl); }
        if (mode == 0) {
            if (ORD & 2) {
                asm volatile("shfl.sync.idx.b32 %0, %1, 1, 31, 0xffffffff; shfl.sync.down.b32 %1, %1, 1, 31, 0xffffffff;\n"
                             "cp.async.cg.shared.global [%2], [%3], 16; cp.async.cg.shared.global [%2+512], [%4], 16;\n"
                             "cp.async.cg.shared.global [%2+1024], [%3+128], 16; cp.async.cg.shared.global [%2+1536], [%4+128], 16;"
                             : "=&r"(dl), "+r"(dcur) : "r"(wdst + off), "l"(pbase + (size_t)sc.x * 256), "l"(pbase + (size_t)sc.y * 256) : "memory");
            } else {
                dl = __shfl_sync(0xffffffff, dcur, 1); dcur = __shfl_down_sync(0xffffffff, dcur, 1);
                cpa2(wdst + off, sc.x); cpa2(wdst + off + 512, sc.y);
            }
        }
        if (mode == 1 && w < 16) {
#pragma unroll
            for (int j = 0; j < 4; j++) {
                const int kk = 4 * j + q, ch = 16 * (w & 7) + 2 * (kk & 7) + (kk >> 3);
                asm volatile("cp.async.cg.shared.global [%0], [%1], 16;" :: "r"(ring0 + kk * 128 + ((c ^ (kk & 7)) << 4)), "l"(w_mix + ch * 16 + (w >> 3) * 8 + c) : "memory");
            }
            asm volatile("cp.async.mbarrier.arrive.noinc.shared.b64 [%0];" :: "r"(mbarW) : "memory");
        }
        if (mode == 2 || mode == 3) {
#pragma unroll
            for (int j = 0; j < 4; j += mode - 1)
                asm volatile("cp.async.cg.shared.global [%0], [%1], 16;" :: "r"(ring0 + off + j * 512 + lane * 16), "l"(stash + (mode - 2) * 512 + j * 128 + lane * 3) : "memory");
        }
        asm volatile("cp.async.commit_group;" ::: "memory");
        if (ORD & 4) { if (mode != 4) r = lds64(mp + recl); if (mode == 0) s0 = lds64(mp + srcl); }
        float z[4], y[4], t1[4], t2[4];
        mma1688z(z, az.x, az.y, rc.y);
        mma1688z(y, az.z, az.w, rc.y);
        uint32_t bt;
        asm("{.reg .pred p; .reg .b32 m; and.b32 m, %2, %3; setp.ne.u32 p, m, 0; selp.b32 %0, %1, 0, p;}" : "=r"(bt) : "r"(rc.x), "r"(bits0), "r"(smask));
        mma1688z(t1, at[0], at[1], bt);
        mma1688z(t2, at[2], at[3], bt);
        if (TP == 1) tick();
        const uint32_t T0 = pack2(t1[0], t1[2]), T1 = pack2(t2[0], t2[2]), T2 = pack2(t1[1], t1[3]), T3 = pack2(t2[1], t2[3]);
        const uint32_t R0 = pack2(silu_h(z[0]), silu_h(z[2]));
        if (TP == 2) tick();
        const uint32_t R1 = pack2(silu_h(z[1]), silu_h(z[3]));
        if (TP == 3) tick();
        const uint32_t R2 = pack2(silu_h(y[0]), silu_h(y[2])), R3 = pack2(silu_h(y[1]), silu_h(y[3]));
        if (TP == 4) tick();
        mma16816(acc[0], mul_lo(xa.x, R0), mul_hi(xa.z, R0), mul_lo(xa.y, R0), mul_hi(xa.w, R0), T0, T1);
        mma16816(acc[1], mul_lo(xb.x, R1), mul_hi(xb.z, R1), mul_lo(xb.y, R1), mul_hi(xb.w, R1), T2, T3);
        mma16816(acc[2], mul_lo(xc.x, R2), mul_hi(xc.z, R2), mul_lo(xc.y, R2), mul_hi(xc.w, R2), T0, T1);
        mma16816(acc[3], mul_lo(xd.x, R3), mul_hi(xd.z, R3), mul_lo(xd.y, R3), mul_hi(xd.w, R3), T2, T3);
        mp += STEPB; smask <<= 1;
    };
    auto putacc = [&](uint32_t* p) {
        p[0] = pack2(acc[0][0], acc[0][1]); p[32] = pack2(acc[0][2], acc[0][3]); p[64] = pack2(acc[2][0], acc[2][1]); p[96] = pack2(acc[2][2], acc[2][3]);
        p[256] = pack2(acc[1][0], acc[1][1]); p[288] = pack2(acc[1][2], acc[1][3]); p[320] = pack2(acc[3][0], acc[3][1]); p[352] = pack2(acc[3][2], acc[3][3]);
    };
    int ph = 0;
    auto phase_end = [&]() {
        az = *(const uint4*)(smem + SM_AZ + (ph + 1) * 512 + lane * 16);
        putacc(stash + (ph >> 1) * 512 + (ph & 1) * 128);
#pragma unroll
        for (int i = 0; i < 16; i++) acc[i / 4][i % 4] = 0.f;
        pbase += 256; mp = 0; smask = 1; ph++;
        dreg += tphase; dcur = dreg + tcur;
        WSTAMP(ph - 1);
    };
    uint32_t t0 = now;
    auto report = [&](uint32_t cand) {
        uint32_t b0, b1;
        asm volatile("ld.volatile.shared.v2.u32 {%0,%1}, [%2+16];" : "=r"(b0), "=r"(b1) : "r"(flg) : "memory");
        asm volatile("{.reg .pred p; setp.eq.u32 p, %2, 0; @p red.max.relaxed.gpu.global.u64 [%0], %1;}"
                     :: "l"(&gs->t0), "l"((((unsigned long long)b1 << 32) | b0) + (cand - b0)), "r"(lane) : "memory");
    };
    if (w == PW) {
        asm volatile("mov.u32 %0, %%globaltimer_lo;" : "=r"(now));
        now += PTOL - PTOL0;
    }
    auto relay = [&]() {
        uint32_t g0, g1, b0, b1;
        asm volatile("ld.volatile.shared.v2.u32 {%0,%1}, [%4+32]; ld.volatile.shared.v2.u32 {%2,%3}, [%4+16];"
                     : "=r"(g0), "=r"(g1), "=r"(b0), "=r"(b1) : "r"(flg) : "memory");
        const unsigned long long dg = (((unsigned long long)g1 << 32) | g0) - (((unsigned long long)b1 << 32) | b0);
        asm volatile("{.reg .pred p, q; setp.eq.u32 p, %1, 0; setp.lt.u64 q, %2, 30000; @q st.shared.u32 [%3+4], %4;\n"
                     "@p cp.async.cg.shared.global [%3+32], [%0], 16;}"
                     :: "l"(&gs->t0), "r"(lane), "l"(dg), "r"(flg), "r"(g0) : "memory");
    };
    const bool special = w == 0 || w == PW;
#pragma unroll 1
    for (int it = S - 1; it > 0; it--) {
        if (special) {
            if (w == 0) relay();
            else {
                const uint32_t cand = now - dl + tcur - PTOL;
                if ((int)(cand - t0) > 0) report(cand);
            }
        }
        dcur += t0 - tcur; tcur = t0;
#pragma unroll
        for (int k = 0; k < DS; k++) {
            if (k == DS - 1) asm volatile("ld.volatile.shared.u32 %0, [%1+4];" : "=r"(t0) : "r"(flg));
            step(k * SLOTB, 0);
            if (mp == mend || now < dl) {
                if (mp == mend) phase_end();
                if (k < DS - 1 && (RELAY >> k & 1) && w == 0) relay();
                asm volatile("{.reg .pred p; .reg .u32 d;\n"
                             "PACE_LOOP: mov.u32 d, %%globaltimer_lo; sub.u32 d, %0, d; setp.lt.u32 p, d, 32768; @p nanosleep.u32 %1; @p bra.uni PACE_LOOP;}"
                             :: "r"(dl), "n"(PSLEEP) : "memory");
            }
        }
    }
    __syncwarp();
    step(0, 1); step(SLOTB, 2); step(2 * SLOTB, 3); step(3 * SLOTB, 4);
    WSTAMP(3);

    {
        putacc((uint32_t*)(smem + SM_RING + 2 * SLOTB + w * 2048 + 512) + lane);
        const int wg = w >> 2, w4 = w & 3;
        int nd[8];
#pragma unroll
        for (int j = 0; j < 8; j++) { const int l = wg * 8 + j; nd[j] = order[(t >> 1) ? 79 - l : l]; asm volatile("" : "+r"(nd[j])); }
        const bool odd = t & 1;
        uint2* ob = (uint2*)out + (size_t)n0 * 128 + w4 * 16 + g + (odd ? 8 : 0);
        asm volatile("cp.async.wait_all;" ::: "memory");
        mbar_wait(mbarW, 0);
        asm volatile("fence.proxy.async.shared::cta;" ::: "memory");
        TSTAMP(26);
        bar_sync(2 + wg, 128);
        if ((tid & 127) == 0) {
            const uint32_t ticket = atomicAdd((uint32_t*)flag + 12, 1);
            int spins = 0;
            while (flag[13] + LEAD < ticket && ++spins < (1 << 16)) {}
        }
        bar_sync(2 + wg, 128);
        TSTAMP(27);
        const uint64_t descA0 = (uint64_t)(((sb + SM_RING) & 0x3FFFF) >> 4) | ((uint64_t)1 << 16) | ((uint64_t)(1024 >> 4) << 32) | ((uint64_t)1 << 62);
        const uint64_t descB0 = (uint64_t)(((sb + SM_RING + SLOTB + wg * 8192) & 0x3FFFF) >> 4) | ((uint64_t)(128 >> 4) << 16) | ((uint64_t)(1024 >> 4) << 32);
        float d[2][32];
        asm volatile("wgmma.fence.sync.aligned;" ::: "memory");
#pragma unroll
        for (int mt = 0; mt < 2; mt++) {
#pragma unroll
            for (int ks = 0; ks < 8; ks++) {
                const uint64_t da = descA0 + (uint64_t)((ks * 2048 + mt * 16384) >> 4), db = descB0 + (uint64_t)(((ks & 3) * 256 + (ks >> 2) * SLOTB) >> 4);
                asm volatile("{.reg .pred p; setp.ne.b32 p, %34, 0;\n"
                    "wgmma.mma_async.sync.aligned.m64n64k16.f32.bf16.bf16 "
                    "{%0,%1,%2,%3,%4,%5,%6,%7,%8,%9,%10,%11,%12,%13,%14,%15,%16,%17,%18,%19,%20,%21,%22,%23,%24,%25,%26,%27,%28,%29,%30,%31}, %32, %33, p, 1, 1, 1, 1;}"
                    : "+f"(d[mt][0]), "+f"(d[mt][1]), "+f"(d[mt][2]), "+f"(d[mt][3]), "+f"(d[mt][4]), "+f"(d[mt][5]), "+f"(d[mt][6]), "+f"(d[mt][7]),
                      "+f"(d[mt][8]), "+f"(d[mt][9]), "+f"(d[mt][10]), "+f"(d[mt][11]), "+f"(d[mt][12]), "+f"(d[mt][13]), "+f"(d[mt][14]), "+f"(d[mt][15]),
                      "+f"(d[mt][16]), "+f"(d[mt][17]), "+f"(d[mt][18]), "+f"(d[mt][19]), "+f"(d[mt][20]), "+f"(d[mt][21]), "+f"(d[mt][22]), "+f"(d[mt][23]),
                      "+f"(d[mt][24]), "+f"(d[mt][25]), "+f"(d[mt][26]), "+f"(d[mt][27]), "+f"(d[mt][28]), "+f"(d[mt][29]), "+f"(d[mt][30]), "+f"(d[mt][31])
                    : "l"(da), "l"(db), "r"(ks));
            }
            asm volatile("wgmma.commit_group.sync.aligned;" ::: "memory");
            if (mt == RELAT - 1) asm volatile("{.reg .pred p; setp.eq.u32 p, %1, 0; @p red.shared.add.u32 [%0+52], 1;}" :: "r"(flg), "r"(tid & 127) : "memory");
        }
#pragma unroll
        for (int mt = 0; mt < 2; mt++) {
            if (mt == 0) asm volatile("wgmma.wait_group.sync.aligned 1;" ::: "memory");
            else asm volatile("wgmma.wait_group.sync.aligned 0;" ::: "memory");
            if (RELAT == 0 && mt == 0 && (tid & 127) == 0) atomicAdd((uint32_t*)flag + 13, 1);
            TSTAMP(23 + mt);
#pragma unroll
            for (int i = 0; i < 32; i++) asm volatile("" : "+f"(d[mt][i]) :: "memory");
#pragma unroll
            for (int j = 0; j < 8; j++) {
                const uint32_t v0 = pack2(d[mt][4 * j], d[mt][4 * j + 1]), v1 = pack2(d[mt][4 * j + 2], d[mt][4 * j + 3]);
                const uint32_t rv = __shfl_xor_sync(0xffffffff, odd ? v0 : v1, 1);
                if (nd[j] < nn) ob[nd[j] * 128 + mt * 64] = odd ? make_uint2(rv, v1) : make_uint2(v0, rv);
            }
        }
    }
    TSTAMP(8);
}

}

extern "C" void kernel_launch(void* const* d_in, const int* in_sizes, int n_in, void* d_out, int out_size) {
    (void)in_sizes; (void)n_in; (void)out_size;
    cudaFuncSetAttribute(tfn_kernel, cudaFuncAttributeMaxDynamicSharedMemorySize, SM_TOTAL);
    Scratch* gs = nullptr;
    cudaGetSymbolAddress((void**)&gs, g_scratch);
    cudaLaunchConfig_t cfg = {};
    cfg.gridDim = dim3(NB); cfg.blockDim = dim3(NT); cfg.dynamicSmemBytes = SM_TOTAL; cfg.stream = cudaStreamPerThread;
    cudaLaunchAttribute at[1];
    at[0].id = cudaLaunchAttributeCooperative; at[0].val.cooperative = 1;
    cfg.attrs = at; cfg.numAttrs = 1;
    cudaLaunchKernelEx(&cfg, tfn_kernel, (const unsigned char*)d_in[0], (const int4*)d_in[1], (const int4*)d_in[2],
                       (const uint4*)d_in[3], (const uint4*)d_in[4], (const uint16_t*)d_in[5], (const uint16_t*)d_in[6],
                       (const uint4*)d_in[7], (uint32_t*)d_out, gs);
}
```

```cpp
#include <cuda_runtime.h>
#include <cuda_bf16.h>
#include <stdint.h>

#define VOL
#define ORD 1
#define ABL 0
namespace {

constexpr int NN = 10000;
constexpr int NE = 320000;
constexpr int NB = 132;
constexpr int NW = 20;
constexpr int NT = NW * 32;
constexpr int CW = NW - 1;
#define PWARP 10
constexpr int PW = PWARP;
constexpr int NPB = 76;
constexpr int CELL = 48;
constexpr int RCH = 2880;
constexpr int CAP = 19;
constexpr int DS = 4;
constexpr int STEPB = 160;
constexpr int NE4 = NE / 4;
constexpr int NPIECE = NB * 8;
constexpr int KB = 320, KN = 32 * KB;
constexpr uint32_t F_WRAP = 1;

constexpr int SLOTB = NW * 2048;
constexpr int SM_RING = 0;
constexpr int SM_META = SM_RING + DS * SLOTB;
constexpr int SM_AZ = SM_META + NW * CAP * STEPB;
constexpr int SM_MISC = SM_AZ + 2048;
constexpr int SM_TOTAL = SM_MISC + 2048;
constexpr int SM_STAGE = SM_RING;
constexpr int SM_HIST = SM_RING + 25600;
constexpr int SM_POS = SM_RING;
constexpr int SM_SMALL = SM_HIST + 13056;
constexpr int SM_LIST = SM_RING + SLOTB;
constexpr int SM_ROUT = SM_RING + 2 * SLOTB;
constexpr int SM_RECS = SM_RING + 3 * SLOTB;
constexpr int SM_RAWY = SM_META;
constexpr int SM_RAWE = SM_RAWY + 608 * 32;
constexpr int SM_KEYS = SM_RAWE + 608 * 32;
static_assert(SM_TOTAL <= 232448 && SM_KEYS + NPIECE * 16 <= SM_AZ, "smem");
static_assert(SM_RECS + NB * CELL * 16 + 16 <= SM_AZ && SM_KEYS + NPIECE * 16 <= SM_RECS + NB * CELL * 16 && SM_SMALL + 1152 <= SLOTB && DS == 4, "smem");

struct Scratch {
    uint4 keys[NB * NPIECE];
    uint4 recs[NB * RCH];
    uint4 stash[NB * NW * 256];
    unsigned bar[4];
    unsigned long long t0, pad;
};
__device__ Scratch g_scratch;
#define TSTAMP(i)
#define TSTAMPC(i)
#define WSTAMP(i)

__device__ __forceinline__ void mma16816(float* d, uint32_t a0, uint32_t a1, uint32_t a2, uint32_t a3, uint32_t b0, uint32_t b1) {
    asm VOL("mma.sync.aligned.m16n8k16.row.col.f32.bf16.bf16.f32 {%0,%1,%2,%3}, {%4,%5,%6,%7}, {%8,%9}, {%0,%1,%2,%3};"
        : "+f"(d[0]), "+f"(d[1]), "+f"(d[2]), "+f"(d[3]) : "r"(a0), "r"(a1), "r"(a2), "r"(a3), "r"(b0), "r"(b1));
}
__device__ __forceinline__ void mma1688z(float* d, uint32_t a0, uint32_t a1, uint32_t b0) {
    asm VOL("mma.sync.aligned.m16n8k8.row.col.f32.bf16.bf16.f32 {%0,%1,%2,%3}, {%4,%5}, {%6}, {%7,%7,%7,%7};"
        : "=f"(d[0]), "=f"(d[1]), "=f"(d[2]), "=f"(d[3]) : "r"(a0), "r"(a1), "r"(b0), "f"(0.f));
}
__device__ __forceinline__ uint32_t pack2(float lo, float hi) {
    uint32_t r; asm VOL("cvt.rn.bf16x2.f32 %0, %1, %2;" : "=r"(r) : "f"(hi), "f"(lo)); return r;
}
__device__ __forceinline__ float silu_h(float h) {
    float t; asm VOL("tanh.approx.f32 %0, %1;" : "=f"(t) : "f"(h)); return fmaf(h, t, h);
}
__device__ __forceinline__ uint32_t mul_lo(uint32_t v, uint32_t r) {
    __nv_bfloat162 a = *(__nv_bfloat162*)&v, b = *(__nv_bfloat162*)&r; __nv_bfloat162 c = __hmul2(a, __low2bfloat162(b)); return *(uint32_t*)&c;
}
__device__ __forceinline__ uint32_t mul_hi(uint32_t v, uint32_t r) {
    __nv_bfloat162 a = *(__nv_bfloat162*)&v, b = *(__nv_bfloat162*)&r; __nv_bfloat162 c = __hmul2(a, __high2bfloat162(b)); return *(uint32_t*)&c;
}
__device__ __forceinline__ uint2 lds64(uint32_t a) {
    uint2 r; asm volatile("ld.shared.v2.u32 {%0,%1}, [%2];" : "=r"(r.x), "=r"(r.y) : "r"(a)); return r;
}
__device__ __forceinline__ uint4 lds128(uint32_t a) {
    uint4 r; asm volatile("ld.shared.v4.u32 {%0,%1,%2,%3}, [%4];" : "=r"(r.x), "=r"(r.y), "=r"(r.z), "=r"(r.w) : "r"(a) : "memory"); return r;
}
__device__ __forceinline__ void bar_sync(int id, int n) { asm volatile("bar.sync %0, %1;" :: "r"(id), "r"(n) : "memory"); }
__device__ __forceinline__ void bar_arrive(int id, int n) { asm volatile("bar.arrive %0, %1;" :: "r"(id), "r"(n) : "memory"); }
__device__ __forceinline__ void mbar_wait(uint32_t bar, uint32_t ph) {
    uint32_t done; int spins = 0;
    do {
        asm volatile("{.reg .pred p; mbarrier.try_wait.parity.shared.b64 p, [%1], %2; selp.u32 %0,1,0,p;}" : "=r"(done) : "r"(bar), "r"(ph) : "memory");
    } while (!done && ++spins < (1 << 22));
}
__device__ __forceinline__ unsigned gbar_read(const unsigned* ctr) {
    unsigned v; asm volatile("ld.relaxed.gpu.global.u32 %0, [%1];" : "=r"(v) : "l"(ctr) : "memory");
    return v;
}
__device__ __forceinline__ void gbar_arrive(unsigned* ctr) {
    asm volatile("red.add.release.gpu.global.u32 [%0], 1;" :: "l"(ctr) : "memory");
}
__device__ __forceinline__ bool gbar_wait(const unsigned* ctr, unsigned target) {
    unsigned v; int spins = 0;
    do { asm volatile("ld.acquire.gpu.global.u32 %0, [%1];" : "=r"(v) : "l"(ctr) : "memory"); } while ((int)(v - target) < 0 && ++spins < (1 << 22));
    return (int)(v - target) >= 0;
}
__device__ __forceinline__ int chunk_start4(int c) { return (c * NE4) / NB; }
__device__ __forceinline__ float bf2f(uint32_t h) { return __uint_as_float(h << 16); }

__device__ __noinline__ void slow_path(unsigned char* smem, int n0, int nn, const uint16_t* x, const int* src, const int* dst,
                                       const uint16_t* Y, const uint16_t* ef, const uint16_t* w_rad, const uint16_t* cg,
                                       const uint16_t* w_mix, __nv_bfloat16* out) {
    float* agg = (float*)smem;
    const int tid = threadIdx.x, lane = tid & 31, w = tid >> 5;
    bar_sync(1, NT);
    for (int i = tid; i < NPB * 512; i += NT) agg[i] = 0.f;
    bar_sync(1, NT);
    for (int e0 = w * 32; e0 < NE; e0 += NT) {
        int dl = dst[e0 + lane] - n0;
        unsigned m = __ballot_sync(0xffffffff, dl >= 0 && dl < nn);
        while (m) {
            int l = __ffs(m) - 1; m &= m - 1;
            int e = e0 + l, d = __shfl_sync(0xffffffff, dl, l), s = src[e];
            float T[16];
            for (int i = 0; i < 4; i++) for (int o = 0; o < 4; o++) {
                float a = 0.f;
                for (int f = 0; f < 4; f++) a += bf2f(Y[e * 4 + f]) * bf2f(cg[i * 16 + f * 4 + o]);
                T[i * 4 + o] = a;
            }
            for (int k = 0; k < 4; k++) {
                int c = lane + 32 * k;
                float z = 0.f;
                for (int j = 0; j < 4; j++) z += bf2f(ef[e * 4 + j]) * bf2f(w_rad[j * 128 + c]);
                float R = z / (1.f + __expf(-z));
                for (int o = 0; o < 4; o++) {
                    float a = 0.f;
                    for (int i = 0; i < 4; i++) a += bf2f(x[(size_t)s * 512 + c * 4 + i]) * T[i * 4 + o];
                    atomicAdd(&agg[d * 512 + c * 4 + o], R * a);
                }
            }
        }
    }
    bar_sync(1, NT);
    for (int i = tid; i < nn * 512; i += NT) {
        int n = i >> 9, d = (i >> 2) & 127, o = i & 3;
        float a = 0.f;
        for (int c = 0; c < 128; c++) a += agg[n * 512 + c * 4 + o] * bf2f(w_mix[c * 128 + d]);
        out[(size_t)(n0 + n) * 512 + (i & 511)] = __float2bfloat16(a);
    }
}

#define PACE 24000
#define YDELAY 300
#define TP 0
#define BFENCE 0
#define ASYM 0
#define PEV 10
#define EPI 2
#define LEAD 0
#define RELAT 2
#define POFF 1700
#define RELAY 2
#define PSLEEP 32
#define PTOL0 300
#define PTOL 800
__global__ void __launch_bounds__(NT, 1)
tfn_kernel(const unsigned char* __restrict__ x, const int4* __restrict__ src4, const int4* __restrict__ dst4,
           const uint4* __restrict__ Y, const uint4* __restrict__ ef, const uint16_t* __restrict__ w_rad,
           const uint16_t* __restrict__ cg, const uint4* __restrict__ w_mix, uint32_t* __restrict__ out, Scratch* __restrict__ gs) {
    extern __shared__ __align__(1024) unsigned char smem[];
    const uint32_t sb = (uint32_t)__cvta_generic_to_shared(smem);
    const int b = blockIdx.x, tid = threadIdx.x, lane = tid & 31, g = lane >> 2, t = lane & 3;
    const int w = __shfl_sync(0xffffffff, tid >> 5, 0);
    uint32_t* stage = (uint32_t*)(smem + SM_STAGE);
    uint32_t* hist = (uint32_t*)(smem + SM_HIST);
    uint32_t* cnt = (uint32_t*)(smem + SM_MISC);
    uint32_t* deg = cnt + 136;
    uint32_t* order = deg + 104;
    uint32_t* cnt2 = order + 80;
    volatile uint32_t* flag = cnt2 + 136;
    const uint32_t mbarK = sb + SM_MISC + 1920, mbarR = mbarK + 8, mbarW = mbarK + 16;
    const int n0 = b * NPB, nn = min(NPB, NN - n0);
    TSTAMP(0);

    const int c0 = chunk_start4(b), c1 = chunk_start4(b + 1);
    const bool has4 = c0 + tid < c1;
    int4 d4 = make_int4(0, 0, 0, 0), s4 = d4;
    if (has4) { d4 = __ldg(dst4 + c0 + tid); s4 = __ldg(src4 + c0 + tid); }
    unsigned tgt = 0;
    if (tid == NT - 1) {
        tgt = gbar_read(&gs->bar[0]);
        asm volatile("mbarrier.init.shared.b64 [%0], 1;" :: "r"(mbarK));
        asm volatile("mbarrier.init.shared.b64 [%0], 1;" :: "r"(mbarR));
        asm volatile("mbarrier.init.shared.b64 [%0], 512;" :: "r"(mbarW));
        asm volatile("fence.mbarrier_init.release.cluster;" ::: "memory");
        flag[0] = 0; flag[12] = 0; flag[13] = 0; flag[15] = 0;
    }
    if (w == CW) {
        asm volatile("cp.async.cg.shared.global [%0], [%1], 16;" :: "r"(sb + SM_SMALL + lane * 16), "l"(w_rad + lane * 8) : "memory");
        asm volatile("cp.async.cg.shared.global [%0], [%1], 16;" :: "r"(sb + SM_SMALL + 512 + lane * 16), "l"(w_rad + 256 + lane * 8) : "memory");
        if (lane < 8) asm volatile("cp.async.cg.shared.global [%0], [%1], 16;" :: "r"(sb + SM_SMALL + 1024 + lane * 16), "l"(cg + lane * 8) : "memory");
    }
    ((uint4*)hist)[tid] = make_uint4(0, 0, 0, 0);
    {
        const uint32_t dk = (80 + b % 22) * KN + (b & 31) * KB;
#pragma unroll
        for (int j = 0; j < 3; j++) if (tid + j * NT < NB * CELL / 4) ((uint4*)stage)[tid + j * NT] = make_uint4(dk, dk, dk, dk);
    }
    if (tid < 136) cnt[tid] = 0;
    if (tid == 0) { *(uint4*)(smem + SM_MISC + 1824 + 32) = make_uint4(0, 0, 0, 0); *(uint4*)(smem + SM_RECS + NB * CELL * 16) = make_uint4(0, 0, 0, 0); }
    if (tid < 80) { deg[tid] = 127 - tid; order[tid] = tid; }
    __syncthreads();
    TSTAMP(9);
    if (tid == 64) {
        if (YDELAY) __nanosleep(YDELAY);
        asm volatile("mbarrier.arrive.expect_tx.shared.b64 _, [%0], %1;" :: "r"(mbarR), "r"((c1 - c0) * 64) : "memory");
        asm volatile("cp.async.bulk.shared::cluster.global.mbarrier::complete_tx::bytes [%0], [%1], %2, [%3];"
                     :: "r"(sb + SM_RAWY), "l"(Y + 2 * c0), "r"((c1 - c0) * 32), "r"(mbarR) : "memory");
        asm volatile("cp.async.bulk.shared::cluster.global.mbarrier::complete_tx::bytes [%0], [%1], %2, [%3];"
                     :: "r"(sb + SM_RAWE), "l"(ef + 2 * c0), "r"((c1 - c0) * 32), "r"(mbarR) : "memory");
    }

    uint32_t bin[4] = {0, 0, 0, 0}, slot[4] = {0, 0, 0, 0};
    if (has4) {
        const uint32_t dd[4] = {(uint32_t)d4.x, (uint32_t)d4.y, (uint32_t)d4.z, (uint32_t)d4.w}, ss[4] = {(uint32_t)s4.x, (uint32_t)s4.y, (uint32_t)s4.z, (uint32_t)s4.w};
#pragma unroll
        for (int k = 0; k < 4; k++) { bin[k] = dd[k] / NPB; slot[k] = atomicAdd(&cnt[bin[k]], 1); }
#pragma unroll
        for (int k = 0; k < 4; k++) stage[bin[k] * CELL + min(slot[k], CELL - 1)] = (dd[k] - bin[k] * NPB) * KN + ss[k];
    }
    if (w == CW) {
        if (tid == NT - 1) { tgt = tgt / NB + 1; flag[14] = (tgt & 1) << 31; tgt *= NB; }
        asm volatile("cp.async.wait_all;" ::: "memory");
    }
    bar_sync(1, NT);
    TSTAMP(1);
    const uint32_t tag = flag[14];
#pragma unroll
    for (int j = 0; j < 2; j++) {
        const int i = tid + j * NT;
        if (i < NPIECE) {
            const uint2 sa = *(const uint2*)(stage + i * 6), sc = *(const uint2*)(stage + i * 6 + 2);
            uint2 se = *(const uint2*)(stage + i * 6 + 4);
            const uint32_t cf = cnt[i >> 3], cn = min(cf, 63u);
            if ((i & 7) == 7) {
                const uint32_t al = cf > CELL - 8 ? 7 : 0;
                se.y = (atomicAdd((uint32_t*)flag + 15, cf + al) + al) & ~al;
                cnt2[i >> 3] = se.y;
            }
            asm volatile("{.reg .b64 lo, hi; mov.b64 lo, {%1,%2}; mov.b64 hi, {%3,%4}; st.relaxed.gpu.global.v2.b64 [%0], {lo, hi};}"
                         :: "l"(gs->keys + ((i >> 3) * NB + b) * 8 + ((i ^ b) & 7)),
                            "r"(sa.x | (se.x << 20)), "r"(sa.y | ((se.x >> 12) << 20) | ((cn & 7) << 28) | tag),
                            "r"(sc.x | (se.y << 20)), "r"(sc.y | ((se.y >> 12) << 20) | ((cn >> 3) << 28) | tag) : "memory");
        }
    }
    bar_sync(1, NT);
    if (tid == NT - 1) {
        TSTAMPC(10);
        asm volatile("red.add.relaxed.gpu.global.u32 [%0], 1;" :: "l"(&gs->bar[0]) : "memory");
    }
    uint32_t at[4];
    {
        const int o = g & 3, f = 2 * (t & 1);
#pragma unroll
        for (int i = 0; i < 4; i++) {
            const uint16_t* cp = (const uint16_t*)(smem + SM_SMALL + 1024) + i * 16 + f * 4 + o;
            at[i] = (t >> 1) == (g >> 2) ? cp[0] | ((uint32_t)cp[4] << 16) : 0;
        }
    }

    uint32_t key[2][6], ha[2][6], rk[2][6], kidx[2], ka[2];
    int nk[2];
#pragma unroll
    for (int j = 0; j < 2; j++) {
        const int i0 = j ? 2 * 608 - 1 - tid : tid, i = min(i0, NPIECE - 1), r = i / NB, c = i - r * NB;
        ka[j] = sb + SM_KEYS + (c * 8 + ((r ^ c) & 7)) * 16;
        kidx[j] = (c * CELL + r * 6) << 17;
        nk[j] = i0 < NPIECE && w < CW ? -6 * r : -1000;
    }
    asm volatile("" : "+r"(at[0]), "+r"(at[1]), "+r"(at[2]), "+r"(at[3]), "+r"(ka[0]), "+r"(ka[1]), "+r"(kidx[0]), "+r"(kidx[1]), "+r"(nk[0]), "+r"(nk[1]));
    if (w == CW) {
        if (tid == NT - 1) {
            asm volatile("mbarrier.arrive.expect_tx.shared.b64 _, [%0], %1;" :: "r"(mbarK), "r"(NPIECE * 16) : "memory");
            gbar_wait(&gs->bar[0], tgt);
            TSTAMPC(13);
            asm volatile("fence.proxy.async.global;" ::: "memory");
            asm volatile("cp.async.bulk.shared::cluster.global.mbarrier::complete_tx::bytes [%0], [%1], %2, [%3];"
                         :: "r"(sb + SM_KEYS), "l"(gs->keys + b * NPIECE), "r"(NPIECE * 16), "r"(mbarK) : "memory");
        }
        __syncwarp();
        bar_sync(7, NT);
        if (tid == NT - 1) {
            TSTAMPC(11);
            asm volatile("cp.async.bulk.global.shared::cta.bulk_group [%0], [%1], %2;"
                         :: "l"(gs->recs + b * RCH), "r"(sb + SM_ROUT), "r"(((flag[15] + 1) & ~1u) * 16) : "memory");
            asm volatile("cp.async.bulk.commit_group; cp.async.bulk.wait_group 0;" ::: "memory");
            TSTAMPC(14);
            asm volatile("red.add.relaxed.gpu.global.u32 [%0], 1;" :: "l"(&gs->bar[1]) : "memory");
            TSTAMPC(15);
            if (!gbar_wait(&gs->bar[1], tgt)) *flag = 1;
            TSTAMPC(17);
        }
    } else {
        if (w < 8) {
            const uint32_t* wp = (const uint32_t*)(smem + SM_SMALL) + (t & 1) * 128 + 8 * w + g;
            const uint32_t wr0 = t < 2 ? wp[0] : 0, wr1 = t < 2 ? wp[64] : 0;
            *(uint2*)(smem + SM_AZ + (w >> 1) * 512 + lane * 16 + (w & 1) * 8) =
                make_uint2(pack2(0.5f * bf2f(wr0 & 0xFFFF), 0.5f * bf2f(wr1 & 0xFFFF)), pack2(0.5f * bf2f(wr0 >> 16), 0.5f * bf2f(wr1 >> 16)));
        }
        const bool sw = g & 1;
        uint32_t rp[4];
#pragma unroll
        for (int k = 0; k < 4; k++) rp[k] = cnt2[bin[k]] + slot[k];
        uint4* ro = (uint4*)(smem + SM_ROUT);
        uint4 *p0 = ro + (sw ? rp[2] : rp[0]), *p1 = ro + (sw ? rp[3] : rp[1]), *p2 = ro + (sw ? rp[0] : rp[2]), *p3 = ro + (sw ? rp[1] : rp[3]);
        const uint32_t ya = sb + SM_RAWY + tid * 32 + (sw ? 16 : 0);
        mbar_wait(mbarR, 0);
        TSTAMP(18);
        if (has4) {
            const uint4 y0 = lds128(ya), e0 = lds128(ya + (SM_RAWE - SM_RAWY)), y1 = lds128(ya ^ 16), e1 = lds128((ya ^ 16) + (SM_RAWE - SM_RAWY));
            *p0 = make_uint4(y0.x, e0.x, y0.y, e0.y); *p1 = make_uint4(y0.z, e0.z, y0.w, e0.w);
            *p2 = make_uint4(y1.x, e1.x, y1.y, e1.y); *p3 = make_uint4(y1.z, e1.z, y1.w, e1.w);
        }
        asm volatile("fence.proxy.async.shared::cta;" ::: "memory");
        bar_arrive(7, NT);
    }
    __syncwarp();
    TSTAMP(2);

    if (w < CW) {
        mbar_wait(mbarK, 0);
        TSTAMP(3);
        uint4 v[2] = {lds128(ka[0]), lds128(ka[1])};
#pragma unroll
        for (int j = 0; j < 2; j++) {
            int spins = 0;
            while ((int)((v[j].y ^ tag) | (v[j].w ^ tag)) < 0) {
                asm volatile("{.reg .b64 lo, hi; ld.relaxed.gpu.global.v2.b64 {lo, hi}, [%4]; mov.b64 {%0,%1}, lo; mov.b64 {%2,%3}, hi;}"
                             : "=r"(v[j].x), "=r"(v[j].y), "=r"(v[j].z), "=r"(v[j].w) : "l"((const unsigned char*)(gs->keys + b * NPIECE) + (ka[j] - sb - SM_KEYS)) : "memory");
                if (++spins > (1 << 20)) { *flag = 1; break; }
            }
            const uint32_t hc = ((v[j].y >> 28) & 7) | ((v[j].w >> 25) & 0x38);
            if (j == 1 && nk[j] == -42) {
                cnt[kidx[j] / (CELL << 17)] = hc | ((v[j].z >> 20) << 8);
                v[j].w |= ((80 * KN) >> 12) << 20;
            }
            if (hc > CELL - 1) *flag = 1;
            nk[j] += hc;
            if (nk[j] > 0) {
                key[j][0] = v[j].x & 0xFFFFF; key[j][1] = v[j].y & 0xFFFFF; key[j][2] = v[j].z & 0xFFFFF; key[j][3] = v[j].w & 0xFFFFF;
                key[j][4] = (v[j].x >> 20) | ((v[j].y >> 8) & 0xFF000); key[j][5] = (v[j].z >> 20) | ((v[j].w >> 8) & 0xFF000);
#pragma unroll
                for (int u = 0; u < 6; u++) {
                    ha[j][u] = __umulhi(key[j][u], 0xFFFFFFFFu / KB + 1);
                    rk[j][u] = atomicAdd(&hist[ha[j][u]], 1);
                    atomicAdd(&deg[ha[j][u] >> 5], 128);
                }
            }
        }
        bar_sync(9, NT - 32);
        TSTAMP(20);
#pragma unroll
        for (int j = 0; j < 2; j++) kidx[j] += ((cnt[kidx[j] / (CELL << 17)] >> 8) & 7) << 17;
        const int n = tid >> 3, sub = tid & 7;
        const uint32_t me = deg[n];
        int r = 0;
#pragma unroll
        for (int k = 0; k < 5; k++) { const uint2 dd = *(const uint2*)(deg + sub * 10 + 2 * k); r += (dd.x > me) + (dd.y > me); }
        r += __shfl_xor_sync(0xffffffff, r, 1); r += __shfl_xor_sync(0xffffffff, r, 2); r += __shfl_xor_sync(0xffffffff, r, 4);
        if (sub == 0) order[r] = n;
    }
    if (w < CW) {
        bar_sync(9, NT - 32);
        TSTAMP(22);
#pragma unroll 1
        for (int v = w; v < NW; v += (w == 1 ? CW - 1 : NW)) {
            const uint2 na = *(const uint2*)(order + 2 * v), nb = *(const uint2*)(order + 78 - 2 * v);
            const uint32_t ia0 = na.x * 32 + lane, ib0 = nb.y * 32 + lane, ia1 = na.y * 32 + lane, ib1 = nb.x * 32 + lane;
            const uint32_t ca = hist[ia0] + (hist[ia1] << 16), cab = ca + hist[ib0] + (hist[ib1] << 16);
            uint32_t inc = cab;
#pragma unroll
            for (int o = 1; o < 32; o <<= 1)
                asm volatile("{.reg .pred p; .reg .u32 u; shfl.sync.up.b32 u|p, %0, %1, 0, 0xffffffff; @p add.u32 %0, %0, u;}" : "+r"(inc) : "r"(o));
            const uint32_t ea = inc - cab, eb = ea + ca, base = sb + SM_LIST + v * 2048;
            uint2* pos = (uint2*)(smem + SM_POS);
            pos[ia0] = make_uint2(base + (ea & 0xFFFF) * 8, na.x * (0u - 4 * KN));
            pos[ib0] = make_uint2(base + (eb & 0xFFFF) * 8, nb.y * (0u - 4 * KN) + 0x10000);
            pos[ia1] = make_uint2(base + 4 + (ea >> 16) * 8, na.y * (0u - 4 * KN));
            pos[ib1] = make_uint2(base + 4 + (eb >> 16) * 8, nb.x * (0u - 4 * KN) + 0x10000);
            if (lane == 31) { cnt2[v] = inc; if (max(inc & 0xFFFF, inc >> 16) > 4 * CAP) *flag = 1; }
        }
        bar_sync(9, NT - 32);
        TSTAMP(21);
        const uint32_t over = *flag;
#pragma unroll
        for (int j = 0; j < 2; j++) {
            if (nk[j] > 0) {
                uint2 h[6];
#pragma unroll
                for (int u = 0; u < 6; u++) h[u] = lds64(sb + SM_POS + ha[j][u] * 8);
                if (over) nk[j] = 0;
#pragma unroll
                for (int u = 0; u < 6; u++)
                    asm volatile("{.reg .pred p; setp.gt.s32 p, %2, %3; @p st.shared.u32 [%0], %1;}"
                                 :: "r"(h[u].x + rk[j][u] * 8), "r"(key[j][u] * 4 + h[u].y + (kidx[j] + (u << 17))), "r"(nk[j]), "r"(u) : "memory");
            }
        }
    }
    bar_sync(1, NT);
    TSTAMP(4);
    if (*flag) {
        slow_path(smem, n0, nn, (const uint16_t*)x, (const int*)src4, (const int*)dst4, (const uint16_t*)Y, (const uint16_t*)ef, w_rad, cg,
                  (const uint16_t*)w_mix, (__nv_bfloat16*)out);
        return;
    }
    {
        const uint32_t ci = cnt[min(w + NW * lane, NB)];
        const uint4* gp = gs->recs + w * RCH + lane;
        const uint32_t sp = sb + SM_RECS + (w * CELL + lane) * 16;
#pragma unroll
        for (int j = 0; j < 7; j++) {
            const uint32_t cj = __shfl_sync(0xffffffff, ci, j);
            asm volatile("{.reg .pred p; setp.lt.u32 p, %2, %3; @p cp.async.cg.shared.global [%0], [%1], 16;}"
                         :: "r"(sp + j * (NW * CELL * 16) + ((cj >> 4) & 0x70)), "l"(gp + j * (NW * RCH) + (cj >> 8)), "r"(lane), "r"(cj & 0xFF) : "memory");
        }
        if (__any_sync(0xffffffff, (ci & 0xFF) > 32)) {
#pragma unroll 1
            for (int j = 0; j < 7; j++) {
                const uint32_t cj = __shfl_sync(0xffffffff, ci, j);
                if (lane + 32 < (cj & 0xFF))
                    asm volatile("cp.async.cg.shared.global [%0], [%1], 16;"
                                 :: "r"(sp + j * (NW * CELL * 16) + ((cj >> 4) & 0x70) + 512), "l"(gp + j * (NW * RCH) + (cj >> 8) + 32) : "memory");
            }
        }
        asm volatile("cp.async.commit_group;" ::: "memory");
    }
    const uint32_t len2 = cnt2[w];
    const int S = __shfl_sync(0xffffffff, max((int)(max(len2 & 0xFFFF, len2 >> 16) + 3) >> 2, DS + 1), 0);
    const int mylen = (lane & 1) ? len2 >> 16 : len2 & 0xFFFF;
    constexpr int NRAW = (CAP + 3) / 4;
    uint32_t bits0 = 0, raw[NRAW];
    unsigned char* meta = smem + SM_META + w * (CAP * STEPB);
#pragma unroll
    for (int k = 0; k < NRAW; k++) raw[k] = mylen ? ((uint32_t*)(smem + SM_LIST + w * 2048))[min(k * 16 + (lane >> 1), mylen - 1) * 2 + (lane & 1)] : 4 * n0;
    const uint32_t sv0 = raw[0] & 0xFFFF;
    const int q = lane >> 3, c = lane & 7;
    const uint32_t ring0 = sb + SM_RING + w * 2048;
    uint32_t wdst = ring0 + q * 128 + ((c + 2 * q) & 7) * 16;
    uint32_t rsrc = ring0 + t * 128 + ((g + 2 * t) & 7) * 16;
    uint32_t recl = sb + SM_META + w * (CAP * STEPB) + g * 16 + (t & 1) * 8, srcl = sb + SM_META + w * (CAP * STEPB) + 128 + q * 8;
    uint32_t flg = sb + SM_MISC + (136 + 104 + 80 + 136) * 4;
    asm volatile("" : "+r"(wdst), "+r"(rsrc), "+r"(recl), "+r"(srcl), "+r"(flg));
    const unsigned char* pbase = x + c * 16;
    auto cpa2 = [&](uint32_t dstp, uint32_t sv) {
        asm volatile("cp.async.cg.shared.global [%0], [%1], 16; cp.async.cg.shared.global [%0+1024], [%1+128], 16;"
                     :: "r"(dstp), "l"(pbase + (size_t)sv * 256) : "memory");
    };
    auto fill = [&](int i) {
        cpa2(wdst + i * SLOTB, __shfl_sync(0xffffffff, sv0, 8 * i + 2 * q)); cpa2(wdst + i * SLOTB + 512, __shfl_sync(0xffffffff, sv0, 8 * i + 2 * q + 1));
        asm volatile("cp.async.commit_group;" ::: "memory");
    };
    fill(0);
    TSTAMP(5);
    if (w == 0) {
        unsigned long long tbase;
        asm volatile("mov.u64 %0, %%globaltimer;" : "=l"(tbase));
        tbase += POFF;
        flag[1] = (uint32_t)tbase; flag[4] = (uint32_t)tbase; flag[5] = (uint32_t)(tbase >> 32);
        if (lane == 0) {
            asm volatile("red.max.relaxed.gpu.global.u64 [%0], %1;" :: "l"(&gs->t0), "l"(tbase) : "memory");
            if (b < 128) asm volatile("cp.async.bulk.prefetch.L2.global [%0], 256;" :: "l"(w_mix + b * 16));
        }
    }
    uint32_t ra[NRAW];
#pragma unroll
    for (int k = 0; k < NRAW; k++) {
        const uint32_t m = (__ballot_sync(0xffffffff, raw[k] & 0x10000) >> g) & 0x01010101u;
        bits0 |= ((m * 0x10204080u) >> 28) << (4 * k);
        ra[k] = sb + SM_RECS + (k * 16 + (lane >> 1) < mylen ? raw[k] >> 17 : NB * CELL) * 16;
    }
    if (t < 2) bits0 = ~bits0;
    fill(1);
    asm volatile("cp.async.wait_group 2;" ::: "memory");
    bar_sync(1, NT);
    TSTAMP(19);
    {
        uint4 rv[NRAW];
#pragma unroll
        for (int k = 0; k < NRAW - 1; k++) rv[k] = lds128(ra[k]);
        if ((NRAW - 1) * 4 < S) rv[NRAW - 1] = lds128(ra[NRAW - 1]);
        if (tid == 0) asm volatile("cp.async.cg.shared.global [%0], [%1], 16;" :: "r"(sb + SM_MISC + 1824 + 32), "l"(&gs->t0) : "memory");
        fill(2);
        bar_sync(1, NT);
        TSTAMP(12);
        unsigned char* mr = meta + (q - 1) * STEPB + c * 16;
        unsigned char* ms = meta + (q - DS - 1) * STEPB + 128 + c * 4;
#pragma unroll
        for (int k = 0; k < NRAW; k++) {
            if (k == 0) {
                *(uint4*)(mr + (q == 0 ? S * STEPB : 0)) = rv[k];
                *(uint32_t*)(ms + S * STEPB) = sv0 + F_WRAP;
            } else if (k * 4 + q < S) {
                *(uint4*)(mr + k * 4 * STEPB) = rv[k];
                *(uint32_t*)(ms + k * 4 * STEPB + (k == 1 && q == 0 ? S * STEPB : 0)) = raw[k] & 0xFFFF;
            }
        }
    }
    __syncwarp();
    const uint32_t tphase = PACE / 4;
    uint32_t dreg;
    {
        const int st = lane == 0 ? S - 1 : min(lane, S) - 1;
        const uint4 u0 = *(const uint4*)(meta + st * STEPB + 128), u1 = *(const uint4*)(meta + st * STEPB + 144);
        int pos = (u0.x + u0.y + u0.z + u0.w + u1.x + u1.y + u1.z + u1.w) >> 5;
        pos += ((u0.x & F_WRAP) ? NN : 0) + (lane == S ? NN : 0) - NN * (2 * DS + 1) / 32;
        dreg = pos * (int)tphase / NN;
    }
    fill(3);
    TSTAMP(6);

    uint32_t* stash = (uint32_t*)(gs->stash + (b * NW + w) * 256) + lane;
    float acc[4][4];
#pragma unroll
    for (int i = 0; i < 16; i++) acc[i / 4][i % 4] = 0.f;
    uint4 az = *(const uint4*)(smem + SM_AZ + lane * 16);
    uint32_t dcur = dreg, dl = 0, now = flag[1], tcur = 0;
    uint32_t mp = 0, smask = 1;
    const uint32_t mend = S * STEPB;
    uint2 r = lds64(mend - STEPB + recl), s0 = lds64(mend - STEPB + srcl);
    auto step = [&](const uint32_t off, const int mode, const bool pc = true) {
        auto tick = [&]() { if (mode == 0 && pc) { unsigned long long n64; asm volatile("mov.u64 %0, %%globaltimer;" : "=l"(n64)); now = (uint32_t)n64; } };
        if (TP == 0) tick();
        const uint2 rc = r, sc = s0;
        if (ORD & 1) { if (mode != 4) r = lds64(mp + recl); if (mode == 0) s0 = lds64(mp + srcl); }
        asm volatile("cp.async.wait_group %0;" :: "n"(DS - 1) : "memory");
        const uint4 xa = lds128(rsrc + off), xb = lds128(rsrc + off + 512), xc = lds128(rsrc + off + 1024), xd = lds128(rsrc + off + 1536);
        if (!(ORD & 1) && !(ORD & 4)) { if (mode != 4) r = lds64(mp + recl); if (mode == 0) s0 = lds64(mp + srcl); }
        if (mode == 0) {
            if (ORD & 2) {
                asm volatile("shfl.sync.idx.b32 %0, %1, 1, 31, 0xffffffff; shfl.sync.down.b32 %1, %1, 1, 31, 0xffffffff;\n"
                             "cp.async.cg.shared.global [%2], [%3], 16; cp.async.cg.shared.global [%2+512], [%4], 16;\n"
                             "cp.async.cg.shared.global [%2+1024], [%3+128], 16; cp.async.cg.shared.global [%2+1536], [%4+128], 16;"
                             : "=&r"(dl), "+r"(dcur) : "r"(wdst + off), "l"(pbase + (size_t)sc.x * 256), "l"(pbase + (size_t)sc.y * 256) : "memory");
            } else {
                dl = __shfl_sync(0xffffffff, dcur, 1); dcur = __shfl_down_sync(0xffffffff, dcur, 1);
                cpa2(wdst + off, sc.x); cpa2(wdst + off + 512, sc.y);
            }
        }
        if (mode == 1 && w < 16) {
#pragma unroll
            for (int j = 0; j < 4; j++) {
                const int kk = 4 * j + q, ch = 16 * (w & 7) + 2 * (kk & 7) + (kk >> 3);
                asm volatile("cp.async.cg.shared.global [%0], [%1], 16;" :: "r"(ring0 + kk * 128 + ((c ^ (kk & 7)) << 4)), "l"(w_mix + ch * 16 + (w >> 3) * 8 + c) : "memory");
            }
            asm volatile("cp.async.mbarrier.arrive.noinc.shared.b64 [%0];" :: "r"(mbarW) : "memory");
        }
        if (mode == 2 || mode == 3) {
#pragma unroll
            for (int j = 0; j < 4; j += mode - 1)
                asm volatile("cp.async.cg.shared.global [%0], [%1], 16;" :: "r"(ring0 + off + j * 512 + lane * 16), "l"(stash + (mode - 2) * 512 + j * 128 + lane * 3) : "memory");
        }
        asm volatile("cp.async.commit_group;" ::: "memory");
        if (ORD & 4) { if (mode != 4) r = lds64(mp + recl); if (mode == 0) s0 = lds64(mp + srcl); }
        float z[4], y[4], t1[4], t2[4];
        mma1688z(z, az.x, az.y, rc.y);
        mma1688z(y, az.z, az.w, rc.y);
        uint32_t bt;
        asm("{.reg .pred p; .reg .b32 m; and.b32 m, %2, %3; setp.ne.u32 p, m, 0; selp.b32 %0, %1, 0, p;}" : "=r"(bt) : "r"(rc.x), "r"(bits0), "r"(smask));
        mma1688z(t1, at[0], at[1], bt);
        mma1688z(t2, at[2], at[3], bt);
        if (TP == 1) tick();
        const uint32_t T0 = pack2(t1[0], t1[2]), T1 = pack2(t2[0], t2[2]), T2 = pack2(t1[1], t1[3]), T3 = pack2(t2[1], t2[3]);
        const uint32_t R0 = pack2(silu_h(z[0]), silu_h(z[2]));
        if (TP == 2) tick();
        const uint32_t R1 = pack2(silu_h(z[1]), silu_h(z[3]));
        if (TP == 3) tick();
        const uint32_t R2 = pack2(silu_h(y[0]), silu_h(y[2])), R3 = pack2(silu_h(y[1]), silu_h(y[3]));
        if (TP == 4) tick();
        mma16816(acc[0], mul_lo(xa.x, R0), mul_hi(xa.z, R0), mul_lo(xa.y, R0), mul_hi(xa.w, R0), T0, T1);
        mma16816(acc[1], mul_lo(xb.x, R1), mul_hi(xb.z, R1), mul_lo(xb.y, R1), mul_hi(xb.w, R1), T2, T3);
        mma16816(acc[2], mul_lo(xc.x, R2), mul_hi(xc.z, R2), mul_lo(xc.y, R2), mul_hi(xc.w, R2), T0, T1);
        mma16816(acc[3], mul_lo(xd.x, R3), mul_hi(xd.z, R3), mul_lo(xd.y, R3), mul_hi(xd.w, R3), T2, T3);
        mp += STEPB; smask <<= 1;
    };
    auto putacc = [&](uint32_t* p) {
        p[0] = pack2(acc[0][0], acc[0][1]); p[32] = pack2(acc[0][2], acc[0][3]); p[64] = pack2(acc[2][0], acc[2][1]); p[96] = pack2(acc[2][2], acc[2][3]);
        p[256] = pack2(acc[1][0], acc[1][1]); p[288] = pack2(acc[1][2], acc[1][3]); p[320] = pack2(acc[3][0], acc[3][1]); p[352] = pack2(acc[3][2], acc[3][3]);
    };
    int ph = 0;
    auto phase_end = [&]() {
        az = *(const uint4*)(smem + SM_AZ + (ph + 1) * 512 + lane * 16);
        putacc(stash + (ph >> 1) * 512 + (ph & 1) * 128);
#pragma unroll
        for (int i = 0; i < 16; i++) acc[i / 4][i % 4] = 0.f;
        pbase += 256; mp = 0; smask = 1; ph++;
        dreg += tphase; dcur = dreg + tcur;
        WSTAMP(ph - 1);
    };
    uint32_t t0 = now;
    auto report = [&](uint32_t cand) {
        uint32_t b0, b1;
        asm volatile("ld.volatile.shared.v2.u32 {%0,%1}, [%2+16];" : "=r"(b0), "=r"(b1) : "r"(flg) : "memory");
        asm volatile("{.reg .pred p; setp.eq.u32 p, %2, 0; @p red.max.relaxed.gpu.global.u64 [%0], %1;}"
                     :: "l"(&gs->t0), "l"((((unsigned long long)b1 << 32) | b0) + (cand - b0)), "r"(lane) : "memory");
    };
    if (w == PW) {
        asm volatile("mov.u32 %0, %%globaltimer_lo;" : "=r"(now));
        now += PTOL - PTOL0;
    }
    auto relay = [&]() {
        uint32_t g0, g1, b0, b1;
        asm volatile("ld.volatile.shared.v2.u32 {%0,%1}, [%4+32]; ld.volatile.shared.v2.u32 {%2,%3}, [%4+16];"
                     : "=r"(g0), "=r"(g1), "=r"(b0), "=r"(b1) : "r"(flg) : "memory");
        const unsigned long long dg = (((unsigned long long)g1 << 32) | g0) - (((unsigned long long)b1 << 32) | b0);
        asm volatile("{.reg .pred p, q; setp.eq.u32 p, %1, 0; setp.lt.u64 q, %2, 30000; @q st.shared.u32 [%3+4], %4;\n"
                     "@p cp.async.cg.shared.global [%3+32], [%0], 16;}"
                     :: "l"(&gs->t0), "r"(lane), "l"(dg), "r"(flg), "r"(g0) : "memory");
    };
    const bool special = w == 0 || w == PW;
#pragma unroll 1
    for (int it = S - 1; it > 0; it--) {
        if (special) {
            if (w == 0) relay();
            else {
                const uint32_t cand = now - dl + tcur - PTOL;
                if ((int)(cand - t0) > 0) report(cand);
            }
        }
        dcur += t0 - tcur; tcur = t0;
#pragma unroll
        for (int k = 0; k < DS; k++) {
            if (k == DS - 1) asm volatile("ld.volatile.shared.u32 %0, [%1+4];" : "=r"(t0) : "r"(flg));
            step(k * SLOTB, 0, PEV >> k & 1);
            if (mp == mend || ((PEV >> k & 1) && now < dl)) {
                if (mp == mend) phase_end();
                if (k < DS - 1 && (RELAY >> k & 1) && w == 0) relay();
                asm volatile("{.reg .pred p; .reg .u32 d;\n"
                             "PACE_LOOP: mov.u32 d, %%globaltimer_lo; sub.u32 d, %0, d; setp.lt.u32 p, d, 32768; @p nanosleep.u32 %1; @p bra.uni PACE_LOOP;}"
                             :: "r"(dl), "n"(PSLEEP) : "memory");
            }
        }
    }
    __syncwarp();
    step(0, 1); step(SLOTB, 2); step(2 * SLOTB, 3); step(3 * SLOTB, 4);
    WSTAMP(3);

    {
        putacc((uint32_t*)(smem + SM_RING + 2 * SLOTB + w * 2048 + 512) + lane);
        const int wg = w >> 2, w4 = w & 3;
        int nd[8];
#pragma unroll
        for (int j = 0; j < 8; j++) { const int l = wg * 8 + j; nd[j] = order[(t >> 1) ? 79 - l : l]; asm volatile("" : "+r"(nd[j])); }
        const bool odd = t & 1;
        uint2* ob = (uint2*)out + (size_t)n0 * 128 + w4 * 16 + g + (odd ? 8 : 0);
        asm volatile("cp.async.wait_all;" ::: "memory");
        mbar_wait(mbarW, 0);
        asm volatile("fence.proxy.async.shared::cta;" ::: "memory");
        TSTAMP(26);
        bar_sync(2 + wg, 128);
        if ((tid & 127) == 0) {
            const uint32_t ticket = atomicAdd((uint32_t*)flag + 12, 1);
            int spins = 0;
            while (flag[13] + LEAD < ticket && ++spins < (1 << 16)) {}
        }
        bar_sync(2 + wg, 128);
        TSTAMP(27);
        const uint64_t descA0 = (uint64_t)(((sb + SM_RING) & 0x3FFFF) >> 4) | ((uint64_t)1 << 16) | ((uint64_t)(1024 >> 4) << 32) | ((uint64_t)1 << 62);
        const uint64_t descB0 = (uint64_t)(((sb + SM_RING + SLOTB + wg * 8192) & 0x3FFFF) >> 4) | ((uint64_t)(128 >> 4) << 16) | ((uint64_t)(1024 >> 4) << 32);
        float d[2][32];
        asm volatile("wgmma.fence.sync.aligned;" ::: "memory");
#pragma unroll
        for (int mt = 0; mt < 2; mt++) {
#pragma unroll
            for (int ks = 0; ks < 8; ks++) {
                const uint64_t da = descA0 + (uint64_t)((ks * 2048 + mt * 16384) >> 4), db = descB0 + (uint64_t)(((ks & 3) * 256 + (ks >> 2) * SLOTB) >> 4);
                asm volatile("{.reg .pred p; setp.ne.b32 p, %34, 0;\n"
                    "wgmma.mma_async.sync.aligned.m64n64k16.f32.bf16.bf16 "
                    "{%0,%1,%2,%3,%4,%5,%6,%7,%8,%9,%10,%11,%12,%13,%14,%15,%16,%17,%18,%19,%20,%21,%22,%23,%24,%25,%26,%27,%28,%29,%30,%31}, %32, %33, p, 1, 1, 1, 1;}"
                    : "+f"(d[mt][0]), "+f"(d[mt][1]), "+f"(d[mt][2]), "+f"(d[mt][3]), "+f"(d[mt][4]), "+f"(d[mt][5]), "+f"(d[mt][6]), "+f"(d[mt][7]),
                      "+f"(d[mt][8]), "+f"(d[mt][9]), "+f"(d[mt][10]), "+f"(d[mt][11]), "+f"(d[mt][12]), "+f"(d[mt][13]), "+f"(d[mt][14]), "+f"(d[mt][15]),
                      "+f"(d[mt][16]), "+f"(d[mt][17]), "+f"(d[mt][18]), "+f"(d[mt][19]), "+f"(d[mt][20]), "+f"(d[mt][21]), "+f"(d[mt][22]), "+f"(d[mt][23]),
                      "+f"(d[mt][24]), "+f"(d[mt][25]), "+f"(d[mt][26]), "+f"(d[mt][27]), "+f"(d[mt][28]), "+f"(d[mt][29]), "+f"(d[mt][30]), "+f"(d[mt][31])
                    : "l"(da), "l"(db), "r"(ks));
            }
            asm volatile("wgmma.commit_group.sync.aligned;" ::: "memory");
            if (mt == RELAT - 1) asm volatile("{.reg .pred p; setp.eq.u32 p, %1, 0; @p red.shared.add.u32 [%0+52], 1;}" :: "r"(flg), "r"(tid & 127) : "memory");
        }
#pragma unroll
        for (int mt = 0; mt < 2; mt++) {
            if (mt == 0) asm volatile("wgmma.wait_group.sync.aligned 1;" ::: "memory");
            else asm volatile("wgmma.wait_group.sync.aligned 0;" ::: "memory");
            if (RELAT == 0 && mt == 0 && (tid & 127) == 0) atomicAdd((uint32_t*)flag + 13, 1);
            TSTAMP(23 + mt);
#pragma unroll
            for (int i = 0; i < 32; i++) asm volatile("" : "+f"(d[mt][i]) :: "memory");
#pragma unroll
            for (int j = 0; j < 8; j++) {
                const uint32_t v0 = pack2(d[mt][4 * j], d[mt][4 * j + 1]), v1 = pack2(d[mt][4 * j + 2], d[mt][4 * j + 3]);
                const uint32_t rv = __shfl_xor_sync(0xffffffff, odd ? v0 : v1, 1);
                if (nd[j] < nn) ob[nd[j] * 128 + mt * 64] = odd ? make_uint2(rv, v1) : make_uint2(v0, rv);
            }
        }
    }
    TSTAMP(8);
}

}

extern "C" void kernel_launch(void* const* d_in, const int* in_sizes, int n_in, void* d_out, int out_size) {
    (void)in_sizes; (void)n_in; (void)out_size;
    cudaFuncSetAttribute(tfn_kernel, cudaFuncAttributeMaxDynamicSharedMemorySize, SM_TOTAL);
    Scratch* gs = nullptr;
    cudaGetSymbolAddress((void**)&gs, g_scratch);
    cudaLaunchConfig_t cfg = {};
    cfg.gridDim = dim3(NB); cfg.blockDim = dim3(NT); cfg.dynamicSmemBytes = SM_TOTAL; cfg.stream = cudaStreamPerThread;
    cudaLaunchAttribute at[1];
    at[0].id = cudaLaunchAttributeCooperative; at[0].val.cooperative = 1;
    cfg.attrs = at; cfg.numAttrs = 1;
    cudaLaunchKernelEx(&cfg, tfn_kernel, (const unsigned char*)d_in[0], (const int4*)d_in[1], (const int4*)d_in[2],
                       (const uint4*)d_in[3], (const uint4*)d_in[4], (const uint16_t*)d_in[5], (const uint16_t*)d_in[6],
                       (const uint4*)d_in[7], (uint32_t*)d_out, gs);
}
```

```cpp
#include <cuda_runtime.h>
#include <cuda_bf16.h>
#include <stdint.h>

#define VOL
#define DMODE 1
#define T0K 2
#define GSLEEP 0
#define ADELAY 0
#define ABL 0
namespace {

constexpr int NN = 10000;
constexpr int NE = 320000;
constexpr int NB = 132;
constexpr int NW = 20;
constexpr int NT = NW * 32;
constexpr int CW = NW - 1;
#define PWARP 10
constexpr int PW = PWARP;
constexpr int NPB = 76;
constexpr int CELL = 48;
constexpr int RCH = 2880;
constexpr int CAP = 19;
constexpr int DS = 4;
constexpr int STEPB = 160;
constexpr int NE4 = NE / 4;
constexpr int NPIECE = NB * 8;
constexpr int KB = 320, KN = 32 * KB;
constexpr uint32_t F_WRAP = 1;

constexpr int SLOTB = NW * 2048;
constexpr int SM_RING = 0;
constexpr int SM_META = SM_RING + DS * SLOTB;
constexpr int SM_AZ = SM_META + NW * CAP * STEPB;
constexpr int SM_MISC = SM_AZ + 2048;
constexpr int SM_TOTAL = SM_MISC + 2048;
constexpr int SM_STAGE = SM_RING;
constexpr int SM_HIST = SM_RING + 25600;
constexpr int SM_POS = SM_RING;
constexpr int SM_SMALL = SM_HIST + 13056;
constexpr int SM_LIST = SM_RING + SLOTB;
constexpr int SM_ROUT = SM_RING + 2 * SLOTB;
constexpr int SM_RECS = SM_RING + 3 * SLOTB;
constexpr int SM_RAWY = SM_META;
constexpr int SM_RAWE = SM_RAWY + 608 * 32;
constexpr int SM_KEYS = SM_RAWE + 608 * 32;
static_assert(SM_TOTAL <= 232448 && SM_KEYS + NPIECE * 16 <= SM_AZ, "smem");
static_assert(SM_RECS + NB * CELL * 16 + 16 <= SM_AZ && SM_KEYS + NPIECE * 16 <= SM_RECS + NB * CELL * 16 && SM_SMALL + 1152 <= SLOTB && DS == 4, "smem");

struct Scratch {
    uint4 keys[NB * NPIECE];
    uint4 recs[NB * RCH];
    uint4 stash[NB * NW * 256];
    unsigned bar[4];
    unsigned long long t0, pad;
};
__device__ Scratch g_scratch;
#define TSTAMP(i)
#define TSTAMPC(i)
#define WSTAMP(i)

__device__ __forceinline__ void mma16816(float* d, uint32_t a0, uint32_t a1, uint32_t a2, uint32_t a3, uint32_t b0, uint32_t b1) {
    asm VOL("mma.sync.aligned.m16n8k16.row.col.f32.bf16.bf16.f32 {%0,%1,%2,%3}, {%4,%5,%6,%7}, {%8,%9}, {%0,%1,%2,%3};"
        : "+f"(d[0]), "+f"(d[1]), "+f"(d[2]), "+f"(d[3]) : "r"(a0), "r"(a1), "r"(a2), "r"(a3), "r"(b0), "r"(b1));
}
__device__ __forceinline__ void mma1688z(float* d, uint32_t a0, uint32_t a1, uint32_t b0) {
    asm VOL("mma.sync.aligned.m16n8k8.row.col.f32.bf16.bf16.f32 {%0,%1,%2,%3}, {%4,%5}, {%6}, {%7,%7,%7,%7};"
        : "=f"(d[0]), "=f"(d[1]), "=f"(d[2]), "=f"(d[3]) : "r"(a0), "r"(a1), "r"(b0), "f"(0.f));
}
__device__ __forceinline__ uint32_t pack2(float lo, float hi) {
    uint32_t r; asm VOL("cvt.rn.bf16x2.f32 %0, %1, %2;" : "=r"(r) : "f"(hi), "f"(lo)); return r;
}
__device__ __forceinline__ float silu_h(float h) {
    float t; asm VOL("tanh.approx.f32 %0, %1;" : "=f"(t) : "f"(h)); return fmaf(h, t, h);
}
__device__ __forceinline__ uint32_t mul_lo(uint32_t v, uint32_t r) {
    __nv_bfloat162 a = *(__nv_bfloat162*)&v, b = *(__nv_bfloat162*)&r; __nv_bfloat162 c = __hmul2(a, __low2bfloat162(b)); return *(uint32_t*)&c;
}
__device__ __forceinline__ uint32_t mul_hi(uint32_t v, uint32_t r) {
    __nv_bfloat162 a = *(__nv_bfloat162*)&v, b = *(__nv_bfloat162*)&r; __nv_bfloat162 c = __hmul2(a, __high2bfloat162(b)); return *(uint32_t*)&c;
}
__device__ __forceinline__ uint2 lds64(uint32_t a) {
    uint2 r; asm volatile("ld.shared.v2.u32 {%0,%1}, [%2];" : "=r"(r.x), "=r"(r.y) : "r"(a)); return r;
}
__device__ __forceinline__ uint4 lds128(uint32_t a) {
    uint4 r; asm volatile("ld.shared.v4.u32 {%0,%1,%2,%3}, [%4];" : "=r"(r.x), "=r"(r.y), "=r"(r.z), "=r"(r.w) : "r"(a) : "memory"); return r;
}
__device__ __forceinline__ void bar_sync(int id, int n) { asm volatile("bar.sync %0, %1;" :: "r"(id), "r"(n) : "memory"); }
__device__ __forceinline__ void bar_arrive(int id, int n) { asm volatile("bar.arrive %0, %1;" :: "r"(id), "r"(n) : "memory"); }
__device__ __forceinline__ void mbar_wait(uint32_t bar, uint32_t ph) {
    uint32_t done; int spins = 0;
    do {
        asm volatile("{.reg .pred p; mbarrier.try_wait.parity.shared.b64 p, [%1], %2; selp.u32 %0,1,0,p;}" : "=r"(done) : "r"(bar), "r"(ph) : "memory");
    } while (!done && ++spins < (1 << 22));
}
__device__ __forceinline__ unsigned gbar_read(const unsigned* ctr) {
    unsigned v; asm volatile("ld.relaxed.gpu.global.u32 %0, [%1];" : "=r"(v) : "l"(ctr) : "memory");
    return v;
}
__device__ __forceinline__ void gbar_arrive(unsigned* ctr) {
    asm volatile("red.add.release.gpu.global.u32 [%0], 1;" :: "l"(ctr) : "memory");
}
__device__ __forceinline__ bool gbar_wait(const unsigned* ctr, unsigned target) {
    unsigned v; int spins = 0;
    while (true) {
        asm volatile("ld.acquire.gpu.global.u32 %0, [%1];" : "=r"(v) : "l"(ctr) : "memory");
        if ((int)(v - target) >= 0 || ++spins > (1 << 22)) break;
        if (GSLEEP) __nanosleep(GSLEEP);
    }
    return (int)(v - target) >= 0;
}
__device__ __forceinline__ int chunk_start4(int c) { return (c * NE4) / NB; }
__device__ __forceinline__ float bf2f(uint32_t h) { return __uint_as_float(h << 16); }

__device__ __noinline__ void slow_path(unsigned char* smem, int n0, int nn, const uint16_t* x, const int* src, const int* dst,
                                       const uint16_t* Y, const uint16_t* ef, const uint16_t* w_rad, const uint16_t* cg,
                                       const uint16_t* w_mix, __nv_bfloat16* out) {
    float* agg = (float*)smem;
    const int tid = threadIdx.x, lane = tid & 31, w = tid >> 5;
    bar_sync(1, NT);
    for (int i = tid; i < NPB * 512; i += NT) agg[i] = 0.f;
    bar_sync(1, NT);
    for (int e0 = w * 32; e0 < NE; e0 += NT) {
        int dl = dst[e0 + lane] - n0;
        unsigned m = __ballot_sync(0xffffffff, dl >= 0 && dl < nn);
        while (m) {
            int l = __ffs(m) - 1; m &= m - 1;
            int e = e0 + l, d = __shfl_sync(0xffffffff, dl, l), s = src[e];
            float T[16];
            for (int i = 0; i < 4; i++) for (int o = 0; o < 4; o++) {
                float a = 0.f;
                for (int f = 0; f < 4; f++) a += bf2f(Y[e * 4 + f]) * bf2f(cg[i * 16 + f * 4 + o]);
                T[i * 4 + o] = a;
            }
            for (int k = 0; k < 4; k++) {
                int c = lane + 32 * k;
                float z = 0.f;
                for (int j = 0; j < 4; j++) z += bf2f(ef[e * 4 + j]) * bf2f(w_rad[j * 128 + c]);
                float R = z / (1.f + __expf(-z));
                for (int o = 0; o < 4; o++) {
                    float a = 0.f;
                    for (int i = 0; i < 4; i++) a += bf2f(x[(size_t)s * 512 + c * 4 + i]) * T[i * 4 + o];
                    atomicAdd(&agg[d * 512 + c * 4 + o], R * a);
                }
            }
        }
    }
    bar_sync(1, NT);
    for (int i = tid; i < nn * 512; i += NT) {
        int n = i >> 9, d = (i >> 2) & 127, o = i & 3;
        float a = 0.f;
        for (int c = 0; c < 128; c++) a += agg[n * 512 + c * 4 + o] * bf2f(w_mix[c * 128 + d]);
        out[(size_t)(n0 + n) * 512 + (i & 511)] = __float2bfloat16(a);
    }
}

#define PACE 24000
#define YDELAY 300
#define TP 0
#define BFENCE 0
#define ASYM 0
#define KFIRST 0
#define EPI 2
#define LEAD 0
#define RELAT 2
#define POFF 1800
#define RELAY 2
#define PSLEEP 32
#define PTOL0 300
#define PTOL 800
__global__ void __launch_bounds__(NT, 1)
tfn_kernel(const unsigned char* __restrict__ x, const int4* __restrict__ src4, const int4* __restrict__ dst4,
           const uint4* __restrict__ Y, const uint4* __restrict__ ef, const uint16_t* __restrict__ w_rad,
           const uint16_t* __restrict__ cg, const uint4* __restrict__ w_mix, uint32_t* __restrict__ out, Scratch* __restrict__ gs) {
    extern __shared__ __align__(1024) unsigned char smem[];
    const uint32_t sb = (uint32_t)__cvta_generic_to_shared(smem);
    const int b = blockIdx.x, tid = threadIdx.x, lane = tid & 31, g = lane >> 2, t = lane & 3;
    const int w = __shfl_sync(0xffffffff, tid >> 5, 0);
    uint32_t* stage = (uint32_t*)(smem + SM_STAGE);
    uint32_t* hist = (uint32_t*)(smem + SM_HIST);
    uint32_t* cnt = (uint32_t*)(smem + SM_MISC);
    uint32_t* deg = cnt + 136;
    uint32_t* order = deg + 104;
    uint32_t* cnt2 = order + 80;
    volatile uint32_t* flag = cnt2 + 136;
    const uint32_t mbarK = sb + SM_MISC + 1920, mbarR = mbarK + 8, mbarW = mbarK + 16;
    const int n0 = b * NPB, nn = min(NPB, NN - n0);
    TSTAMP(0);

    const int c0 = chunk_start4(b), c1 = chunk_start4(b + 1);
    const bool has4 = c0 + tid < c1;
    int4 d4 = make_int4(0, 0, 0, 0), s4 = d4;
    if (has4) { d4 = __ldg(dst4 + c0 + tid); s4 = __ldg(src4 + c0 + tid); }
    unsigned tgt = 0;
    if (tid == NT - 1) {
        tgt = gbar_read(&gs->bar[0]);
        asm volatile("mbarrier.init.shared.b64 [%0], 1;" :: "r"(mbarK));
        asm volatile("mbarrier.init.shared.b64 [%0], 1;" :: "r"(mbarR));
        asm volatile("mbarrier.init.shared.b64 [%0], 512;" :: "r"(mbarW));
        asm volatile("fence.mbarrier_init.release.cluster;" ::: "memory");
        flag[0] = 0; flag[12] = 0; flag[13] = 0; flag[15] = 0;
    }
    if (w == CW) {
        asm volatile("cp.async.cg.shared.global [%0], [%1], 16;" :: "r"(sb + SM_SMALL + lane * 16), "l"(w_rad + lane * 8) : "memory");
        asm volatile("cp.async.cg.shared.global [%0], [%1], 16;" :: "r"(sb + SM_SMALL + 512 + lane * 16), "l"(w_rad + 256 + lane * 8) : "memory");
        if (lane < 8) asm volatile("cp.async.cg.shared.global [%0], [%1], 16;" :: "r"(sb + SM_SMALL + 1024 + lane * 16), "l"(cg + lane * 8) : "memory");
    }
    ((uint4*)hist)[tid] = make_uint4(0, 0, 0, 0);
    {
        const uint32_t dk = (80 + b % 22) * KN + (b & 31) * KB;
#pragma unroll
        for (int j = 0; j < 3; j++) if (tid + j * NT < NB * CELL / 4) ((uint4*)stage)[tid + j * NT] = make_uint4(dk, dk, dk, dk);
    }
    if (tid < 136) cnt[tid] = 0;
    if (tid == 0) { *(uint4*)(smem + SM_MISC + 1824 + 32) = make_uint4(0, 0, 0, 0); *(uint4*)(smem + SM_RECS + NB * CELL * 16) = make_uint4(0, 0, 0, 0); }
    if (tid < 80) { deg[tid] = 127 - tid; order[tid] = tid; }
    __syncthreads();
    TSTAMP(9);
    if (tid == 64) {
        if (YDELAY) __nanosleep(YDELAY);
        asm volatile("mbarrier.arrive.expect_tx.shared.b64 _, [%0], %1;" :: "r"(mbarR), "r"((c1 - c0) * 64) : "memory");
        asm volatile("cp.async.bulk.shared::cluster.global.mbarrier::complete_tx::bytes [%0], [%1], %2, [%3];"
                     :: "r"(sb + SM_RAWY), "l"(Y + 2 * c0), "r"((c1 - c0) * 32), "r"(mbarR) : "memory");
        asm volatile("cp.async.bulk.shared::cluster.global.mbarrier::complete_tx::bytes [%0], [%1], %2, [%3];"
                     :: "r"(sb + SM_RAWE), "l"(ef + 2 * c0), "r"((c1 - c0) * 32), "r"(mbarR) : "memory");
    }

    uint32_t bin[4] = {0, 0, 0, 0}, slot[4] = {0, 0, 0, 0};
    if (has4) {
        const uint32_t dd[4] = {(uint32_t)d4.x, (uint32_t)d4.y, (uint32_t)d4.z, (uint32_t)d4.w}, ss[4] = {(uint32_t)s4.x, (uint32_t)s4.y, (uint32_t)s4.z, (uint32_t)s4.w};
#pragma unroll
        for (int k = 0; k < 4; k++) { bin[k] = dd[k] / NPB; slot[k] = atomicAdd(&cnt[bin[k]], 1); }
#pragma unroll
        for (int k = 0; k < 4; k++) stage[bin[k] * CELL + min(slot[k], CELL - 1)] = (dd[k] - bin[k] * NPB) * KN + ss[k];
    }
    if (w == CW) {
        if (tid == NT - 1) { tgt = tgt / NB + 1; flag[14] = (tgt & 1) << 31; tgt *= NB; }
        asm volatile("cp.async.wait_all;" ::: "memory");
    }
    bar_sync(1, NT);
    TSTAMP(1);
    const uint32_t tag = flag[14];
#pragma unroll
    for (int j = 0; j < 2; j++) {
        const int i = tid + j * NT;
        if (i < NPIECE) {
            const uint2 sa = *(const uint2*)(stage + i * 6), sc = *(const uint2*)(stage + i * 6 + 2);
            uint2 se = *(const uint2*)(stage + i * 6 + 4);
            const uint32_t cf = cnt[i >> 3], cn = min(cf, 63u);
            if ((i & 7) == 7) {
                const uint32_t al = cf > CELL - 8 ? 7 : 0;
                uint32_t o;
                asm volatile("atom.shared.add.u32 %0, [%1], %2;" : "=r"(o) : "r"(sb + SM_MISC + 1824 + 60), "r"(cf + al) : "memory");
                se.y = (o + al) & ~al;
                cnt2[i >> 3] = se.y;
            }
            asm volatile("{.reg .b64 lo, hi; mov.b64 lo, {%1,%2}; mov.b64 hi, {%3,%4}; st.relaxed.gpu.global.v2.b64 [%0], {lo, hi};}"
                         :: "l"(gs->keys + ((i >> 3) * NB + b) * 8 + ((i ^ b) & 7)),
                            "r"(sa.x | (se.x << 20)), "r"(sa.y | ((se.x >> 12) << 20) | ((cn & 7) << 28) | tag),
                            "r"(sc.x | (se.y << 20)), "r"(sc.y | ((se.y >> 12) << 20) | ((cn >> 3) << 28) | tag) : "memory");
        }
    }
    bar_sync(1, NT);
    if (tid == NT - 1) {
        TSTAMPC(10);
        asm volatile("red.add.relaxed.gpu.global.u32 [%0], 1;" :: "l"(&gs->bar[0]) : "memory");
        asm volatile("mbarrier.arrive.expect_tx.shared.b64 _, [%0], %1;" :: "r"(mbarK), "r"(NPIECE * 16) : "memory");
        if (ADELAY) mbar_wait(mbarR, 0);
        gbar_wait(&gs->bar[0], tgt);
        TSTAMPC(13);
        asm volatile("fence.proxy.async.global;" ::: "memory");
        asm volatile("cp.async.bulk.shared::cluster.global.mbarrier::complete_tx::bytes [%0], [%1], %2, [%3];"
                 :: "r"(sb + SM_KEYS), "l"(gs->keys + b * NPIECE), "r"(NPIECE * 16), "r"(mbarK) : "memory");
    }
    __syncwarp();
    uint32_t at[4];
    {
        const int o = g & 3, f = 2 * (t & 1);
#pragma unroll
        for (int i = 0; i < 4; i++) {
            const uint16_t* cp = (const uint16_t*)(smem + SM_SMALL + 1024) + i * 16 + f * 4 + o;
            at[i] = (t >> 1) == (g >> 2) ? cp[0] | ((uint32_t)cp[4] << 16) : 0;
        }
    }

    const int q = lane >> 3, c = lane & 7;
    const uint32_t ring0 = sb + SM_RING + w * 2048;
    uint32_t wdst = ring0 + q * 128 + ((c + 2 * q) & 7) * 16;
    uint32_t rsrc = ring0 + t * 128 + ((g + 2 * t) & 7) * 16;
    uint32_t recl = sb + SM_META + w * (CAP * STEPB) + g * 16 + (t & 1) * 8, srcl = sb + SM_META + w * (CAP * STEPB) + 128 + q * 8;
    uint32_t flg = sb + SM_MISC + (136 + 104 + 80 + 136) * 4;
    asm volatile("" : "+r"(wdst), "+r"(rsrc), "+r"(recl), "+r"(srcl), "+r"(flg));
    uint32_t key[2][6], ha[2][6], rk[2][6], kidx[2], ka[2];
    int nk[2];
#pragma unroll
    for (int j = 0; j < 2; j++) {
        const int i0 = j ? 2 * 608 - 1 - tid : tid, i = min(i0, NPIECE - 1), r = i / NB, cc = i - r * NB;
        ka[j] = sb + SM_KEYS + (cc * 8 + ((r ^ cc) & 7)) * 16;
        kidx[j] = (cc * CELL + r * 6) << 17;
        nk[j] = i0 < NPIECE && w < CW ? -6 * r : -1000;
    }
    asm volatile("" : "+r"(at[0]), "+r"(at[1]), "+r"(at[2]), "+r"(at[3]), "+r"(ka[0]), "+r"(ka[1]), "+r"(kidx[0]), "+r"(kidx[1]), "+r"(nk[0]), "+r"(nk[1]));
    if (w == CW) {
        __syncwarp();
        bar_sync(7, NT);
        if (tid == NT - 1) {
            TSTAMPC(11);
            asm volatile("cp.async.bulk.global.shared::cta.bulk_group [%0], [%1], %2;"
                         :: "l"(gs->recs + b * RCH), "r"(sb + SM_ROUT), "r"(((flag[15] + 1) & ~1u) * 16) : "memory");
            asm volatile("cp.async.bulk.commit_group; cp.async.bulk.wait_group 0;" ::: "memory");
            TSTAMPC(14);
            asm volatile("red.add.relaxed.gpu.global.u32 [%0], 1;" :: "l"(&gs->bar[1]) : "memory");
            TSTAMPC(15);
        }
    } else {
        if (w < 8) {
            const uint32_t* wp = (const uint32_t*)(smem + SM_SMALL) + (t & 1) * 128 + 8 * w + g;
            const uint32_t wr0 = t < 2 ? wp[0] : 0, wr1 = t < 2 ? wp[64] : 0;
            *(uint2*)(smem + SM_AZ + (w >> 1) * 512 + lane * 16 + (w & 1) * 8) =
                make_uint2(pack2(0.5f * bf2f(wr0 & 0xFFFF), 0.5f * bf2f(wr1 & 0xFFFF)), pack2(0.5f * bf2f(wr0 >> 16), 0.5f * bf2f(wr1 >> 16)));
        }
        const bool sw = g & 1;
        uint32_t rp[4];
#pragma unroll
        for (int k = 0; k < 4; k++) rp[k] = cnt2[bin[k]] + slot[k];
        uint4* ro = (uint4*)(smem + SM_ROUT);
        uint4 *p0 = ro + (sw ? rp[2] : rp[0]), *p1 = ro + (sw ? rp[3] : rp[1]), *p2 = ro + (sw ? rp[0] : rp[2]), *p3 = ro + (sw ? rp[1] : rp[3]);
        const uint32_t ya = sb + SM_RAWY + tid * 32 + (sw ? 16 : 0);
        mbar_wait(mbarR, 0);
        TSTAMP(18);
        if (has4) {
            const uint4 y0 = lds128(ya), e0 = lds128(ya + (SM_RAWE - SM_RAWY)), y1 = lds128(ya ^ 16), e1 = lds128((ya ^ 16) + (SM_RAWE - SM_RAWY));
            *p0 = make_uint4(y0.x, e0.x, y0.y, e0.y); *p1 = make_uint4(y0.z, e0.z, y0.w, e0.w);
            *p2 = make_uint4(y1.x, e1.x, y1.y, e1.y); *p3 = make_uint4(y1.z, e1.z, y1.w, e1.w);
        }
        asm volatile("fence.proxy.async.shared::cta;" ::: "memory");
        bar_arrive(7, NT);
    }
    __syncwarp();
    TSTAMP(2);

    if (w < CW) {
        mbar_wait(mbarK, 0);
        TSTAMP(3);
        uint4 v[2] = {lds128(ka[0]), lds128(ka[1])};
#pragma unroll
        for (int j = 0; j < 2; j++) {
            int spins = 0;
            while ((int)((v[j].y ^ tag) | (v[j].w ^ tag)) < 0) {
                asm volatile("{.reg .b64 lo, hi; ld.relaxed.gpu.global.v2.b64 {lo, hi}, [%4]; mov.b64 {%0,%1}, lo; mov.b64 {%2,%3}, hi;}"
                             : "=r"(v[j].x), "=r"(v[j].y), "=r"(v[j].z), "=r"(v[j].w) : "l"((const unsigned char*)(gs->keys + b * NPIECE) + (ka[j] - sb - SM_KEYS)) : "memory");
                if (++spins > (1 << 20)) { *flag = 1; break; }
            }
            const uint32_t hc = ((v[j].y >> 28) & 7) | ((v[j].w >> 25) & 0x38);
            if (j == 1 && nk[j] == -42) {
                cnt[kidx[j] / (CELL << 17)] = hc | ((v[j].z >> 20) << 8);
                v[j].w |= ((80 * KN) >> 12) << 20;
            }
            if (hc > CELL - 1) *flag = 1;
            nk[j] += hc;
            if (nk[j] > 0) {
                key[j][0] = v[j].x & 0xFFFFF; key[j][1] = v[j].y & 0xFFFFF; key[j][2] = v[j].z & 0xFFFFF; key[j][3] = v[j].w & 0xFFFFF;
                key[j][4] = (v[j].x >> 20) | ((v[j].y >> 8) & 0xFF000); key[j][5] = (v[j].z >> 20) | ((v[j].w >> 8) & 0xFF000);
#pragma unroll
                for (int u = 0; u < 6; u++) {
                    ha[j][u] = __umulhi(key[j][u], 0xFFFFFFFFu / KB + 1);
                    rk[j][u] = atomicAdd(&hist[ha[j][u]], 1);
                    atomicAdd(&deg[ha[j][u] >> 5], 128);
                }
            }
        }
        bar_sync(9, NT - 32);
        TSTAMP(20);
#pragma unroll
        for (int j = 0; j < 2; j++) kidx[j] += ((cnt[kidx[j] / (CELL << 17)] >> 8) & 7) << 17;
        const int n = tid >> 3, sub = tid & 7;
        const uint32_t me = deg[n];
        int r = 0;
#pragma unroll
        for (int k = 0; k < 5; k++) { const uint2 dd = *(const uint2*)(deg + sub * 10 + 2 * k); r += (dd.x > me) + (dd.y > me); }
        r += __shfl_xor_sync(0xffffffff, r, 1); r += __shfl_xor_sync(0xffffffff, r, 2); r += __shfl_xor_sync(0xffffffff, r, 4);
        if (sub == 0) order[r] = n;
    }
    bar_sync(1, NT);
    TSTAMP(22);
    uint32_t len2;
    {
        const uint2 na = *(const uint2*)(order + 2 * w), nb = *(const uint2*)(order + 78 - 2 * w);
        const uint32_t ia0 = na.x * 32 + lane, ib0 = nb.y * 32 + lane, ia1 = na.y * 32 + lane, ib1 = nb.x * 32 + lane;
        const uint32_t ca = hist[ia0] + (hist[ia1] << 16), cab = ca + hist[ib0] + (hist[ib1] << 16);
        uint32_t inc = cab;
#pragma unroll
        for (int o = 1; o < 32; o <<= 1)
            asm volatile("{.reg .pred p; .reg .u32 u; shfl.sync.up.b32 u|p, %0, %1, 0, 0xffffffff; @p add.u32 %0, %0, u;}" : "+r"(inc) : "r"(o));
        const uint32_t ea = inc - cab, eb = ea + ca, base = sb + SM_LIST + w * 2048;
        uint2* pos = (uint2*)(smem + SM_POS);
        pos[ia0] = make_uint2(base + (ea & 0xFFFF) * 8, na.x * (0u - 4 * KN));
        pos[ib0] = make_uint2(base + (eb & 0xFFFF) * 8, nb.y * (0u - 4 * KN) + 0x10000);
        pos[ia1] = make_uint2(base + 4 + (ea >> 16) * 8, na.y * (0u - 4 * KN));
        pos[ib1] = make_uint2(base + 4 + (eb >> 16) * 8, nb.x * (0u - 4 * KN) + 0x10000);
        if (max(inc & 0xFFFF, inc >> 16) > 4 * CAP) *flag = 1;
        len2 = __shfl_sync(0xffffffff, inc, 31);
    }
    uint32_t ci = cnt[min(w + NW * lane, NB)];
    ci = ((((w + NW * lane) * (RCH / 8) + (ci >> 11)) << 8) | (ci & 0xFF)) + ((ci >> 8) & 7);
    if (w == CW) {
        bar_arrive(9, NT);
        if (tid == NT - 1) { if (!gbar_wait(&gs->bar[1], tgt)) *flag = 1; TSTAMPC(17); }
        __syncwarp();
    } else {
        bar_sync(9, NT);
        TSTAMP(21);
        const uint32_t over = *flag;
#pragma unroll
        for (int j = 0; j < 2; j++) {
            if (nk[j] > 0) {
                uint2 h[6];
#pragma unroll
                for (int u = 0; u < 6; u++) h[u] = lds64(sb + SM_POS + ha[j][u] * 8);
                if (over) nk[j] = 0;
#pragma unroll
                for (int u = 0; u < 6; u++)
                    asm volatile("{.reg .pred p; setp.gt.s32 p, %2, %3; @p st.shared.u32 [%0], %1;}"
                                 :: "r"(h[u].x + rk[j][u] * 8), "r"(key[j][u] * 4 + h[u].y + (kidx[j] + (u << 17))), "r"(nk[j]), "r"(u) : "memory");
            }
        }
    }
    bar_sync(1, NT);
    TSTAMP(4);
    if (*flag) {
        slow_path(smem, n0, nn, (const uint16_t*)x, (const int*)src4, (const int*)dst4, (const uint16_t*)Y, (const uint16_t*)ef, w_rad, cg,
                  (const uint16_t*)w_mix, (__nv_bfloat16*)out);
        return;
    }
    {
        const uint4* gp = gs->recs + lane;
        const uint32_t sp = sb + SM_RECS + (w * CELL + lane) * 16;
#pragma unroll
        for (int j = 0; j < 7; j++) {
            const uint32_t cj = __shfl_sync(0xffffffff, ci, j);
            asm volatile("{.reg .pred p; setp.lt.u32 p, %2, %3; @p cp.async.cg.shared.global [%0], [%1], 16;}"
                         :: "r"(sp + j * (NW * CELL * 16)), "l"(gp + (size_t)(cj >> 8) * 8), "r"(lane), "r"(cj & 0xFF) : "memory");
        }
        for (uint32_t m = __ballot_sync(0xffffffff, (ci & 0xFF) > 32); m; m &= m - 1) {
            const int j = __ffs(m) - 1;
            const uint32_t cj = __shfl_sync(0xffffffff, ci, j);
            if (lane + 32 < (cj & 0xFF))
                asm volatile("cp.async.cg.shared.global [%0], [%1], 16;" :: "r"(sp + j * (NW * CELL * 16) + 512), "l"(gp + (size_t)(cj >> 8) * 8 + 32) : "memory");
        }
        asm volatile("cp.async.commit_group;" ::: "memory");
    }
    const int S = __shfl_sync(0xffffffff, max((int)(max(len2 & 0xFFFF, len2 >> 16) + 3) >> 2, DS + 1), 0);
    const int mylen = (lane & 1) ? len2 >> 16 : len2 & 0xFFFF;
    constexpr int NRAW = (CAP + 3) / 4;
    uint32_t bits0 = 0, raw[NRAW];
    unsigned char* meta = smem + SM_META + w * (CAP * STEPB);
#pragma unroll
    for (int k = 0; k < NRAW; k++) raw[k] = mylen ? ((uint32_t*)(smem + SM_LIST + w * 2048))[min(k * 16 + (lane >> 1), mylen - 1) * 2 + (lane & 1)] : 4 * n0;
    const uint32_t sv0 = raw[0] & 0xFFFF;
    const unsigned char* pbase = x + c * 16;
    auto cpa2 = [&](uint32_t dstp, uint32_t sv) {
        asm volatile("cp.async.cg.shared.global [%0], [%1], 16; cp.async.cg.shared.global [%0+1024], [%1+128], 16;"
                     :: "r"(dstp), "l"(pbase + (size_t)sv * 256) : "memory");
    };
    auto fill = [&](int i) {
        cpa2(wdst + i * SLOTB, __shfl_sync(0xffffffff, sv0, 8 * i + 2 * q)); cpa2(wdst + i * SLOTB + 512, __shfl_sync(0xffffffff, sv0, 8 * i + 2 * q + 1));
        asm volatile("cp.async.commit_group;" ::: "memory");
    };
    fill(0);
    TSTAMP(5);
    if (w == 0) {
        unsigned long long tbase;
        asm volatile("mov.u64 %0, %%globaltimer;" : "=l"(tbase));
        tbase += POFF;
        flag[1] = (uint32_t)tbase; flag[4] = (uint32_t)tbase; flag[5] = (uint32_t)(tbase >> 32);
        if (lane == 0) {
            asm volatile("red.max.relaxed.gpu.global.u64 [%0], %1;" :: "l"(&gs->t0), "l"(tbase) : "memory");
            if (b < 128) asm volatile("cp.async.bulk.prefetch.L2.global [%0], 256;" :: "l"(w_mix + b * 16));
        }
    }
    uint32_t ra[NRAW];
#pragma unroll
    for (int k = 0; k < NRAW; k++) {
        const uint32_t m = (__ballot_sync(0xffffffff, raw[k] & 0x10000) >> g) & 0x01010101u;
        bits0 |= ((m * 0x10204080u) >> 28) << (4 * k);
        ra[k] = sb + SM_RECS + (k * 16 + (lane >> 1) < mylen ? raw[k] >> 17 : NB * CELL) * 16;
    }
    if (t < 2) bits0 = ~bits0;
    asm volatile("" : "+r"(bits0), "+r"(ra[0]), "+r"(ra[1]), "+r"(ra[2]), "+r"(ra[3]), "+r"(ra[4]));
    fill(1);
    asm volatile("cp.async.wait_group 2;" ::: "memory");
    bar_sync(1, NT);
    TSTAMP(19);
    {
        uint4 rv[NRAW];
#pragma unroll
        for (int k = 0; k < NRAW - 1; k++) rv[k] = lds128(ra[k]);
        if ((NRAW - 1) * 4 < S) rv[NRAW - 1] = lds128(ra[NRAW - 1]);
        if (tid == 0) asm volatile("cp.async.cg.shared.global [%0], [%1], 16;" :: "r"(sb + SM_MISC + 1824 + 32), "l"(&gs->t0) : "memory");
        fill(2);
        bar_sync(1, NT);
        TSTAMP(12);
        unsigned char* mr = meta + (q - 1) * STEPB + c * 16;
        unsigned char* ms = meta + (q - DS - 1) * STEPB + 128 + c * 4;
#pragma unroll
        for (int k = 0; k < NRAW; k++) {
            if (k == 0) {
                *(uint4*)(mr + (q == 0 ? S * STEPB : 0)) = rv[k];
                *(uint32_t*)(ms + S * STEPB) = sv0 + F_WRAP;
            } else if (k * 4 + q < S) {
                *(uint4*)(mr + k * 4 * STEPB) = rv[k];
                *(uint32_t*)(ms + k * 4 * STEPB + (k == 1 && q == 0 ? S * STEPB : 0)) = raw[k] & 0xFFFF;
            }
        }
    }
    __syncwarp();
    const uint32_t tphase = PACE / 4;
    uint32_t dreg;
    {
        const int st = lane == 0 ? S - 1 : min(lane, S) - 1;
        const uint4 u0 = *(const uint4*)(meta + st * STEPB + 128), u1 = *(const uint4*)(meta + st * STEPB + 144);
        int pos = (u0.x + u0.y + u0.z + u0.w + u1.x + u1.y + u1.z + u1.w) >> 5;
        pos += ((u0.x & F_WRAP) ? NN : 0) + (lane == S ? NN : 0) - NN * (2 * DS + 1) / 32;
        dreg = pos * (int)tphase / NN;
    }
    fill(3);
    TSTAMP(6);

    uint32_t* stash = (uint32_t*)(gs->stash + (b * NW + w) * 256) + lane;
    float acc[4][4];
#pragma unroll
    for (int i = 0; i < 16; i++) acc[i / 4][i % 4] = 0.f;
    uint4 az = *(const uint4*)(smem + SM_AZ + lane * 16);
    uint32_t dcur = dreg, dl = 0, now = flag[1], tcur = 0;
    uint32_t mp = 0, smask = 1, didx = 2;
    const uint32_t mend = S * STEPB;
    uint2 r = lds64(mend - STEPB + recl), s0 = lds64(mend - STEPB + srcl);
    auto step = [&](const uint32_t off, const int mode, const bool pc = true) {
        auto tick = [&]() { if (mode == 0 && pc) { unsigned long long n64; asm volatile("mov.u64 %0, %%globaltimer;" : "=l"(n64)); now = (uint32_t)n64; } };
        if (TP == 0) tick();
        const uint2 rc = r, sc = s0;
        if (mode != 4) r = lds64(mp + recl);
        if (mode == 0) s0 = lds64(mp + srcl);
        asm volatile("cp.async.wait_group %0;" :: "n"(DS - 1) : "memory");
        const uint4 xa = lds128(rsrc + off), xb = lds128(rsrc + off + 512), xc = lds128(rsrc + off + 1024), xd = lds128(rsrc + off + 1536);
        if (mode == 0) {
            if (pc) { dl = __shfl_sync(0xffffffff, dcur, didx); didx += 2; }
            cpa2(wdst + off, sc.x); cpa2(wdst + off + 512, sc.y);
        }
        if (mode == 1 && w < 16) {
#pragma unroll
            for (int j = 0; j < 4; j++) {
                const int kk = 4 * j + q, ch = 16 * (w & 7) + 2 * (kk & 7) + (kk >> 3);
                asm volatile("cp.async.cg.shared.global [%0], [%1], 16;" :: "r"(ring0 + kk * 128 + ((c ^ (kk & 7)) << 4)), "l"(w_mix + ch * 16 + (w >> 3) * 8 + c) : "memory");
            }
            asm volatile("cp.async.mbarrier.arrive.noinc.shared.b64 [%0];" :: "r"(mbarW) : "memory");
        }
        if (mode == 2 || mode == 3) {
#pragma unroll
            for (int j = 0; j < 4; j += mode - 1)
                asm volatile("cp.async.cg.shared.global [%0], [%1], 16;" :: "r"(ring0 + off + j * 512 + lane * 16), "l"(stash + (mode - 2) * 512 + j * 128 + lane * 3) : "memory");
        }
        asm volatile("cp.async.commit_group;" ::: "memory");
        float z[4], y[4], t1[4], t2[4];
        mma1688z(z, az.x, az.y, rc.y);
        mma1688z(y, az.z, az.w, rc.y);
        uint32_t bt;
        asm("{.reg .pred p; .reg .b32 m; and.b32 m, %2, %3; setp.ne.u32 p, m, 0; selp.b32 %0, %1, 0, p;}" : "=r"(bt) : "r"(rc.x), "r"(bits0), "r"(smask));
        mma1688z(t1, at[0], at[1], bt);
        mma1688z(t2, at[2], at[3], bt);
        if (TP == 1) tick();
        const uint32_t T0 = pack2(t1[0], t1[2]), T1 = pack2(t2[0], t2[2]), T2 = pack2(t1[1], t1[3]), T3 = pack2(t2[1], t2[3]);
        const uint32_t R0 = pack2(silu_h(z[0]), silu_h(z[2]));
        if (TP == 2) tick();
        const uint32_t R1 = pack2(silu_h(z[1]), silu_h(z[3]));
        if (TP == 3) tick();
        const uint32_t R2 = pack2(silu_h(y[0]), silu_h(y[2])), R3 = pack2(silu_h(y[1]), silu_h(y[3]));
        if (TP == 4) tick();
        mma16816(acc[0], mul_lo(xa.x, R0), mul_hi(xa.z, R0), mul_lo(xa.y, R0), mul_hi(xa.w, R0), T0, T1);
        mma16816(acc[1], mul_lo(xb.x, R1), mul_hi(xb.z, R1), mul_lo(xb.y, R1), mul_hi(xb.w, R1), T2, T3);
        mma16816(acc[2], mul_lo(xc.x, R2), mul_hi(xc.z, R2), mul_lo(xc.y, R2), mul_hi(xc.w, R2), T0, T1);
        mma16816(acc[3], mul_lo(xd.x, R3), mul_hi(xd.z, R3), mul_lo(xd.y, R3), mul_hi(xd.w, R3), T2, T3);
        mp += STEPB; smask <<= 1;
    };
    auto putacc = [&](uint32_t* p) {
        p[0] = pack2(acc[0][0], acc[0][1]); p[32] = pack2(acc[0][2], acc[0][3]); p[64] = pack2(acc[2][0], acc[2][1]); p[96] = pack2(acc[2][2], acc[2][3]);
        p[256] = pack2(acc[1][0], acc[1][1]); p[288] = pack2(acc[1][2], acc[1][3]); p[320] = pack2(acc[3][0], acc[3][1]); p[352] = pack2(acc[3][2], acc[3][3]);
    };
    int ph = 0;
    auto phase_end = [&](const bool odd) {
        az = *(const uint4*)(smem + SM_AZ + (ph + 1) * 512 + lane * 16);
        putacc(stash + (ph >> 1) * 512 + (ph & 1) * 128);
#pragma unroll
        for (int i = 0; i < 16; i++) acc[i / 4][i % 4] = 0.f;
        pbase += 256; mp = 0; smask = 1; ph++;
        dcur += tphase; didx = odd ? 2 : 1;
        WSTAMP(ph - 1);
    };
    uint32_t t0 = now;
    auto report = [&](uint32_t cand) {
        uint32_t b0, b1;
        asm volatile("ld.volatile.shared.v2.u32 {%0,%1}, [%2+16];" : "=r"(b0), "=r"(b1) : "r"(flg) : "memory");
        asm volatile("{.reg .pred p; setp.eq.u32 p, %2, 0; @p red.max.relaxed.gpu.global.u64 [%0], %1;}"
                     :: "l"(&gs->t0), "l"((((unsigned long long)b1 << 32) | b0) + (cand - b0)), "r"(lane) : "memory");
    };
    if (w == PW) {
        asm volatile("mov.u32 %0, %%globaltimer_lo;" : "=r"(now));
        now += PTOL - PTOL0;
    }
    auto relay = [&]() {
        uint32_t g0, g1, b0, b1;
        asm volatile("ld.volatile.shared.v2.u32 {%0,%1}, [%4+32]; ld.volatile.shared.v2.u32 {%2,%3}, [%4+16];"
                     : "=r"(g0), "=r"(g1), "=r"(b0), "=r"(b1) : "r"(flg) : "memory");
        const unsigned long long dg = (((unsigned long long)g1 << 32) | g0) - (((unsigned long long)b1 << 32) | b0);
        asm volatile("{.reg .pred p, q; setp.eq.u32 p, %1, 0; setp.lt.u64 q, %2, 30000; @q st.shared.u32 [%3+4], %4;\n"
                     "@p cp.async.cg.shared.global [%3+32], [%0], 16;}"
                     :: "l"(&gs->t0), "r"(lane), "l"(dg), "r"(flg), "r"(g0) : "memory");
    };
    const bool special = w == 0 || w == PW;
#pragma unroll 1
    for (int it = S - 1; it > 0; it--) {
        if (special) {
            if (w == 0) relay();
            else {
                const uint32_t cand = now - dl + tcur - PTOL;
                if ((int)(cand - t0) > 0) report(cand);
            }
        }
        dcur += t0 - tcur; tcur = t0;
#pragma unroll
        for (int k = 0; k < DS; k++) {
            if (k == T0K) asm volatile("ld.volatile.shared.u32 %0, [%1+4];" : "=r"(t0) : "r"(flg));
            step(k * SLOTB, 0, k & 1);
            if (!(k & 1)) {
                if (mp == mend) phase_end(k & 1);
            } else if (mp == mend || now < dl) {
                if (mp == mend) phase_end(k & 1);
                if (k < DS - 1 && (RELAY >> k & 1) && w == 0) relay();
                asm volatile("{.reg .pred p; .reg .u32 d;\n"
                             "PACE_LOOP: mov.u32 d, %%globaltimer_lo; sub.u32 d, %0, d; setp.lt.u32 p, d, 32768; @p nanosleep.u32 %1; @p bra.uni PACE_LOOP;}"
                             :: "r"(dl), "n"(PSLEEP) : "memory");
            }
        }
    }
    __syncwarp();
    step(0, 1); step(SLOTB, 2); step(2 * SLOTB, 3); step(3 * SLOTB, 4);
    WSTAMP(3);

    {
        putacc((uint32_t*)(smem + SM_RING + 2 * SLOTB + w * 2048 + 512) + lane);
        const int wg = w >> 2, w4 = w & 3;
        int nd[8];
#pragma unroll
        for (int j = 0; j < 8; j++) { const int l = wg * 8 + j; nd[j] = order[(t >> 1) ? 79 - l : l]; asm volatile("" : "+r"(nd[j])); }
        const bool odd = t & 1;
        uint2* ob = (uint2*)out + (size_t)n0 * 128 + w4 * 16 + g + (odd ? 8 : 0);
        asm volatile("cp.async.wait_all;" ::: "memory");
        mbar_wait(mbarW, 0);
        asm volatile("fence.proxy.async.shared::cta;" ::: "memory");
        TSTAMP(26);
        bar_sync(2 + wg, 128);
        if ((tid & 127) == 0) {
            const uint32_t ticket = atomicAdd((uint32_t*)flag + 12, 1);
            int spins = 0;
            while (flag[13] + LEAD < ticket && ++spins < (1 << 16)) {}
        }
        bar_sync(2 + wg, 128);
        TSTAMP(27);
        const uint64_t descA0 = (uint64_t)(((sb + SM_RING) & 0x3FFFF) >> 4) | ((uint64_t)1 << 16) | ((uint64_t)(1024 >> 4) << 32) | ((uint64_t)1 << 62);
        const uint64_t descB0 = (uint64_t)(((sb + SM_RING + SLOTB + wg * 8192) & 0x3FFFF) >> 4) | ((uint64_t)(128 >> 4) << 16) | ((uint64_t)(1024 >> 4) << 32);
        float d[2][32];
        asm volatile("wgmma.fence.sync.aligned;" ::: "memory");
#pragma unroll
        for (int mt = 0; mt < 2; mt++) {
#pragma unroll
            for (int ks = 0; ks < 8; ks++) {
                const uint64_t da = descA0 + (uint64_t)((ks * 2048 + mt * 16384) >> 4), db = descB0 + (uint64_t)(((ks & 3) * 256 + (ks >> 2) * SLOTB) >> 4);
                asm volatile("{.reg .pred p; setp.ne.b32 p, %34, 0;\n"
                    "wgmma.mma_async.sync.aligned.m64n64k16.f32.bf16.bf16 "
                    "{%0,%1,%2,%3,%4,%5,%6,%7,%8,%9,%10,%11,%12,%13,%14,%15,%16,%17,%18,%19,%20,%21,%22,%23,%24,%25,%26,%27,%28,%29,%30,%31}, %32, %33, p, 1, 1, 1, 1;}"
                    : "+f"(d[mt][0]), "+f"(d[mt][1]), "+f"(d[mt][2]), "+f"(d[mt][3]), "+f"(d[mt][4]), "+f"(d[mt][5]), "+f"(d[mt][6]), "+f"(d[mt][7]),
                      "+f"(d[mt][8]), "+f"(d[mt][9]), "+f"(d[mt][10]), "+f"(d[mt][11]), "+f"(d[mt][12]), "+f"(d[mt][13]), "+f"(d[mt][14]), "+f"(d[mt][15]),
                      "+f"(d[mt][16]), "+f"(d[mt][17]), "+f"(d[mt][18]), "+f"(d[mt][19]), "+f"(d[mt][20]), "+f"(d[mt][21]), "+f"(d[mt][22]), "+f"(d[mt][23]),
                      "+f"(d[mt][24]), "+f"(d[mt][25]), "+f"(d[mt][26]), "+f"(d[mt][27]), "+f"(d[mt][28]), "+f"(d[mt][29]), "+f"(d[mt][30]), "+f"(d[mt][31])
                    : "l"(da), "l"(db), "r"(ks));
            }
            asm volatile("wgmma.commit_group.sync.aligned;" ::: "memory");
            if (mt == RELAT - 1) asm volatile("{.reg .pred p; setp.eq.u32 p, %1, 0; @p red.shared.add.u32 [%0+52], 1;}" :: "r"(flg), "r"(tid & 127) : "memory");
        }
#pragma unroll
        for (int mt = 0; mt < 2; mt++) {
            if (mt == 0) asm volatile("wgmma.wait_group.sync.aligned 1;" ::: "memory");
            else asm volatile("wgmma.wait_group.sync.aligned 0;" ::: "memory");
            if (RELAT == 0 && mt == 0 && (tid & 127) == 0) atomicAdd((uint32_t*)flag + 13, 1);
            TSTAMP(23 + mt);
#pragma unroll
            for (int i = 0; i < 32; i++) asm volatile("" : "+f"(d[mt][i]) :: "memory");
#pragma unroll
            for (int j = 0; j < 8; j++) {
                const uint32_t v0 = pack2(d[mt][4 * j], d[mt][4 * j + 1]), v1 = pack2(d[mt][4 * j + 2], d[mt][4 * j + 3]);
                const uint32_t rv = __shfl_xor_sync(0xffffffff, odd ? v0 : v1, 1);
                if (nd[j] < nn) ob[nd[j] * 128 + mt * 64] = odd ? make_uint2(rv, v1) : make_uint2(v0, rv);
            }
        }
    }
    TSTAMP(8);
}

}

extern "C" void kernel_launch(void* const* d_in, const int* in_sizes, int n_in, void* d_out, int out_size) {
    (void)in_sizes; (void)n_in; (void)out_size;
    cudaFuncSetAttribute(tfn_kernel, cudaFuncAttributeMaxDynamicSharedMemorySize, SM_TOTAL);
    Scratch* gs = nullptr;
    cudaGetSymbolAddress((void**)&gs, g_scratch);
    cudaLaunchConfig_t cfg = {};
    cfg.gridDim = dim3(NB); cfg.blockDim = dim3(NT); cfg.dynamicSmemBytes = SM_TOTAL; cfg.stream = cudaStreamPerThread;
    cudaLaunchAttribute at[1];
    at[0].id = cudaLaunchAttributeCooperative; at[0].val.cooperative = 1;
    cfg.attrs = at; cfg.numAttrs = 1;
    cudaLaunchKernelEx(&cfg, tfn_kernel, (const unsigned char*)d_in[0], (const int4*)d_in[1], (const int4*)d_in[2],
                       (const uint4*)d_in[3], (const uint4*)d_in[4], (const uint16_t*)d_in[5], (const uint16_t*)d_in[6],
                       (const uint4*)d_in[7], (uint32_t*)d_out, gs);
}
```

```cpp
#include <cuda_runtime.h>
#include <cuda_bf16.h>
#include <stdint.h>

#define VOL
#define DMODE 1
#define T0K 2
#define GSLEEP 0
#define ADELAY 0
#define ABL 0
namespace {

constexpr int NN = 10000;
constexpr int NE = 320000;
constexpr int NB = 132;
constexpr int NW = 20;
constexpr int NT = NW * 32;
constexpr int CW = NW - 1;
#define PWARP 10
constexpr int PW = PWARP;
constexpr int NPB = 76;
constexpr int CELL = 48;
constexpr int RCH = 2880;
constexpr int CAP = 19;
constexpr int DS = 4;
constexpr int STEPB = 160;
constexpr int NE4 = NE / 4;
constexpr int NPIECE = NB * 8;
constexpr int KB = 320, KN = 32 * KB;
constexpr uint32_t F_WRAP = 1;

constexpr int SLOTB = NW * 2048;
constexpr int SM_RING = 0;
constexpr int SM_META = SM_RING + DS * SLOTB;
constexpr int SM_AZ = SM_META + NW * CAP * STEPB;
constexpr int SM_MISC = SM_AZ + 2048;
constexpr int SM_TOTAL = SM_MISC + 2048;
constexpr int SM_STAGE = SM_RING;
constexpr int SM_HIST = SM_RING + 25600;
constexpr int SM_POS = SM_RING;
constexpr int SM_SMALL = SM_HIST + 13056;
constexpr int SM_LIST = SM_RING + SLOTB;
constexpr int SM_ROUT = SM_RING + 2 * SLOTB;
constexpr int SM_RECS = SM_RING + 3 * SLOTB;
constexpr int SM_RAWY = SM_META;
constexpr int SM_RAWE = SM_RAWY + 608 * 32;
constexpr int SM_KEYS = SM_RAWE + 608 * 32;
static_assert(SM_TOTAL <= 232448 && SM_KEYS + NPIECE * 16 <= SM_AZ, "smem");
static_assert(SM_RECS + NB * CELL * 16 + 16 <= SM_AZ && SM_KEYS + NPIECE * 16 <= SM_RECS + NB * CELL * 16 && SM_SMALL + 1152 <= SLOTB && DS == 4, "smem");

struct Scratch {
    uint4 keys[NB * NPIECE];
    uint4 recs[NB * RCH];
    uint4 stash[NB * NW * 256];
    unsigned bar[4];
    unsigned long long t0, pad;
};
__device__ Scratch g_scratch;
#define TSTAMP(i)
#define TSTAMPC(i)
#define WSTAMP(i)

__device__ __forceinline__ void mma16816(float* d, uint32_t a0, uint32_t a1, uint32_t a2, uint32_t a3, uint32_t b0, uint32_t b1) {
    asm VOL("mma.sync.aligned.m16n8k16.row.col.f32.bf16.bf16.f32 {%0,%1,%2,%3}, {%4,%5,%6,%7}, {%8,%9}, {%0,%1,%2,%3};"
        : "+f"(d[0]), "+f"(d[1]), "+f"(d[2]), "+f"(d[3]) : "r"(a0), "r"(a1), "r"(a2), "r"(a3), "r"(b0), "r"(b1));
}
__device__ __forceinline__ void mma1688z(float* d, uint32_t a0, uint32_t a1, uint32_t b0) {
    asm VOL("mma.sync.aligned.m16n8k8.row.col.f32.bf16.bf16.f32 {%0,%1,%2,%3}, {%4,%5}, {%6}, {%7,%7,%7,%7};"
        : "=f"(d[0]), "=f"(d[1]), "=f"(d[2]), "=f"(d[3]) : "r"(a0), "r"(a1), "r"(b0), "f"(0.f));
}
__device__ __forceinline__ uint32_t pack2(float lo, float hi) {
    uint32_t r; asm VOL("cvt.rn.bf16x2.f32 %0, %1, %2;" : "=r"(r) : "f"(hi), "f"(lo)); return r;
}
__device__ __forceinline__ float silu_h(float h) {
    float t; asm VOL("tanh.approx.f32 %0, %1;" : "=f"(t) : "f"(h)); return fmaf(h, t, h);
}
__device__ __forceinline__ uint32_t mul_lo(uint32_t v, uint32_t r) {
    __nv_bfloat162 a = *(__nv_bfloat162*)&v, b = *(__nv_bfloat162*)&r; __nv_bfloat162 c = __hmul2(a, __low2bfloat162(b)); return *(uint32_t*)&c;
}
__device__ __forceinline__ uint32_t mul_hi(uint32_t v, uint32_t r) {
    __nv_bfloat162 a = *(__nv_bfloat162*)&v, b = *(__nv_bfloat162*)&r; __nv_bfloat162 c = __hmul2(a, __high2bfloat162(b)); return *(uint32_t*)&c;
}
__device__ __forceinline__ uint2 lds64(uint32_t a) {
    uint2 r; asm volatile("ld.shared.v2.u32 {%0,%1}, [%2];" : "=r"(r.x), "=r"(r.y) : "r"(a)); return r;
}
__device__ __forceinline__ uint4 lds128(uint32_t a) {
    uint4 r; asm volatile("ld.shared.v4.u32 {%0,%1,%2,%3}, [%4];" : "=r"(r.x), "=r"(r.y), "=r"(r.z), "=r"(r.w) : "r"(a) : "memory"); return r;
}
__device__ __forceinline__ void bar_sync(int id, int n) { asm volatile("bar.sync %0, %1;" :: "r"(id), "r"(n) : "memory"); }
__device__ __forceinline__ void bar_arrive(int id, int n) { asm volatile("bar.arrive %0, %1;" :: "r"(id), "r"(n) : "memory"); }
__device__ __forceinline__ void mbar_wait(uint32_t bar, uint32_t ph) {
    uint32_t done; int spins = 0;
    do {
        asm volatile("{.reg .pred p; mbarrier.try_wait.parity.shared.b64 p, [%1], %2; selp.u32 %0,1,0,p;}" : "=r"(done) : "r"(bar), "r"(ph) : "memory");
    } while (!done && ++spins < (1 << 22));
}
__device__ __forceinline__ unsigned gbar_read(const unsigned* ctr) {
    unsigned v; asm volatile("ld.relaxed.gpu.global.u32 %0, [%1];" : "=r"(v) : "l"(ctr) : "memory");
    return v;
}
__device__ __forceinline__ void gbar_arrive(unsigned* ctr) {
    asm volatile("red.add.release.gpu.global.u32 [%0], 1;" :: "l"(ctr) : "memory");
}
__device__ __forceinline__ bool gbar_wait(const unsigned* ctr, unsigned target) {
    unsigned v; int spins = 0;
    while (true) {
        asm volatile("ld.acquire.gpu.global.u32 %0, [%1];" : "=r"(v) : "l"(ctr) : "memory");
        if ((int)(v - target) >= 0 || ++spins > (1 << 22)) break;
        if (GSLEEP) __nanosleep(GSLEEP);
    }
    return (int)(v - target) >= 0;
}
__device__ __forceinline__ int chunk_start4(int c) { return (c * NE4) / NB; }
__device__ __forceinline__ float bf2f(uint32_t h) { return __uint_as_float(h << 16); }

__device__ __noinline__ void slow_path(unsigned char* smem, int n0, int nn, const uint16_t* x, const int* src, const int* dst,
                                       const uint16_t* Y, const uint16_t* ef, const uint16_t* w_rad, const uint16_t* cg,
                                       const uint16_t* w_mix, __nv_bfloat16* out) {
    float* agg = (float*)smem;
    const int tid = threadIdx.x, lane = tid & 31, w = tid >> 5;
    bar_sync(1, NT);
    for (int i = tid; i < NPB * 512; i += NT) agg[i] = 0.f;
    bar_sync(1, NT);
    for (int e0 = w * 32; e0 < NE; e0 += NT) {
        int dl = dst[e0 + lane] - n0;
        unsigned m = __ballot_sync(0xffffffff, dl >= 0 && dl < nn);
        while (m) {
            int l = __ffs(m) - 1; m &= m - 1;
            int e = e0 + l, d = __shfl_sync(0xffffffff, dl, l), s = src[e];
            float T[16];
            for (int i = 0; i < 4; i++) for (int o = 0; o < 4; o++) {
                float a = 0.f;
                for (int f = 0; f < 4; f++) a += bf2f(Y[e * 4 + f]) * bf2f(cg[i * 16 + f * 4 + o]);
                T[i * 4 + o] = a;
            }
            for (int k = 0; k < 4; k++) {
                int c = lane + 32 * k;
                float z = 0.f;
                for (int j = 0; j < 4; j++) z += bf2f(ef[e * 4 + j]) * bf2f(w_rad[j * 128 + c]);
                float R = z / (1.f + __expf(-z));
                for (int o = 0; o < 4; o++) {
                    float a = 0.f;
                    for (int i = 0; i < 4; i++) a += bf2f(x[(size_t)s * 512 + c * 4 + i]) * T[i * 4 + o];
                    atomicAdd(&agg[d * 512 + c * 4 + o], R * a);
                }
            }
        }
    }
    bar_sync(1, NT);
    for (int i = tid; i < nn * 512; i += NT) {
        int n = i >> 9, d = (i >> 2) & 127, o = i & 3;
        float a = 0.f;
        for (int c = 0; c < 128; c++) a += agg[n * 512 + c * 4 + o] * bf2f(w_mix[c * 128 + d]);
        out[(size_t)(n0 + n) * 512 + (i & 511)] = __float2bfloat16(a);
    }
}

#define PACE 24000
#define YDELAY 300
#define TP 0
#define BFENCE 0
#define ASYM 0
#define KFIRST 0
#define GATE0 1
#define SWAP 1
#define EPI 2
#define LEAD 0
#define RELAT 2
#define POFF 3100
#define PSLEEP 32
#define PTOL0 300
#define PTOL 800
__global__ void __launch_bounds__(NT, 1)
tfn_kernel(const unsigned char* __restrict__ x, const int4* __restrict__ src4, const int4* __restrict__ dst4,
           const uint4* __restrict__ Y, const uint4* __restrict__ ef, const uint16_t* __restrict__ w_rad,
           const uint16_t* __restrict__ cg, const uint4* __restrict__ w_mix, uint32_t* __restrict__ out, Scratch* __restrict__ gs) {
    extern __shared__ __align__(1024) unsigned char smem[];
    const uint32_t sb = (uint32_t)__cvta_generic_to_shared(smem);
    const int b = blockIdx.x, tid = threadIdx.x, lane = tid & 31, g = lane >> 2, t = lane & 3;
    const int w = __shfl_sync(0xffffffff, tid >> 5, 0);
    uint32_t* stage = (uint32_t*)(smem + SM_STAGE);
    uint32_t* hist = (uint32_t*)(smem + SM_HIST);
    uint32_t* cnt = (uint32_t*)(smem + SM_MISC);
    uint32_t* deg = cnt + 136;
    uint32_t* order = deg + 104;
    uint32_t* cnt2 = order + 80;
    volatile uint32_t* flag = cnt2 + 136;
    const uint32_t mbarK = sb + SM_MISC + 1920, mbarR = mbarK + 8, mbarW = mbarK + 16;
    const int n0 = b * NPB, nn = min(NPB, NN - n0);
    TSTAMP(0);

    const int c0 = chunk_start4(b), c1 = chunk_start4(b + 1);
    const bool has4 = c0 + tid < c1;
    int4 d4 = make_int4(0, 0, 0, 0), s4 = d4;
    if (has4) { d4 = __ldg(dst4 + c0 + tid); s4 = __ldg(src4 + c0 + tid); }
    unsigned tgt = 0;
    if (tid == NT - 1) {
        tgt = gbar_read(&gs->bar[0]);
        asm volatile("mbarrier.init.shared.b64 [%0], 1;" :: "r"(mbarK));
        asm volatile("mbarrier.init.shared.b64 [%0], 1;" :: "r"(mbarR));
        asm volatile("mbarrier.init.shared.b64 [%0], 512;" :: "r"(mbarW));
        asm volatile("fence.mbarrier_init.release.cluster;" ::: "memory");
        flag[0] = 0; flag[12] = 0; flag[13] = 0; flag[15] = 0;
    }
    if (w == CW) {
        asm volatile("cp.async.cg.shared.global [%0], [%1], 16;" :: "r"(sb + SM_SMALL + lane * 16), "l"(w_rad + lane * 8) : "memory");
        asm volatile("cp.async.cg.shared.global [%0], [%1], 16;" :: "r"(sb + SM_SMALL + 512 + lane * 16), "l"(w_rad + 256 + lane * 8) : "memory");
        if (lane < 8) asm volatile("cp.async.cg.shared.global [%0], [%1], 16;" :: "r"(sb + SM_SMALL + 1024 + lane * 16), "l"(cg + lane * 8) : "memory");
    }
    ((uint4*)hist)[tid] = make_uint4(0, 0, 0, 0);
    {
        const uint32_t dk = (80 + b % 22) * KN + (b & 31) * KB;
#pragma unroll
        for (int j = 0; j < 3; j++) if (tid + j * NT < NB * CELL / 4) ((uint4*)stage)[tid + j * NT] = make_uint4(dk, dk, dk, dk);
    }
    if (tid < 136) cnt[tid] = 0;
    if (tid == 0) { *(uint4*)(smem + SM_MISC + 1824 + 32) = make_uint4(0, 0, 0, 0); *(uint4*)(smem + SM_RECS + NB * CELL * 16) = make_uint4(0, 0, 0, 0); }
    if (tid < 80) { deg[tid] = 127 - tid; order[tid] = tid; }
    __syncthreads();
    TSTAMP(9);
    if (tid == 64) {
        if (YDELAY) __nanosleep(YDELAY);
        asm volatile("mbarrier.arrive.expect_tx.shared.b64 _, [%0], %1;" :: "r"(mbarR), "r"((c1 - c0) * 64) : "memory");
        asm volatile("cp.async.bulk.shared::cluster.global.mbarrier::complete_tx::bytes [%0], [%1], %2, [%3];"
                     :: "r"(sb + SM_RAWY), "l"(Y + 2 * c0), "r"((c1 - c0) * 32), "r"(mbarR) : "memory");
        asm volatile("cp.async.bulk.shared::cluster.global.mbarrier::complete_tx::bytes [%0], [%1], %2, [%3];"
                     :: "r"(sb + SM_RAWE), "l"(ef + 2 * c0), "r"((c1 - c0) * 32), "r"(mbarR) : "memory");
    }

    uint32_t bin[4] = {0, 0, 0, 0}, slot[4] = {0, 0, 0, 0};
    if (has4) {
        const uint32_t dd[4] = {(uint32_t)d4.x, (uint32_t)d4.y, (uint32_t)d4.z, (uint32_t)d4.w}, ss[4] = {(uint32_t)s4.x, (uint32_t)s4.y, (uint32_t)s4.z, (uint32_t)s4.w};
#pragma unroll
        for (int k = 0; k < 4; k++) { bin[k] = dd[k] / NPB; slot[k] = atomicAdd(&cnt[bin[k]], 1); }
#pragma unroll
        for (int k = 0; k < 4; k++) stage[bin[k] * CELL + min(slot[k], CELL - 1)] = (dd[k] - bin[k] * NPB) * KN + ss[k];
    }
    if (w == CW) {
        if (tid == NT - 1) { tgt = tgt / NB + 1; flag[14] = (tgt & 1) << 31; tgt *= NB; }
        asm volatile("cp.async.wait_all;" ::: "memory");
    }
    bar_sync(1, NT);
    TSTAMP(1);
    const uint32_t tag = flag[14];
#pragma unroll
    for (int j = 0; j < 2; j++) {
        const int i = tid + j * NT;
        if (i < NPIECE) {
            const uint2 sa = *(const uint2*)(stage + i * 6), sc = *(const uint2*)(stage + i * 6 + 2);
            uint2 se = *(const uint2*)(stage + i * 6 + 4);
            const uint32_t cf = cnt[i >> 3], cn = min(cf, 63u);
            if ((i & 7) == 7) {
                const uint32_t al = cf > CELL - 8 ? 7 : 0;
                uint32_t o;
                asm volatile("atom.shared.add.u32 %0, [%1], %2;" : "=r"(o) : "r"(sb + SM_MISC + 1824 + 60), "r"(cf + al) : "memory");
                se.y = (o + al) & ~al;
                cnt2[i >> 3] = se.y;
            }
            asm volatile("{.reg .b64 lo, hi; mov.b64 lo, {%1,%2}; mov.b64 hi, {%3,%4}; st.relaxed.gpu.global.v2.b64 [%0], {lo, hi};}"
                         :: "l"(gs->keys + ((i >> 3) * NB + b) * 8 + ((i ^ b) & 7)),
                            "r"(sa.x | (se.x << 20)), "r"(sa.y | ((se.x >> 12) << 20) | ((cn & 7) << 28) | tag),
                            "r"(sc.x | (se.y << 20)), "r"(sc.y | ((se.y >> 12) << 20) | ((cn >> 3) << 28) | tag) : "memory");
        }
    }
    bar_sync(1, NT);
    if (tid == NT - 1) {
        TSTAMPC(10);
        asm volatile("red.add.relaxed.gpu.global.u32 [%0], 1;" :: "l"(&gs->bar[0]) : "memory");
        asm volatile("mbarrier.arrive.expect_tx.shared.b64 _, [%0], %1;" :: "r"(mbarK), "r"(NPIECE * 16) : "memory");
        if (ADELAY) mbar_wait(mbarR, 0);
        gbar_wait(&gs->bar[0], tgt);
        TSTAMPC(13);
        asm volatile("fence.proxy.async.global;" ::: "memory");
        asm volatile("cp.async.bulk.shared::cluster.global.mbarrier::complete_tx::bytes [%0], [%1], %2, [%3];"
                 :: "r"(sb + SM_KEYS), "l"(gs->keys + b * NPIECE), "r"(NPIECE * 16), "r"(mbarK) : "memory");
    }
    __syncwarp();
    uint32_t at[4];
    {
        const int o = g & 3, f = 2 * (t & 1);
#pragma unroll
        for (int i = 0; i < 4; i++) {
            const uint16_t* cp = (const uint16_t*)(smem + SM_SMALL + 1024) + i * 16 + f * 4 + o;
            at[i] = (t >> 1) == (g >> 2) ? cp[0] | ((uint32_t)cp[4] << 16) : 0;
        }
    }

    const int q = lane >> 3, c = lane & 7;
    const uint32_t ring0 = sb + SM_RING + w * 2048;
    uint32_t wdst = ring0 + q * 128 + ((c + 2 * q) & 7) * 16;
    uint32_t rsrc = ring0 + t * 128 + ((g + 2 * t) & 7) * 16;
    uint32_t recl = sb + SM_META + w * (CAP * STEPB) + g * 16 + (t & 1) * 8, srcl = sb + SM_META + w * (CAP * STEPB) + 128 + q * 8;
    uint32_t flg = sb + SM_MISC + (136 + 104 + 80 + 136) * 4;
    asm volatile("" : "+r"(wdst), "+r"(rsrc), "+r"(recl), "+r"(srcl), "+r"(flg));
    uint32_t key[2][6], ha[2][6], rk[2][6], kidx[2], ka[2];
    int nk[2];
#pragma unroll
    for (int j = 0; j < 2; j++) {
        const int i0 = j ? 2 * 608 - 1 - tid : tid, i = min(i0, NPIECE - 1), r = i / NB, cc = i - r * NB;
        ka[j] = sb + SM_KEYS + (cc * 8 + ((r ^ cc) & 7)) * 16;
        kidx[j] = (cc * CELL + r * 6) << 17;
        nk[j] = i0 < NPIECE && w < CW ? -6 * r : -1000;
    }
    asm volatile("" : "+r"(at[0]), "+r"(at[1]), "+r"(at[2]), "+r"(at[3]), "+r"(ka[0]), "+r"(ka[1]), "+r"(kidx[0]), "+r"(kidx[1]), "+r"(nk[0]), "+r"(nk[1]));
    if (w == CW) {
        __syncwarp();
        bar_sync(7, NT);
        if (tid == NT - 1) {
            TSTAMPC(11);
            asm volatile("cp.async.bulk.global.shared::cta.bulk_group [%0], [%1], %2;"
                         :: "l"(gs->recs + b * RCH), "r"(sb + SM_ROUT), "r"(((flag[15] + 1) & ~1u) * 16) : "memory");
            asm volatile("cp.async.bulk.commit_group; cp.async.bulk.wait_group 0;" ::: "memory");
            TSTAMPC(14);
            asm volatile("red.add.relaxed.gpu.global.u32 [%0], 1;" :: "l"(&gs->bar[1]) : "memory");
            TSTAMPC(15);
        }
    } else {
        if (w < 8) {
            const uint32_t* wp = (const uint32_t*)(smem + SM_SMALL) + (t & 1) * 128 + 8 * w + g;
            const uint32_t wr0 = t < 2 ? wp[0] : 0, wr1 = t < 2 ? wp[64] : 0;
            *(uint2*)(smem + SM_AZ + (w >> 1) * 512 + lane * 16 + (w & 1) * 8) =
                make_uint2(pack2(0.5f * bf2f(wr0 & 0xFFFF), 0.5f * bf2f(wr1 & 0xFFFF)), pack2(0.5f * bf2f(wr0 >> 16), 0.5f * bf2f(wr1 >> 16)));
        }
        const bool sw = g & 1;
        uint32_t rp[4];
#pragma unroll
        for (int k = 0; k < 4; k++) rp[k] = cnt2[bin[k]] + slot[k];
        uint4* ro = (uint4*)(smem + SM_ROUT);
        uint4 *p0 = ro + (sw ? rp[2] : rp[0]), *p1 = ro + (sw ? rp[3] : rp[1]), *p2 = ro + (sw ? rp[0] : rp[2]), *p3 = ro + (sw ? rp[1] : rp[3]);
        const uint32_t ya = sb + SM_RAWY + tid * 32 + (sw ? 16 : 0);
        mbar_wait(mbarR, 0);
        TSTAMP(18);
        if (has4) {
            const uint4 y0 = lds128(ya), e0 = lds128(ya + (SM_RAWE - SM_RAWY)), y1 = lds128(ya ^ 16), e1 = lds128((ya ^ 16) + (SM_RAWE - SM_RAWY));
            *p0 = make_uint4(y0.x, e0.x, y0.y, e0.y); *p1 = make_uint4(y0.z, e0.z, y0.w, e0.w);
            *p2 = make_uint4(y1.x, e1.x, y1.y, e1.y); *p3 = make_uint4(y1.z, e1.z, y1.w, e1.w);
        }
        asm volatile("fence.proxy.async.shared::cta;" ::: "memory");
        bar_arrive(7, NT);
    }
    __syncwarp();
    TSTAMP(2);

    if (w < CW) {
        mbar_wait(mbarK, 0);
        TSTAMP(3);
        uint4 v[2] = {lds128(ka[0]), lds128(ka[1])};
#pragma unroll
        for (int j = 0; j < 2; j++) {
            int spins = 0;
            while ((int)((v[j].y ^ tag) | (v[j].w ^ tag)) < 0) {
                asm volatile("{.reg .b64 lo, hi; ld.relaxed.gpu.global.v2.b64 {lo, hi}, [%4]; mov.b64 {%0,%1}, lo; mov.b64 {%2,%3}, hi;}"
                             : "=r"(v[j].x), "=r"(v[j].y), "=r"(v[j].z), "=r"(v[j].w) : "l"((const unsigned char*)(gs->keys + b * NPIECE) + (ka[j] - sb - SM_KEYS)) : "memory");
                if (++spins > (1 << 20)) { *flag = 1; break; }
            }
            const uint32_t hc = ((v[j].y >> 28) & 7) | ((v[j].w >> 25) & 0x38);
            if (j == 1 && nk[j] == -42) {
                cnt[kidx[j] / (CELL << 17)] = hc | ((v[j].z >> 20) << 8);
                v[j].w |= ((80 * KN) >> 12) << 20;
            }
            if (hc > CELL - 1) *flag = 1;
            nk[j] += hc;
            if (nk[j] > 0) {
                key[j][0] = v[j].x & 0xFFFFF; key[j][1] = v[j].y & 0xFFFFF; key[j][2] = v[j].z & 0xFFFFF; key[j][3] = v[j].w & 0xFFFFF;
                key[j][4] = (v[j].x >> 20) | ((v[j].y >> 8) & 0xFF000); key[j][5] = (v[j].z >> 20) | ((v[j].w >> 8) & 0xFF000);
#pragma unroll
                for (int u = 0; u < 6; u++) {
                    ha[j][u] = __umulhi(key[j][u], 0xFFFFFFFFu / KB + 1);
                    rk[j][u] = atomicAdd(&hist[ha[j][u]], 1);
                    atomicAdd(&deg[ha[j][u] >> 5], 128);
                }
            }
        }
        bar_sync(9, NT - 32);
        TSTAMP(20);
#pragma unroll
        for (int j = 0; j < 2; j++) kidx[j] += ((cnt[kidx[j] / (CELL << 17)] >> 8) & 7) << 17;
        const int n = tid >> 3, sub = tid & 7;
        const uint32_t me = deg[n];
        int r = 0;
#pragma unroll
        for (int k = 0; k < 5; k++) { const uint2 dd = *(const uint2*)(deg + sub * 10 + 2 * k); r += (dd.x > me) + (dd.y > me); }
        r += __shfl_xor_sync(0xffffffff, r, 1); r += __shfl_xor_sync(0xffffffff, r, 2); r += __shfl_xor_sync(0xffffffff, r, 4);
        if (sub == 0) order[r] = n;
    }
    bar_sync(1, NT);
    TSTAMP(22);
    uint32_t len2;
    {
        const uint2 na = *(const uint2*)(order + 2 * w);
        uint2 nb = *(const uint2*)(order + 78 - 2 * w);
        const uint32_t ia0 = na.x * 32 + lane, ia1 = na.y * 32 + lane;
        const uint32_t ha0 = hist[ia0], ha1 = hist[ia1];
        uint32_t hb0 = hist[nb.y * 32 + lane], hb1 = hist[nb.x * 32 + lane];
        const int su = __reduce_add_sync(0xffffffff, (int)(ha0 - ha1) * (2 * lane - 31)), sv = __reduce_add_sync(0xffffffff, (int)(hb0 - hb1) * (2 * lane - 31));
        if ((su ^ sv) >= 0) {
            nb = make_uint2(nb.y, nb.x);
            const uint32_t tmp = hb0; hb0 = hb1; hb1 = tmp;
            *(uint2*)(order + 78 - 2 * w) = nb;
        }
        const uint32_t ib0 = nb.y * 32 + lane, ib1 = nb.x * 32 + lane;
        const uint32_t ca = ha0 + (ha1 << 16), cab = ca + hb0 + (hb1 << 16);
        uint32_t inc = cab;
#pragma unroll
        for (int o = 1; o < 32; o <<= 1)
            asm volatile("{.reg .pred p; .reg .u32 u; shfl.sync.up.b32 u|p, %0, %1, 0, 0xffffffff; @p add.u32 %0, %0, u;}" : "+r"(inc) : "r"(o));
        const uint32_t ea = inc - cab, eb = ea + ca, base = sb + SM_LIST + w * 2048;
        uint2* pos = (uint2*)(smem + SM_POS);
        pos[ia0] = make_uint2(base + (ea & 0xFFFF) * 8, na.x * (0u - 4 * KN));
        pos[ib0] = make_uint2(base + (eb & 0xFFFF) * 8, nb.y * (0u - 4 * KN) + 0x10000);
        pos[ia1] = make_uint2(base + 4 + (ea >> 16) * 8, na.y * (0u - 4 * KN));
        pos[ib1] = make_uint2(base + 4 + (eb >> 16) * 8, nb.x * (0u - 4 * KN) + 0x10000);
        if (max(inc & 0xFFFF, inc >> 16) > 4 * CAP) *flag = 1;
        len2 = __shfl_sync(0xffffffff, inc, 31);
    }
    uint32_t ci = cnt[min(w + NW * lane, NB)];
    ci = ((((w + NW * lane) * (RCH / 8) + (ci >> 11)) << 8) | (ci & 0xFF)) + ((ci >> 8) & 7);
    if (w == CW) {
        unsigned long long tbase;
        asm volatile("mov.u64 %0, %%globaltimer;" : "=l"(tbase));
        tbase += POFF;
        flag[1] = (uint32_t)tbase; flag[4] = (uint32_t)tbase; flag[5] = (uint32_t)(tbase >> 32);
        if (lane == 0) {
            asm volatile("red.max.relaxed.gpu.global.u64 [%0], %1;" :: "l"(&gs->t0), "l"(tbase) : "memory");
            if (b < 128) asm volatile("cp.async.bulk.prefetch.L2.global [%0], 256;" :: "l"(w_mix + b * 16));
        }
    }
    if (w == CW) {
        bar_arrive(9, NT);
        if (tid == NT - 1) { if (!gbar_wait(&gs->bar[1], tgt)) *flag = 1; TSTAMPC(17); }
        __syncwarp();
    } else {
        bar_sync(9, NT);
        TSTAMP(21);
        const uint32_t over = *flag;
#pragma unroll
        for (int j = 0; j < 2; j++) {
            if (nk[j] > 0) {
                uint2 h[6];
#pragma unroll
                for (int u = 0; u < 6; u++) h[u] = lds64(sb + SM_POS + ha[j][u] * 8);
                if (over) nk[j] = 0;
#pragma unroll
                for (int u = 0; u < 6; u++)
                    asm volatile("{.reg .pred p; setp.gt.s32 p, %2, %3; @p st.shared.u32 [%0], %1;}"
                                 :: "r"(h[u].x + rk[j][u] * 8), "r"(key[j][u] * 4 + h[u].y + (kidx[j] + (u << 17))), "r"(nk[j]), "r"(u) : "memory");
            }
        }
    }
    bar_sync(1, NT);
    TSTAMP(4);
    if (*flag) {
        slow_path(smem, n0, nn, (const uint16_t*)x, (const int*)src4, (const int*)dst4, (const uint16_t*)Y, (const uint16_t*)ef, w_rad, cg,
                  (const uint16_t*)w_mix, (__nv_bfloat16*)out);
        return;
    }
    {
        const uint4* gp = gs->recs + lane;
        const uint32_t sp = sb + SM_RECS + (w * CELL + lane) * 16;
#pragma unroll
        for (int j = 0; j < 7; j++) {
            const uint32_t cj = __shfl_sync(0xffffffff, ci, j);
            asm volatile("{.reg .pred p; setp.lt.u32 p, %2, %3; @p cp.async.cg.shared.global [%0], [%1], 16;}"
                         :: "r"(sp + j * (NW * CELL * 16)), "l"(gp + (size_t)(cj >> 8) * 8), "r"(lane), "r"(cj & 0xFF) : "memory");
        }
        for (uint32_t m = __ballot_sync(0xffffffff, (ci & 0xFF) > 32); m; m &= m - 1) {
            const int j = __ffs(m) - 1;
            const uint32_t cj = __shfl_sync(0xffffffff, ci, j);
            if (lane + 32 < (cj & 0xFF))
                asm volatile("cp.async.cg.shared.global [%0], [%1], 16;" :: "r"(sp + j * (NW * CELL * 16) + 512), "l"(gp + (size_t)(cj >> 8) * 8 + 32) : "memory");
        }
        asm volatile("cp.async.commit_group;" ::: "memory");
    }
    const int S = __shfl_sync(0xffffffff, max((int)(max(len2 & 0xFFFF, len2 >> 16) + 3) >> 2, DS + 1), 0);
    const int mylen = (lane & 1) ? len2 >> 16 : len2 & 0xFFFF;
    constexpr int NRAW = (CAP + 3) / 4;
    uint32_t bits0 = 0, raw[NRAW];
    unsigned char* meta = smem + SM_META + w * (CAP * STEPB);
#pragma unroll
    for (int k = 0; k < NRAW; k++) raw[k] = mylen ? ((uint32_t*)(smem + SM_LIST + w * 2048))[min(k * 16 + (lane >> 1), mylen - 1) * 2 + (lane & 1)] : 4 * n0;
    const uint32_t sv0 = raw[0] & 0xFFFF;
    const unsigned char* pbase = x + c * 16;
    auto cpa2 = [&](uint32_t dstp, uint32_t sv) {
        asm volatile("cp.async.cg.shared.global [%0], [%1], 16; cp.async.cg.shared.global [%0+1024], [%1+128], 16;"
                     :: "r"(dstp), "l"(pbase + (size_t)sv * 256) : "memory");
    };
    auto fill = [&](int i) {
        cpa2(wdst + i * SLOTB, __shfl_sync(0xffffffff, sv0, 8 * i + 2 * q)); cpa2(wdst + i * SLOTB + 512, __shfl_sync(0xffffffff, sv0, 8 * i + 2 * q + 1));
        asm volatile("cp.async.commit_group;" ::: "memory");
    };
    fill(0);
    TSTAMP(5);
    if (tid == 0) asm volatile("cp.async.cg.shared.global [%0], [%1], 16;" :: "r"(flg + 32), "l"(&gs->t0) : "memory");
    auto relay = [&]() {
        uint32_t g0, g1, b0, b1;
        asm volatile("ld.volatile.shared.v2.u32 {%0,%1}, [%4+32]; ld.volatile.shared.v2.u32 {%2,%3}, [%4+16];"
                     : "=r"(g0), "=r"(g1), "=r"(b0), "=r"(b1) : "r"(flg) : "memory");
        const unsigned long long dg = (((unsigned long long)g1 << 32) | g0) - (((unsigned long long)b1 << 32) | b0);
        asm volatile("{.reg .pred p, q; setp.eq.u32 p, %1, 0; setp.lt.u64 q, %2, 30000; @q st.shared.u32 [%3+4], %4;\n"
                     "@p cp.async.cg.shared.global [%3+32], [%0], 16;}"
                     :: "l"(&gs->t0), "r"(lane), "l"(dg), "r"(flg), "r"(g0) : "memory");
    };
    uint32_t ra[NRAW];
#pragma unroll
    for (int k = 0; k < NRAW; k++) {
        const uint32_t m = (__ballot_sync(0xffffffff, raw[k] & 0x10000) >> g) & 0x01010101u;
        bits0 |= ((m * 0x10204080u) >> 28) << (4 * k);
        ra[k] = sb + SM_RECS + (k * 16 + (lane >> 1) < mylen ? raw[k] >> 17 : NB * CELL) * 16;
    }
    if (t < 2) bits0 = ~bits0;
    asm volatile("" : "+r"(bits0), "+r"(ra[0]), "+r"(ra[1]), "+r"(ra[2]), "+r"(ra[3]), "+r"(ra[4]));
    fill(1);
    asm volatile("cp.async.wait_group 2;" ::: "memory");
    bar_sync(1, NT);
    TSTAMP(19);
    {
        uint4 rv[NRAW];
#pragma unroll
        for (int k = 0; k < NRAW - 1; k++) rv[k] = lds128(ra[k]);
        if ((NRAW - 1) * 4 < S) rv[NRAW - 1] = lds128(ra[NRAW - 1]);
        if (w == 0) relay();
        fill(2);
        bar_sync(1, NT);
        TSTAMP(12);
        unsigned char* mr = meta + (q - 1) * STEPB + c * 16;
        unsigned char* ms = meta + (q - DS - 1) * STEPB + 128 + c * 4;
#pragma unroll
        for (int k = 0; k < NRAW; k++) {
            if (k == 0) {
                *(uint4*)(mr + (q == 0 ? S * STEPB : 0)) = rv[k];
                *(uint32_t*)(ms + S * STEPB) = sv0 + F_WRAP;
            } else if (k * 4 + q < S) {
                *(uint4*)(mr + k * 4 * STEPB) = rv[k];
                *(uint32_t*)(ms + k * 4 * STEPB + (k == 1 && q == 0 ? S * STEPB : 0)) = raw[k] & 0xFFFF;
            }
        }
    }
    __syncwarp();
    const uint32_t tphase = PACE / 4;
    uint32_t dreg;
    {
        const int ls = lane >= S ? min(lane - S, S - 1) : lane, st = ls == 0 ? S - 1 : ls - 1;
        const uint4 u0 = *(const uint4*)(meta + st * STEPB + 128), u1 = *(const uint4*)(meta + st * STEPB + 144);
        int pos = (u0.x + u0.y + u0.z + u0.w + u1.x + u1.y + u1.z + u1.w) >> 5;
        pos += ((u0.x & F_WRAP) ? NN : 0) + (lane >= S ? NN : 0) - NN * (2 * DS + 1) / 32;
        dreg = pos * (int)tphase / NN;
    }
    fill(3);
    TSTAMP(6);

    uint32_t* stash = (uint32_t*)(gs->stash + (b * NW + w) * 256) + lane;
    float acc[4][4];
#pragma unroll
    for (int i = 0; i < 16; i++) acc[i / 4][i % 4] = 0.f;
    uint4 az = *(const uint4*)(smem + SM_AZ + lane * 16);
    uint32_t dcur = dreg, dl = 0, now = flag[1], tcur = 0;
    uint32_t mp = 0, smask = 1, didx = 2;
    uint32_t mend = S * STEPB;
    uint2 r = lds64(mend - STEPB + recl), s0 = lds64(mend - STEPB + srcl);
    auto step = [&](const uint32_t off, const int mode, const bool pc = true) {
        auto tick = [&]() { if (mode == 0 && pc) { unsigned long long n64; asm volatile("mov.u64 %0, %%globaltimer;" : "=l"(n64)); now = (uint32_t)n64; } };
        if (TP == 0) tick();
        const uint2 rc = r, sc = s0;
        if (mode != 4) r = lds64(mp + recl);
        if (mode == 0) s0 = lds64(mp + srcl);
        asm volatile("cp.async.wait_group %0;" :: "n"(DS - 1) : "memory");
        const uint4 xa = lds128(rsrc + off), xb = lds128(rsrc + off + 512), xc = lds128(rsrc + off + 1024), xd = lds128(rsrc + off + 1536);
        if (mode == 0) {
            if (pc == (DMODE == 1)) { dl = __shfl_sync(0xffffffff, dcur, didx); didx += 2; }
            cpa2(wdst + off, sc.x); cpa2(wdst + off + 512, sc.y);
        }
        if (mode == 1 && w < 16) {
#pragma unroll
            for (int j = 0; j < 4; j++) {
                const int kk = 4 * j + q, ch = 16 * (w & 7) + 2 * (kk & 7) + (kk >> 3);
                asm volatile("cp.async.cg.shared.global [%0], [%1], 16;" :: "r"(ring0 + kk * 128 + ((c ^ (kk & 7)) << 4)), "l"(w_mix + ch * 16 + (w >> 3) * 8 + c) : "memory");
            }
            asm volatile("cp.async.mbarrier.arrive.noinc.shared.b64 [%0];" :: "r"(mbarW) : "memory");
        }
        if (mode == 2 || mode == 3) {
#pragma unroll
            for (int j = 0; j < 4; j += mode - 1)
                asm volatile("cp.async.cg.shared.global [%0], [%1], 16;" :: "r"(ring0 + off + j * 512 + lane * 16), "l"(stash + (mode - 2) * 512 + j * 128 + lane * 3) : "memory");
        }
        asm volatile("cp.async.commit_group;" ::: "memory");
        float z[4], y[4], t1[4], t2[4];
        mma1688z(z, az.x, az.y, rc.y);
        mma1688z(y, az.z, az.w, rc.y);
        uint32_t bt;
        asm("{.reg .pred p; .reg .b32 m; and.b32 m, %2, %3; setp.ne.u32 p, m, 0; selp.b32 %0, %1, 0, p;}" : "=r"(bt) : "r"(rc.x), "r"(bits0), "r"(smask));
        mma1688z(t1, at[0], at[1], bt);
        mma1688z(t2, at[2], at[3], bt);
        if (TP == 1) tick();
        const uint32_t T0 = pack2(t1[0], t1[2]), T1 = pack2(t2[0], t2[2]), T2 = pack2(t1[1], t1[3]), T3 = pack2(t2[1], t2[3]);
        const uint32_t R0 = pack2(silu_h(z[0]), silu_h(z[2]));
        if (TP == 2) tick();
        const uint32_t R1 = pack2(silu_h(z[1]), silu_h(z[3]));
        if (TP == 3) tick();
        const uint32_t R2 = pack2(silu_h(y[0]), silu_h(y[2])), R3 = pack2(silu_h(y[1]), silu_h(y[3]));
        if (TP == 4) tick();
        mma16816(acc[0], mul_lo(xa.x, R0), mul_hi(xa.z, R0), mul_lo(xa.y, R0), mul_hi(xa.w, R0), T0, T1);
        mma16816(acc[1], mul_lo(xb.x, R1), mul_hi(xb.z, R1), mul_lo(xb.y, R1), mul_hi(xb.w, R1), T2, T3);
        mma16816(acc[2], mul_lo(xc.x, R2), mul_hi(xc.z, R2), mul_lo(xc.y, R2), mul_hi(xc.w, R2), T0, T1);
        mma16816(acc[3], mul_lo(xd.x, R3), mul_hi(xd.z, R3), mul_lo(xd.y, R3), mul_hi(xd.w, R3), T2, T3);
        mp += STEPB; smask <<= 1;
    };
    auto putacc = [&](uint32_t* p) {
        p[0] = pack2(acc[0][0], acc[0][1]); p[32] = pack2(acc[0][2], acc[0][3]); p[64] = pack2(acc[2][0], acc[2][1]); p[96] = pack2(acc[2][2], acc[2][3]);
        p[256] = pack2(acc[1][0], acc[1][1]); p[288] = pack2(acc[1][2], acc[1][3]); p[320] = pack2(acc[3][0], acc[3][1]); p[352] = pack2(acc[3][2], acc[3][3]);
    };
    int ph = 0;
    auto phase_end = [&](const bool odd) {
        az = *(const uint4*)(smem + SM_AZ + (ph + 1) * 512 + lane * 16);
        putacc(stash + (ph >> 1) * 512 + (ph & 1) * 128);
#pragma unroll
        for (int i = 0; i < 16; i++) acc[i / 4][i % 4] = 0.f;
        pbase += 256; mp = 0; smask = 1; ph++;
        dcur += tphase; didx = odd ? 2 : (DMODE == 1 ? 1 : 3);
        if (ph == 3) mend -= DS * STEPB;
        WSTAMP(ph - 1);
    };
    uint32_t t0 = now;
    auto report = [&](uint32_t cand) {
        uint32_t b0, b1;
        asm volatile("ld.volatile.shared.v2.u32 {%0,%1}, [%2+16];" : "=r"(b0), "=r"(b1) : "r"(flg) : "memory");
        asm volatile("{.reg .pred p; setp.eq.u32 p, %2, 0; @p red.max.relaxed.gpu.global.u64 [%0], %1;}"
                     :: "l"(&gs->t0), "l"((((unsigned long long)b1 << 32) | b0) + (cand - b0)), "r"(lane) : "memory");
    };
    if (w == PW) {
        asm volatile("mov.u32 %0, %%globaltimer_lo;" : "=r"(now));
        now += PTOL - PTOL0;
    }
    const uint32_t bias = w == 0 ? 1u << 20 : 0;
    if (w == 0) relay();
    dcur += bias;
    auto body = [&](const int k) -> bool {
        if (k == T0K) asm volatile("ld.volatile.shared.u32 %0, [%1+4];" : "=r"(t0) : "r"(flg));
        step(k * SLOTB, 0, k & 1);
        if (!(k & 1)) {
            if (mp == mend) phase_end(false);
        } else if (mp == mend || now < dl) {
            if (mp == mend) {
                if (k == DS - 1 && ph == 3) return true;
                phase_end(true);
            }
            if (w == 0) { dl -= 1u << 20; relay(); }
            asm volatile("{.reg .pred p; .reg .u32 d;\n"
                         "PACE_LOOP: mov.u32 d, %%globaltimer_lo; sub.u32 d, %0, d; setp.lt.u32 p, d, 32768; @p nanosleep.u32 %1; @p bra.uni PACE_LOOP;}"
                         :: "r"(dl), "n"(PSLEEP) : "memory");
        }
        return false;
    };
    asm volatile("{.reg .pred p; .reg .u32 d;\n"
                 "PACE_LOOP: mov.u32 d, %%globaltimer_lo; sub.u32 d, %0, d; setp.lt.u32 p, d, 32768; @p nanosleep.u32 %1; @p bra.uni PACE_LOOP;}"
                 :: "r"(__shfl_sync(0xffffffff, dreg, 0) + t0), "n"(PSLEEP) : "memory");
    do {
        if (w == PW) {
            const uint32_t cand = now - dl + tcur - PTOL;
            if ((int)(cand - t0) > 0) report(cand);
        }
        dcur += t0 - tcur; tcur = t0;
        body(0); body(1); body(2);
    } while (!body(3));
    __syncwarp();
    step(0, 1); step(SLOTB, 2); step(2 * SLOTB, 3); step(3 * SLOTB, 4);
    WSTAMP(3);

    {
        putacc((uint32_t*)(smem + SM_RING + 2 * SLOTB + w * 2048 + 512) + lane);
        const int wg = w >> 2, w4 = w & 3;
        int nd[8];
#pragma unroll
        for (int j = 0; j < 8; j++) { const int l = wg * 8 + j; nd[j] = order[(t >> 1) ? 79 - l : l]; asm volatile("" : "+r"(nd[j])); }
        const bool odd = t & 1;
        uint2* ob = (uint2*)out + (size_t)n0 * 128 + w4 * 16 + g + (odd ? 8 : 0);
        asm volatile("cp.async.wait_all;" ::: "memory");
        mbar_wait(mbarW, 0);
        asm volatile("fence.proxy.async.shared::cta;" ::: "memory");
        TSTAMP(26);
        bar_sync(2 + wg, 128);
        if ((tid & 127) == 0) {
            const uint32_t ticket = atomicAdd((uint32_t*)flag + 12, 1);
            int spins = 0;
            while (flag[13] + LEAD < ticket && ++spins < (1 << 16)) {}
        }
        bar_sync(2 + wg, 128);
        TSTAMP(27);
        const uint64_t descA0 = (uint64_t)(((sb + SM_RING) & 0x3FFFF) >> 4) | ((uint64_t)1 << 16) | ((uint64_t)(1024 >> 4) << 32) | ((uint64_t)1 << 62);
        const uint64_t descB0 = (uint64_t)(((sb + SM_RING + SLOTB + wg * 8192) & 0x3FFFF) >> 4) | ((uint64_t)(128 >> 4) << 16) | ((uint64_t)(1024 >> 4) << 32);
        float d[2][32];
        asm volatile("wgmma.fence.sync.aligned;" ::: "memory");
#pragma unroll
        for (int mt = 0; mt < 2; mt++) {
#pragma unroll
            for (int ks = 0; ks < 8; ks++) {
                const uint64_t da = descA0 + (uint64_t)((ks * 2048 + mt * 16384) >> 4), db = descB0 + (uint64_t)(((ks & 3) * 256 + (ks >> 2) * SLOTB) >> 4);
                asm volatile("{.reg .pred p; setp.ne.b32 p, %34, 0;\n"
                    "wgmma.mma_async.sync.aligned.m64n64k16.f32.bf16.bf16 "
                    "{%0,%1,%2,%3,%4,%5,%6,%7,%8,%9,%10,%11,%12,%13,%14,%15,%16,%17,%18,%19,%20,%21,%22,%23,%24,%25,%26,%27,%28,%29,%30,%31}, %32, %33, p, 1, 1, 1, 1;}"
                    : "+f"(d[mt][0]), "+f"(d[mt][1]), "+f"(d[mt][2]), "+f"(d[mt][3]), "+f"(d[mt][4]), "+f"(d[mt][5]), "+f"(d[mt][6]), "+f"(d[mt][7]),
                      "+f"(d[mt][8]), "+f"(d[mt][9]), "+f"(d[mt][10]), "+f"(d[mt][11]), "+f"(d[mt][12]), "+f"(d[mt][13]), "+f"(d[mt][14]), "+f"(d[mt][15]),
                      "+f"(d[mt][16]), "+f"(d[mt][17]), "+f"(d[mt][18]), "+f"(d[mt][19]), "+f"(d[mt][20]), "+f"(d[mt][21]), "+f"(d[mt][22]), "+f"(d[mt][23]),
                      "+f"(d[mt][24]), "+f"(d[mt][25]), "+f"(d[mt][26]), "+f"(d[mt][27]), "+f"(d[mt][28]), "+f"(d[mt][29]), "+f"(d[mt][30]), "+f"(d[mt][31])
                    : "l"(da), "l"(db), "r"(ks));
            }
            asm volatile("wgmma.commit_group.sync.aligned;" ::: "memory");
            if (mt == RELAT - 1) asm volatile("{.reg .pred p; setp.eq.u32 p, %1, 0; @p red.shared.add.u32 [%0+52], 1;}" :: "r"(flg), "r"(tid & 127) : "memory");
        }
#pragma unroll
        for (int mt = 0; mt < 2; mt++) {
            if (mt == 0) asm volatile("wgmma.wait_group.sync.aligned 1;" ::: "memory");
            else asm volatile("wgmma.wait_group.sync.aligned 0;" ::: "memory");
            if (RELAT == 0 && mt == 0 && (tid & 127) == 0) atomicAdd((uint32_t*)flag + 13, 1);
            TSTAMP(23 + mt);
#pragma unroll
            for (int i = 0; i < 32; i++) asm volatile("" : "+f"(d[mt][i]) :: "memory");
#pragma unroll
            for (int j = 0; j < 8; j++) {
                const uint32_t v0 = pack2(d[mt][4 * j], d[mt][4 * j + 1]), v1 = pack2(d[mt][4 * j + 2], d[mt][4 * j + 3]);
                const uint32_t rv = __shfl_xor_sync(0xffffffff, odd ? v0 : v1, 1);
                if (nd[j] < nn) ob[nd[j] * 128 + mt * 64] = odd ? make_uint2(rv, v1) : make_uint2(v0, rv);
            }
        }
    }
    TSTAMP(8);
}

}

extern "C" void kernel_launch(void* const* d_in, const int* in_sizes, int n_in, void* d_out, int out_size) {
    (void)in_sizes; (void)n_in; (void)out_size;
    cudaFuncSetAttribute(tfn_kernel, cudaFuncAttributeMaxDynamicSharedMemorySize, SM_TOTAL);
    Scratch* gs = nullptr;
    cudaGetSymbolAddress((void**)&gs, g_scratch);
    cudaLaunchConfig_t cfg = {};
    cfg.gridDim = dim3(NB); cfg.blockDim = dim3(NT); cfg.dynamicSmemBytes = SM_TOTAL; cfg.stream = cudaStreamPerThread;
    cudaLaunchAttribute at[1];
    at[0].id = cudaLaunchAttributeCooperative; at[0].val.cooperative = 1;
    cfg.attrs = at; cfg.numAttrs = 1;
    cudaLaunchKernelEx(&cfg, tfn_kernel, (const unsigned char*)d_in[0], (const int4*)d_in[1], (const int4*)d_in[2],
                       (const uint4*)d_in[3], (const uint4*)d_in[4], (const uint16_t*)d_in[5], (const uint16_t*)d_in[6],
                       (const uint4*)d_in[7], (uint32_t*)d_out, gs);
}
```

```cpp
#include <cuda_runtime.h>
#include <cuda_bf16.h>
#include <stdint.h>

#define VOL
#define PSTEP 2
#define T0K 2
#define GSLEEP 0
#define ADELAY 0
#define ABL 0
namespace {

constexpr int NN = 10000;
constexpr int NE = 320000;
constexpr int NB = 132;
constexpr int NW = 20;
constexpr int NT = NW * 32;
constexpr int CW = NW - 1;
#define PWARP 10
constexpr int PW = PWARP;
constexpr int NPB = 76;
constexpr int CELL = 48;
constexpr int RCH = 2880;
constexpr int CAP = 19;
constexpr int DS = 4;
constexpr int STEPB = 160;
constexpr int NE4 = NE / 4;
constexpr int NPIECE = NB * 8;
constexpr int KB = 320, KN = 32 * KB;
constexpr uint32_t F_WRAP = 1;

constexpr int SLOTB = NW * 2048;
constexpr int SM_RING = 0;
constexpr int SM_META = SM_RING + DS * SLOTB;
constexpr int SM_AZ = SM_META + NW * CAP * STEPB;
constexpr int SM_MISC = SM_AZ + 2048;
constexpr int SM_TOTAL = SM_MISC + 2048;
constexpr int SM_STAGE = SM_RING;
constexpr int SM_HIST = SM_RING + 25600;
constexpr int SM_POS = SM_RING;
constexpr int SM_SMALL = SM_HIST + 13056;
constexpr int SM_LIST = SM_RING + SLOTB;
constexpr int SM_ROUT = SM_RING + 2 * SLOTB;
constexpr int SM_RECS = SM_RING + 3 * SLOTB;
constexpr int SM_RAWY = SM_META;
constexpr int SM_RAWE = SM_RAWY + 608 * 32;
constexpr int SM_KEYS = SM_RAWE + 608 * 32;
static_assert(SM_TOTAL <= 232448 && SM_KEYS + NPIECE * 16 <= SM_AZ, "smem");
static_assert(SM_RECS + NB * CELL * 16 + 16 <= SM_AZ && SM_KEYS + NPIECE * 16 <= SM_RECS + NB * CELL * 16 && SM_SMALL + 1152 <= SLOTB && DS == 4, "smem");

struct Scratch {
    uint4 keys[NB * NPIECE];
    uint4 recs[NB * RCH];
    uint4 stash[NB * NW * 256];
    unsigned bar[4];
    unsigned long long t0, pad;
};
__device__ Scratch g_scratch;
#define TSTAMP(i)
#define TSTAMPC(i)
#define WSTAMP(i)

__device__ __forceinline__ void mma16816(float* d, uint32_t a0, uint32_t a1, uint32_t a2, uint32_t a3, uint32_t b0, uint32_t b1) {
    asm VOL("mma.sync.aligned.m16n8k16.row.col.f32.bf16.bf16.f32 {%0,%1,%2,%3}, {%4,%5,%6,%7}, {%8,%9}, {%0,%1,%2,%3};"
        : "+f"(d[0]), "+f"(d[1]), "+f"(d[2]), "+f"(d[3]) : "r"(a0), "r"(a1), "r"(a2), "r"(a3), "r"(b0), "r"(b1));
}
__device__ __forceinline__ void mma1688z(float* d, uint32_t a0, uint32_t a1, uint32_t b0) {
    asm VOL("mma.sync.aligned.m16n8k8.row.col.f32.bf16.bf16.f32 {%0,%1,%2,%3}, {%4,%5}, {%6}, {%7,%7,%7,%7};"
        : "=f"(d[0]), "=f"(d[1]), "=f"(d[2]), "=f"(d[3]) : "r"(a0), "r"(a1), "r"(b0), "f"(0.f));
}
__device__ __forceinline__ uint32_t pack2(float lo, float hi) {
    uint32_t r; asm VOL("cvt.rn.bf16x2.f32 %0, %1, %2;" : "=r"(r) : "f"(hi), "f"(lo)); return r;
}
__device__ __forceinline__ float silu_h(float h) {
    float t; asm VOL("tanh.approx.f32 %0, %1;" : "=f"(t) : "f"(h)); return fmaf(h, t, h);
}
__device__ __forceinline__ uint32_t mul_lo(uint32_t v, uint32_t r) {
    __nv_bfloat162 a = *(__nv_bfloat162*)&v, b = *(__nv_bfloat162*)&r; __nv_bfloat162 c = __hmul2(a, __low2bfloat162(b)); return *(uint32_t*)&c;
}
__device__ __forceinline__ uint32_t mul_hi(uint32_t v, uint32_t r) {
    __nv_bfloat162 a = *(__nv_bfloat162*)&v, b = *(__nv_bfloat162*)&r; __nv_bfloat162 c = __hmul2(a, __high2bfloat162(b)); return *(uint32_t*)&c;
}
__device__ __forceinline__ uint2 lds64(uint32_t a) {
    uint2 r; asm volatile("ld.shared.v2.u32 {%0,%1}, [%2];" : "=r"(r.x), "=r"(r.y) : "r"(a)); return r;
}
__device__ __forceinline__ uint4 lds128(uint32_t a) {
    uint4 r; asm volatile("ld.shared.v4.u32 {%0,%1,%2,%3}, [%4];" : "=r"(r.x), "=r"(r.y), "=r"(r.z), "=r"(r.w) : "r"(a) : "memory"); return r;
}
__device__ __forceinline__ void bar_sync(int id, int n) { asm volatile("bar.sync %0, %1;" :: "r"(id), "r"(n) : "memory"); }
__device__ __forceinline__ void bar_arrive(int id, int n) { asm volatile("bar.arrive %0, %1;" :: "r"(id), "r"(n) : "memory"); }
__device__ __forceinline__ void mbar_wait(uint32_t bar, uint32_t ph) {
    uint32_t done; int spins = 0;
    do {
        asm volatile("{.reg .pred p; mbarrier.try_wait.parity.shared.b64 p, [%1], %2; selp.u32 %0,1,0,p;}" : "=r"(done) : "r"(bar), "r"(ph) : "memory");
    } while (!done && ++spins < (1 << 22));
}
__device__ __forceinline__ unsigned gbar_read(const unsigned* ctr) {
    unsigned v; asm volatile("ld.relaxed.gpu.global.u32 %0, [%1];" : "=r"(v) : "l"(ctr) : "memory");
    return v;
}
__device__ __forceinline__ void gbar_arrive(unsigned* ctr) {
    asm volatile("red.add.release.gpu.global.u32 [%0], 1;" :: "l"(ctr) : "memory");
}
__device__ __forceinline__ bool gbar_wait(const unsigned* ctr, unsigned target) {
    unsigned v; int spins = 0;
    while (true) {
        asm volatile("ld.acquire.gpu.global.u32 %0, [%1];" : "=r"(v) : "l"(ctr) : "memory");
        if ((int)(v - target) >= 0 || ++spins > (1 << 22)) break;
        if (GSLEEP) __nanosleep(GSLEEP);
    }
    return (int)(v - target) >= 0;
}
__device__ __forceinline__ int chunk_start4(int c) { return (c * NE4) / NB; }
__device__ __forceinline__ float bf2f(uint32_t h) { return __uint_as_float(h << 16); }

__device__ __noinline__ void slow_path(unsigned char* smem, int n0, int nn, const uint16_t* x, const int* src, const int* dst,
                                       const uint16_t* Y, const uint16_t* ef, const uint16_t* w_rad, const uint16_t* cg,
                                       const uint16_t* w_mix, __nv_bfloat16* out) {
    float* agg = (float*)smem;
    const int tid = threadIdx.x, lane = tid & 31, w = tid >> 5;
    bar_sync(1, NT);
    for (int i = tid; i < NPB * 512; i += NT) agg[i] = 0.f;
    bar_sync(1, NT);
    for (int e0 = w * 32; e0 < NE; e0 += NT) {
        int dl = dst[e0 + lane] - n0;
        unsigned m = __ballot_sync(0xffffffff, dl >= 0 && dl < nn);
        while (m) {
            int l = __ffs(m) - 1; m &= m - 1;
            int e = e0 + l, d = __shfl_sync(0xffffffff, dl, l), s = src[e];
            float T[16];
            for (int i = 0; i < 4; i++) for (int o = 0; o < 4; o++) {
                float a = 0.f;
                for (int f = 0; f < 4; f++) a += bf2f(Y[e * 4 + f]) * bf2f(cg[i * 16 + f * 4 + o]);
                T[i * 4 + o] = a;
            }
            for (int k = 0; k < 4; k++) {
                int c = lane + 32 * k;
                float z = 0.f;
                for (int j = 0; j < 4; j++) z += bf2f(ef[e * 4 + j]) * bf2f(w_rad[j * 128 + c]);
                float R = z / (1.f + __expf(-z));
                for (int o = 0; o < 4; o++) {
                    float a = 0.f;
                    for (int i = 0; i < 4; i++) a += bf2f(x[(size_t)s * 512 + c * 4 + i]) * T[i * 4 + o];
                    atomicAdd(&agg[d * 512 + c * 4 + o], R * a);
                }
            }
        }
    }
    bar_sync(1, NT);
    for (int i = tid; i < nn * 512; i += NT) {
        int n = i >> 9, d = (i >> 2) & 127, o = i & 3;
        float a = 0.f;
        for (int c = 0; c < 128; c++) a += agg[n * 512 + c * 4 + o] * bf2f(w_mix[c * 128 + d]);
        out[(size_t)(n0 + n) * 512 + (i & 511)] = __float2bfloat16(a);
    }
}

#define PACE 22750
#define YDELAY 300
#define BFENCE 0
#define ASYM 0
#define KFIRST 0
#define GATE0 1
#define SWAP 1
#define RTRUNC 1
#define PGAP 0
#define ROT 0
#define BATCH 0
#define SKIPPAD 1
#define EPI 2
#define LEAD 0
#define RELAT 2
#define POFF 3100
#define PSLEEP 32
#define PTOL0 300
#define PTOL 800
__global__ void __launch_bounds__(NT, 1)
tfn_kernel(const unsigned char* __restrict__ x, const int4* __restrict__ src4, const int4* __restrict__ dst4,
           const uint4* __restrict__ Y, const uint4* __restrict__ ef, const uint16_t* __restrict__ w_rad,
           const uint16_t* __restrict__ cg, const uint4* __restrict__ w_mix, uint32_t* __restrict__ out, Scratch* __restrict__ gs) {
    extern __shared__ __align__(1024) unsigned char smem[];
    const uint32_t sb = (uint32_t)__cvta_generic_to_shared(smem);
    const int b = blockIdx.x, tid = threadIdx.x, lane = tid & 31, g = lane >> 2, t = lane & 3;
    const int w = __shfl_sync(0xffffffff, tid >> 5, 0);
    uint32_t* stage = (uint32_t*)(smem + SM_STAGE);
    uint32_t* hist = (uint32_t*)(smem + SM_HIST);
    uint32_t* cnt = (uint32_t*)(smem + SM_MISC);
    uint32_t* deg = cnt + 136;
    uint32_t* order = deg + 104;
    uint32_t* cnt2 = order + 80;
    volatile uint32_t* flag = cnt2 + 136;
    const uint32_t mbarK = sb + SM_MISC + 1920, mbarR = mbarK + 8, mbarW = mbarK + 16;
    const int n0 = b * NPB, nn = min(NPB, NN - n0);
    TSTAMP(0);

    const int c0 = chunk_start4(b), c1 = chunk_start4(b + 1);
    const bool has4 = c0 + tid < c1;
    int4 d4 = make_int4(0, 0, 0, 0), s4 = d4;
    if (has4) { d4 = __ldg(dst4 + c0 + tid); s4 = __ldg(src4 + c0 + tid); }
    unsigned tgt = 0;
    if (tid == NT - 1) {
        tgt = gbar_read(&gs->bar[0]);
        asm volatile("mbarrier.init.shared.b64 [%0], 1;" :: "r"(mbarK));
        asm volatile("mbarrier.init.shared.b64 [%0], 1;" :: "r"(mbarR));
        asm volatile("mbarrier.init.shared.b64 [%0], 512;" :: "r"(mbarW));
        asm volatile("fence.mbarrier_init.release.cluster;" ::: "memory");
        flag[0] = 0; flag[12] = 0; flag[13] = 0; flag[15] = 0;
    }
    if (w == CW) {
        asm volatile("cp.async.cg.shared.global [%0], [%1], 16;" :: "r"(sb + SM_SMALL + lane * 16), "l"(w_rad + lane * 8) : "memory");
        asm volatile("cp.async.cg.shared.global [%0], [%1], 16;" :: "r"(sb + SM_SMALL + 512 + lane * 16), "l"(w_rad + 256 + lane * 8) : "memory");
        if (lane < 8) asm volatile("cp.async.cg.shared.global [%0], [%1], 16;" :: "r"(sb + SM_SMALL + 1024 + lane * 16), "l"(cg + lane * 8) : "memory");
    }
    ((uint4*)hist)[tid] = make_uint4(0, 0, 0, 0);
    {
        const uint32_t dk = (80 + b % 22) * KN + (b & 31) * KB;
#pragma unroll
        for (int j = 0; j < 3; j++) if (tid + j * NT < NB * CELL / 4) ((uint4*)stage)[tid + j * NT] = make_uint4(dk, dk, dk, dk);
    }
    if (tid < 136) cnt[tid] = 0;
    if (tid == 0) { *(uint4*)(smem + SM_MISC + 1824 + 32) = make_uint4(0, 0, 0, 0); *(uint4*)(smem + SM_RECS + NB * CELL * 16) = make_uint4(0, 0, 0, 0); }
    if (tid < 80) { deg[tid] = 127 - tid; order[tid] = tid; }
    __syncthreads();
    TSTAMP(9);
    if (tid == 64) {
        if (YDELAY) __nanosleep(YDELAY);
        asm volatile("mbarrier.arrive.expect_tx.shared.b64 _, [%0], %1;" :: "r"(mbarR), "r"((c1 - c0) * 64) : "memory");
        asm volatile("cp.async.bulk.shared::cluster.global.mbarrier::complete_tx::bytes [%0], [%1], %2, [%3];"
                     :: "r"(sb + SM_RAWY), "l"(Y + 2 * c0), "r"((c1 - c0) * 32), "r"(mbarR) : "memory");
        asm volatile("cp.async.bulk.shared::cluster.global.mbarrier::complete_tx::bytes [%0], [%1], %2, [%3];"
                     :: "r"(sb + SM_RAWE), "l"(ef + 2 * c0), "r"((c1 - c0) * 32), "r"(mbarR) : "memory");
    }

    uint32_t bin[4] = {0, 0, 0, 0}, slot[4] = {0, 0, 0, 0};
    if (has4) {
        const uint32_t dd[4] = {(uint32_t)d4.x, (uint32_t)d4.y, (uint32_t)d4.z, (uint32_t)d4.w}, ss[4] = {(uint32_t)s4.x, (uint32_t)s4.y, (uint32_t)s4.z, (uint32_t)s4.w};
#pragma unroll
        for (int k = 0; k < 4; k++) { bin[k] = dd[k] / NPB; slot[k] = atomicAdd(&cnt[bin[k]], 1); }
#pragma unroll
        for (int k = 0; k < 4; k++) stage[bin[k] * CELL + min(slot[k], CELL - 1)] = (dd[k] - bin[k] * NPB) * KN + ss[k];
    }
    if (w == CW) {
        if (tid == NT - 1) { tgt = tgt / NB + 1; flag[14] = (tgt & 1) << 31; tgt *= NB; }
        asm volatile("cp.async.wait_all;" ::: "memory");
    }
    bar_sync(1, NT);
    TSTAMP(1);
    const uint32_t tag = flag[14];
#pragma unroll
    for (int j = 0; j < 2; j++) {
        const int i = tid + j * NT;
        if (i < NPIECE) {
            const uint2 sa = *(const uint2*)(stage + i * 6), sc = *(const uint2*)(stage + i * 6 + 2);
            uint2 se = *(const uint2*)(stage + i * 6 + 4);
            const uint32_t cf = cnt[i >> 3], cn = min(cf, 63u);
            if ((i & 7) == 7) {
                const uint32_t al = cf > CELL - 8 ? 7 : 0;
                uint32_t o;
                asm volatile("atom.shared.add.u32 %0, [%1], %2;" : "=r"(o) : "r"(sb + SM_MISC + 1824 + 60), "r"(cf + al) : "memory");
                se.y = (o + al) & ~al;
                cnt2[i >> 3] = se.y;
            }
            asm volatile("{.reg .b64 lo, hi; mov.b64 lo, {%1,%2}; mov.b64 hi, {%3,%4}; st.relaxed.gpu.global.v2.b64 [%0], {lo, hi};}"
                         :: "l"(gs->keys + ((i >> 3) * NB + b) * 8 + ((i ^ b) & 7)),
                            "r"(sa.x | (se.x << 20)), "r"(sa.y | ((se.x >> 12) << 20) | ((cn & 7) << 28) | tag),
                            "r"(sc.x | (se.y << 20)), "r"(sc.y | ((se.y >> 12) << 20) | ((cn >> 3) << 28) | tag) : "memory");
        }
    }
    bar_sync(1, NT);
    if (tid == NT - 1) {
        TSTAMPC(10);
        asm volatile("red.add.relaxed.gpu.global.u32 [%0], 1;" :: "l"(&gs->bar[0]) : "memory");
        asm volatile("mbarrier.arrive.expect_tx.shared.b64 _, [%0], %1;" :: "r"(mbarK), "r"(NPIECE * 16) : "memory");
        if (ADELAY) mbar_wait(mbarR, 0);
        gbar_wait(&gs->bar[0], tgt);
        TSTAMPC(13);
        asm volatile("fence.proxy.async.global;" ::: "memory");
        asm volatile("cp.async.bulk.shared::cluster.global.mbarrier::complete_tx::bytes [%0], [%1], %2, [%3];"
                 :: "r"(sb + SM_KEYS), "l"(gs->keys + b * NPIECE), "r"(NPIECE * 16), "r"(mbarK) : "memory");
    }
    __syncwarp();
    uint32_t at[4];
    {
        const int o = g & 3, f = 2 * (t & 1);
#pragma unroll
        for (int i = 0; i < 4; i++) {
            const uint16_t* cp = (const uint16_t*)(smem + SM_SMALL + 1024) + i * 16 + f * 4 + o;
            at[i] = (t >> 1) == (g >> 2) ? cp[0] | ((uint32_t)cp[4] << 16) : 0;
        }
    }

    const int q = lane >> 3, c = lane & 7;
    const uint32_t ring0 = sb + SM_RING + w * 2048;
    uint32_t wdst = ring0 + q * 128 + ((c + 2 * q) & 7) * 16;
    uint32_t rsrc = ring0 + t * 128 + ((g + 2 * t) & 7) * 16;
    uint32_t recl = sb + SM_META + w * (CAP * STEPB) + g * 16 + (t & 1) * 8, srcl = sb + SM_META + w * (CAP * STEPB) + 128 + q * 8;
    uint32_t flg = sb + SM_MISC + (136 + 104 + 80 + 136) * 4;
    asm volatile("" : "+r"(wdst), "+r"(rsrc), "+r"(recl), "+r"(srcl), "+r"(flg));
    uint32_t key[2][6], ha[2][6], rk[2][6], kidx[2], ka[2];
    int nk[2];
#pragma unroll
    for (int j = 0; j < 2; j++) {
        const int i0 = j ? 2 * 608 - 1 - tid : tid, i = min(i0, NPIECE - 1), r = i / NB, cc = i - r * NB;
        ka[j] = sb + SM_KEYS + (cc * 8 + ((r ^ cc) & 7)) * 16;
        kidx[j] = (cc * CELL + r * 6) << 17;
        nk[j] = i0 < NPIECE && w < CW ? -6 * r : -1000;
    }
    asm volatile("" : "+r"(at[0]), "+r"(at[1]), "+r"(at[2]), "+r"(at[3]), "+r"(ka[0]), "+r"(ka[1]), "+r"(kidx[0]), "+r"(kidx[1]), "+r"(nk[0]), "+r"(nk[1]));
    if (w == CW) {
        __syncwarp();
        bar_sync(7, NT);
        if (tid == NT - 1) {
            TSTAMPC(11);
            asm volatile("cp.async.bulk.global.shared::cta.bulk_group [%0], [%1], %2;"
                         :: "l"(gs->recs + b * RCH), "r"(sb + SM_ROUT), "r"(((flag[15] + 1) & ~1u) * 16) : "memory");
            asm volatile("cp.async.bulk.commit_group; cp.async.bulk.wait_group 0;" ::: "memory");
            TSTAMPC(14);
            asm volatile("red.add.relaxed.gpu.global.u32 [%0], 1;" :: "l"(&gs->bar[1]) : "memory");
            TSTAMPC(15);
        }
    } else {
        if (w < 8) {
            const uint32_t* wp = (const uint32_t*)(smem + SM_SMALL) + (t & 1) * 128 + 8 * w + g;
            const uint32_t wr0 = t < 2 ? wp[0] : 0, wr1 = t < 2 ? wp[64] : 0;
            *(uint2*)(smem + SM_AZ + (w >> 1) * 512 + lane * 16 + (w & 1) * 8) =
                make_uint2(pack2(0.5f * bf2f(wr0 & 0xFFFF), 0.5f * bf2f(wr1 & 0xFFFF)), pack2(0.5f * bf2f(wr0 >> 16), 0.5f * bf2f(wr1 >> 16)));
        }
        const bool sw = g & 1;
        uint32_t rp[4];
#pragma unroll
        for (int k = 0; k < 4; k++) rp[k] = cnt2[bin[k]] + slot[k];
        uint4* ro = (uint4*)(smem + SM_ROUT);
        uint4 *p0 = ro + (sw ? rp[2] : rp[0]), *p1 = ro + (sw ? rp[3] : rp[1]), *p2 = ro + (sw ? rp[0] : rp[2]), *p3 = ro + (sw ? rp[1] : rp[3]);
        const uint32_t ya = sb + SM_RAWY + tid * 32 + (sw ? 16 : 0);
        mbar_wait(mbarR, 0);
        TSTAMP(18);
        if (has4) {
            const uint4 y0 = lds128(ya), e0 = lds128(ya + (SM_RAWE - SM_RAWY)), y1 = lds128(ya ^ 16), e1 = lds128((ya ^ 16) + (SM_RAWE - SM_RAWY));
            *p0 = make_uint4(y0.x, e0.x, y0.y, e0.y); *p1 = make_uint4(y0.z, e0.z, y0.w, e0.w);
            *p2 = make_uint4(y1.x, e1.x, y1.y, e1.y); *p3 = make_uint4(y1.z, e1.z, y1.w, e1.w);
        }
        asm volatile("fence.proxy.async.shared::cta;" ::: "memory");
        bar_arrive(7, NT);
    }
    __syncwarp();
    TSTAMP(2);

    if (w < CW) {
        mbar_wait(mbarK, 0);
        TSTAMP(3);
        uint4 v[2] = {lds128(ka[0]), lds128(ka[1])};
#pragma unroll
        for (int j = 0; j < 2; j++) {
            int spins = 0;
            while ((int)((v[j].y ^ tag) | (v[j].w ^ tag)) < 0) {
                asm volatile("{.reg .b64 lo, hi; ld.relaxed.gpu.global.v2.b64 {lo, hi}, [%4]; mov.b64 {%0,%1}, lo; mov.b64 {%2,%3}, hi;}"
                             : "=r"(v[j].x), "=r"(v[j].y), "=r"(v[j].z), "=r"(v[j].w) : "l"((const unsigned char*)(gs->keys + b * NPIECE) + (ka[j] - sb - SM_KEYS)) : "memory");
                if (++spins > (1 << 20)) { *flag = 1; break; }
            }
            const uint32_t hc = ((v[j].y >> 28) & 7) | ((v[j].w >> 25) & 0x38);
            if (j == 1 && nk[j] == -42) {
                cnt[kidx[j] / (CELL << 17)] = hc | ((v[j].z >> 20) << 8);
                v[j].w |= ((80 * KN) >> 12) << 20;
            }
            if (hc > CELL - 1) *flag = 1;
            nk[j] += hc;
            if (nk[j] > 0) {
                key[j][0] = v[j].x & 0xFFFFF; key[j][1] = v[j].y & 0xFFFFF; key[j][2] = v[j].z & 0xFFFFF; key[j][3] = v[j].w & 0xFFFFF;
                key[j][4] = (v[j].x >> 20) | ((v[j].y >> 8) & 0xFF000); key[j][5] = (v[j].z >> 20) | ((v[j].w >> 8) & 0xFF000);
#pragma unroll
                for (int u = 0; u < 6; u++) {
                    ha[j][u] = __umulhi(key[j][u], 0xFFFFFFFFu / KB + 1);
                    rk[j][u] = atomicAdd(&hist[ha[j][u]], 1);
                    atomicAdd(&deg[ha[j][u] >> 5], 128);
                }
            }
        }
        bar_sync(9, NT - 32);
        TSTAMP(20);
#pragma unroll
        for (int j = 0; j < 2; j++) kidx[j] += ((cnt[kidx[j] / (CELL << 17)] >> 8) & 7) << 17;
        const int n = tid >> 3, sub = tid & 7;
        const uint32_t me = deg[n];
        int r = 0;
#pragma unroll
        for (int k = 0; k < 5; k++) { const uint2 dd = *(const uint2*)(deg + sub * 10 + 2 * k); r += (dd.x > me) + (dd.y > me); }
        r += __shfl_xor_sync(0xffffffff, r, 1); r += __shfl_xor_sync(0xffffffff, r, 2); r += __shfl_xor_sync(0xffffffff, r, 4);
        if (sub == 0) order[r] = n;
    }
    bar_sync(1, NT);
    TSTAMP(22);
    uint32_t len2;
    {
        const uint2 na = *(const uint2*)(order + 2 * w);
        uint2 nb = *(const uint2*)(order + 78 - 2 * w);
        const uint32_t ia0 = na.x * 32 + lane, ia1 = na.y * 32 + lane;
        const uint32_t ha0 = hist[ia0], ha1 = hist[ia1];
        uint32_t hb0 = hist[nb.y * 32 + lane], hb1 = hist[nb.x * 32 + lane];
        const int su = __reduce_add_sync(0xffffffff, (int)(ha0 - ha1) * (2 * lane - 31)), sv = __reduce_add_sync(0xffffffff, (int)(hb0 - hb1) * (2 * lane - 31));
        if ((su ^ sv) >= 0) {
            nb = make_uint2(nb.y, nb.x);
            const uint32_t tmp = hb0; hb0 = hb1; hb1 = tmp;
            *(uint2*)(order + 78 - 2 * w) = nb;
        }
        const uint32_t ib0 = nb.y * 32 + lane, ib1 = nb.x * 32 + lane;
        const uint32_t ca = ha0 + (ha1 << 16), cab = ca + hb0 + (hb1 << 16);
        uint32_t inc = cab;
#pragma unroll
        for (int o = 1; o < 32; o <<= 1)
            asm volatile("{.reg .pred p; .reg .u32 u; shfl.sync.up.b32 u|p, %0, %1, 0, 0xffffffff; @p add.u32 %0, %0, u;}" : "+r"(inc) : "r"(o));
        const uint32_t ea = inc - cab, eb = ea + ca, base = sb + SM_LIST + w * 2048;
        uint2* pos = (uint2*)(smem + SM_POS);
        pos[ia0] = make_uint2(base + (ea & 0xFFFF) * 8, na.x * (0u - 4 * KN));
        pos[ib0] = make_uint2(base + (eb & 0xFFFF) * 8, nb.y * (0u - 4 * KN) + 0x10000);
        pos[ia1] = make_uint2(base + 4 + (ea >> 16) * 8, na.y * (0u - 4 * KN));
        pos[ib1] = make_uint2(base + 4 + (eb >> 16) * 8, nb.x * (0u - 4 * KN) + 0x10000);
        if (max(inc & 0xFFFF, inc >> 16) > 4 * CAP) *flag = 1;
        len2 = __shfl_sync(0xffffffff, inc, 31);
    }
    uint32_t ci = cnt[min(w + NW * lane, NB)];
    ci = ((((w + NW * lane) * (RCH / 8) + (ci >> 11)) << 8) | (ci & 0xFF)) + ((ci >> 8) & 7);
    if (w == CW) {
        unsigned long long tbase;
        asm volatile("mov.u64 %0, %%globaltimer;" : "=l"(tbase));
        tbase += POFF;
        flag[1] = (uint32_t)tbase; flag[4] = (uint32_t)tbase; flag[5] = (uint32_t)(tbase >> 32);
        if (lane == 0) {
            asm volatile("red.max.relaxed.gpu.global.u64 [%0], %1;" :: "l"(&gs->t0), "l"(tbase) : "memory");
            if (b < 128) asm volatile("cp.async.bulk.prefetch.L2.global [%0], 256;" :: "l"(w_mix + b * 16));
        }
    }
    if (w == CW) {
        bar_arrive(9, NT);
        if (tid == NT - 1) { if (!gbar_wait(&gs->bar[1], tgt)) *flag = 1; TSTAMPC(17); }
        __syncwarp();
    } else {
        bar_sync(9, NT);
        TSTAMP(21);
        const uint32_t over = *flag;
#pragma unroll
        for (int j = 0; j < 2; j++) {
            if (nk[j] > 0) {
                uint2 h[6];
#pragma unroll
                for (int u = 0; u < 6; u++) h[u] = lds64(sb + SM_POS + ha[j][u] * 8);
                if (over) nk[j] = 0;
#pragma unroll
                for (int u = 0; u < 6; u++)
                    asm volatile("{.reg .pred p; setp.gt.s32 p, %2, %3; @p st.shared.u32 [%0], %1;}"
                                 :: "r"(h[u].x + rk[j][u] * 8), "r"(key[j][u] * 4 + h[u].y + (kidx[j] + (u << 17))), "r"(nk[j]), "r"(u) : "memory");
            }
        }
    }
    bar_sync(1, NT);
    TSTAMP(4);
    if (*flag) {
        slow_path(smem, n0, nn, (const uint16_t*)x, (const int*)src4, (const int*)dst4, (const uint16_t*)Y, (const uint16_t*)ef, w_rad, cg,
                  (const uint16_t*)w_mix, (__nv_bfloat16*)out);
        return;
    }
    {
        const uint4* gp = gs->recs + lane;
        const uint32_t sp = sb + SM_RECS + (w * CELL + lane) * 16;
#pragma unroll
        for (int j = 0; j < 7; j++) {
            const uint32_t cj = __shfl_sync(0xffffffff, ci, j);
            asm volatile("{.reg .pred p; setp.lt.u32 p, %2, %3; @p cp.async.cg.shared.global [%0], [%1], 16;}"
                         :: "r"(sp + j * (NW * CELL * 16)), "l"(gp + (size_t)(cj >> 8) * 8), "r"(lane), "r"(cj & 0xFF) : "memory");
        }
        for (uint32_t m = __ballot_sync(0xffffffff, (ci & 0xFF) > 32); m; m &= m - 1) {
            const int j = __ffs(m) - 1;
            const uint32_t cj = __shfl_sync(0xffffffff, ci, j);
            if (lane + 32 < (cj & 0xFF))
                asm volatile("cp.async.cg.shared.global [%0], [%1], 16;" :: "r"(sp + j * (NW * CELL * 16) + 512), "l"(gp + (size_t)(cj >> 8) * 8 + 32) : "memory");
        }
        asm volatile("cp.async.commit_group;" ::: "memory");
    }
    const int S = __shfl_sync(0xffffffff, max((int)(max(len2 & 0xFFFF, len2 >> 16) + 3) >> 2, DS + 2), 0);
    const int mylen = (lane & 1) ? len2 >> 16 : len2 & 0xFFFF;
    constexpr int NRAW = (CAP + 3) / 4;
    uint32_t bits0 = 0, raw[NRAW];
    unsigned char* meta = smem + SM_META + w * (CAP * STEPB);
#pragma unroll
    for (int k = 0; k < NRAW; k++) raw[k] = mylen ? ((uint32_t*)(smem + SM_LIST + w * 2048))[min(k * 16 + (lane >> 1), mylen - 1) * 2 + (lane & 1)] : 4 * n0;
    const uint32_t sv0 = raw[0] & 0xFFFF;
    const unsigned char* pbase = x + c * 16;
    auto cpa2 = [&](uint32_t dstp, uint32_t sv) {
        asm volatile("cp.async.cg.shared.global [%0], [%1], 16; cp.async.cg.shared.global [%0+1024], [%1+128], 16;"
                     :: "r"(dstp), "l"(pbase + (size_t)sv * 256) : "memory");
    };
    auto cpa2p = [&](uint32_t dstp, uint32_t sv) {
        asm volatile("{.reg .pred p; setp.ge.s32 p, %2, 0; @p cp.async.cg.shared.global [%0], [%1], 16; @p cp.async.cg.shared.global [%0+1024], [%1+128], 16;}"
                     :: "r"(dstp), "l"(pbase + (size_t)sv * 256), "r"(sv) : "memory");
    };
    auto fill = [&](int i) {
        cpa2(wdst + i * SLOTB, __shfl_sync(0xffffffff, sv0, 8 * i + 2 * q)); cpa2(wdst + i * SLOTB + 512, __shfl_sync(0xffffffff, sv0, 8 * i + 2 * q + 1));
        asm volatile("cp.async.commit_group;" ::: "memory");
    };
    fill(0);
    TSTAMP(5);
    if (tid == 0) asm volatile("cp.async.cg.shared.global [%0], [%1], 16;" :: "r"(flg + 32), "l"(&gs->t0) : "memory");
    auto relay = [&]() {
        uint32_t g0, g1, b0, b1;
        asm volatile("ld.volatile.shared.v2.u32 {%0,%1}, [%4+32]; ld.volatile.shared.v2.u32 {%2,%3}, [%4+16];"
                     : "=r"(g0), "=r"(g1), "=r"(b0), "=r"(b1) : "r"(flg) : "memory");
        const unsigned long long dg = (((unsigned long long)g1 << 32) | g0) - (((unsigned long long)b1 << 32) | b0);
        asm volatile("{.reg .pred p, q; setp.eq.u32 p, %1, 0; setp.lt.u64 q, %2, 30000; @q st.shared.u32 [%3+4], %4;\n"
                     "@p cp.async.cg.shared.global [%3+32], [%0], 16;}"
                     :: "l"(&gs->t0), "r"(lane), "l"(dg), "r"(flg), "r"(g0) : "memory");
    };
    uint32_t ra[NRAW];
#pragma unroll
    for (int k = 0; k < NRAW; k++) {
        const uint32_t m = (__ballot_sync(0xffffffff, raw[k] & 0x10000) >> g) & 0x01010101u;
        bits0 |= ((m * 0x10204080u) >> 28) << (4 * k);
        ra[k] = sb + SM_RECS + (k * 16 + (lane >> 1) < mylen ? raw[k] >> 17 : NB * CELL) * 16;
    }
    if (t < 2) bits0 = ~bits0;
    asm volatile("" : "+r"(bits0), "+r"(ra[0]), "+r"(ra[1]), "+r"(ra[2]), "+r"(ra[3]), "+r"(ra[4]));
    fill(1);
    asm volatile("cp.async.wait_group 2;" ::: "memory");
    bar_sync(1, NT);
    TSTAMP(19);
    {
        uint4 rv[NRAW];
#pragma unroll
        for (int k = 0; k < NRAW - 1; k++) rv[k] = lds128(ra[k]);
        if ((NRAW - 1) * 4 < S) rv[NRAW - 1] = lds128(ra[NRAW - 1]);
        if (w == 0) relay();
        fill(2);
        bar_sync(1, NT);
        TSTAMP(12);
        unsigned char* mr = meta + (q - 1) * STEPB + c * 16;
        unsigned char* ms = meta + (q - DS - 1) * STEPB + 128 + c * 4;
#pragma unroll
        for (int k = 0; k < NRAW; k++) {
            if (k == 0) {
                *(uint4*)(mr + (q == 0 ? S * STEPB : 0)) = rv[k];
                *(uint32_t*)(ms + S * STEPB) = sv0 + F_WRAP + (SKIPPAD && (lane >> 1) >= mylen ? 0x80000000u : 0);
            } else if (k * 4 + q < S) {
                *(uint4*)(mr + k * 4 * STEPB) = rv[k];
                *(uint32_t*)(ms + k * 4 * STEPB + (k == 1 && q == 0 ? S * STEPB : 0)) = (raw[k] & 0xFFFF) + (ROT && k == 1 && q == 0 ? F_WRAP : 0) + (SKIPPAD && k * 16 + (lane >> 1) >= mylen ? 0x80000000u : 0);
            }
        }
    }
    __syncwarp();
    const uint32_t tphase = PACE / 4;
    uint32_t dreg;
    {
        const int ls = lane >= S ? min(lane - S, S - 1) : lane, st = ROT ? ls : ls == 0 ? S - 1 : ls - 1;
        const uint4 u0 = *(const uint4*)(meta + st * STEPB + 128), u1 = *(const uint4*)(meta + st * STEPB + 144);
        int pos = (u0.x + u0.y + u0.z + u0.w + u1.x + u1.y + u1.z + u1.w) << 1 >> 6;
        pos += ((u0.x & F_WRAP) ? NN : 0) + (lane >= S ? NN : 0) - NN * (2 * DS + 1 + 2 * ROT) / 32;
        dreg = pos * (int)(tphase - PGAP) / NN + (lane >= S ? PGAP : 0);
    }
    fill(3);
    TSTAMP(6);

    uint32_t* stash = (uint32_t*)(gs->stash + (b * NW + w) * 256) + lane;
    float acc[4][4];
#pragma unroll
    for (int i = 0; i < 16; i++) acc[i / 4][i % 4] = 0.f;
    uint4 az = *(const uint4*)(smem + SM_AZ + lane * 16);
    uint32_t dcur = dreg, dl = 0, now = flag[1], tcur = 0;
    uint32_t mp = 0, smask = 1, didx = PSTEP;
    uint32_t mend = S * STEPB;
    uint2 r = lds64(mend - STEPB + recl), s0 = lds64(mend - STEPB + srcl);
    uint2 sp = make_uint2(s0.x - F_WRAP, s0.y - F_WRAP);
    uint4 xa, xb, xc, xd;
    auto loadx = [&](const uint32_t off, const bool lag = false) {
        if (lag) asm volatile("cp.async.wait_group %0;" :: "n"(DS - 2) : "memory");
        else asm volatile("cp.async.wait_group %0;" :: "n"(DS - 1) : "memory");
        xa = lds128(rsrc + off); xb = lds128(rsrc + off + 512); xc = lds128(rsrc + off + 1024); xd = lds128(rsrc + off + 1536);
    };
    auto step = [&](const uint32_t off, const int mode, const bool pc = true) {
        if (mode == 0 && pc) { unsigned long long n64; asm volatile("mov.u64 %0, %%globaltimer;" : "=l"(n64)); now = (uint32_t)n64; }
        const uint2 rc = r;
        uint2 sc = s0;
        if (mode != 4 + ROT) r = lds64(mp + recl);
        if (mode == 0) { if (ROT) sc = lds64(mp + srcl); else s0 = lds64(mp + srcl); }
        auto mem = [&]() {
        const bool oddslot = (off / SLOTB) & 1;
        if (mode != 5) loadx(off, BATCH && mode == 0 && oddslot);
        if (mode == 0) {
            if (pc) { dl = __shfl_sync(0xffffffff, dcur, didx); didx += PSTEP; }
            if (BATCH && oddslot) {
                cpa2(wdst + off - SLOTB, sp.x); cpa2(wdst + off - SLOTB + 512, sp.y);
                asm volatile("cp.async.commit_group;" ::: "memory");
            }
            if (SKIPPAD) { cpa2p(wdst + off, sc.x); cpa2p(wdst + off + 512, sc.y); }
            else if (!BATCH || oddslot) { cpa2(wdst + off, sc.x); cpa2(wdst + off + 512, sc.y); }
            else sp = sc;
        }
        if (mode == 1 && w < 16) {
#pragma unroll
            for (int j = 0; j < 4; j++) {
                const int kk = 4 * j + q, ch = 16 * (w & 7) + 2 * (kk & 7) + (kk >> 3);
                asm volatile("cp.async.cg.shared.global [%0], [%1], 16;" :: "r"(ring0 + kk * 128 + ((c ^ (kk & 7)) << 4)), "l"(w_mix + ch * 16 + (w >> 3) * 8 + c) : "memory");
            }
            asm volatile("cp.async.mbarrier.arrive.noinc.shared.b64 [%0];" :: "r"(mbarW) : "memory");
        }
        if (mode == 2 || mode == 3) {
#pragma unroll
            for (int j = 0; j < 4; j += mode - 1)
                asm volatile("cp.async.cg.shared.global [%0], [%1], 16;" :: "r"(ring0 + off + j * 512 + lane * 16), "l"(stash + (mode - 2) * 512 + j * 128 + lane * 3) : "memory");
        }
        if (mode < 4 && !(BATCH && mode == 0 && !oddslot)) asm volatile("cp.async.commit_group;" ::: "memory");
        };
        if (!ROT) mem();
        float z[4], y[4], t1[4], t2[4];
        mma1688z(z, az.x, az.y, rc.y);
        mma1688z(y, az.z, az.w, rc.y);
        uint32_t bt;
        asm("{.reg .pred p; .reg .b32 m; and.b32 m, %2, %3; setp.ne.u32 p, m, 0; selp.b32 %0, %1, 0, p;}" : "=r"(bt) : "r"(rc.x), "r"(bits0), "r"(smask));
        mma1688z(t1, at[0], at[1], bt);
        mma1688z(t2, at[2], at[3], bt);
        const uint32_t T0 = pack2(t1[0], t1[2]), T1 = pack2(t2[0], t2[2]), T2 = pack2(t1[1], t1[3]), T3 = pack2(t2[1], t2[3]);
        uint32_t R[8];
#pragma unroll
        for (int i = 0; i < 4; i++) { R[i] = __float_as_uint(silu_h(z[i])); R[4 + i] = __float_as_uint(silu_h(y[i])); }
        mma16816(acc[0], mul_hi(xa.x, R[0]), mul_hi(xa.z, R[2]), mul_hi(xa.y, R[0]), mul_hi(xa.w, R[2]), T0, T1);
        mma16816(acc[1], mul_hi(xb.x, R[1]), mul_hi(xb.z, R[3]), mul_hi(xb.y, R[1]), mul_hi(xb.w, R[3]), T2, T3);
        mma16816(acc[2], mul_hi(xc.x, R[4]), mul_hi(xc.z, R[6]), mul_hi(xc.y, R[4]), mul_hi(xc.w, R[6]), T0, T1);
        mma16816(acc[3], mul_hi(xd.x, R[5]), mul_hi(xd.z, R[7]), mul_hi(xd.y, R[5]), mul_hi(xd.w, R[7]), T2, T3);
        if (ROT) mem();
        mp += STEPB; smask <<= 1;
    };
    if (ROT) {
        loadx(0);
        if (!BATCH) {
            cpa2(wdst, sp.x); cpa2(wdst + 512, sp.y);
            asm volatile("cp.async.commit_group;" ::: "memory");
        }
    }
    auto putacc = [&](uint32_t* p) {
#pragma unroll
        for (int i = 0; i < 16; i++) acc[i / 4][i % 4] *= 1.0028f;
        p[0] = pack2(acc[0][0], acc[0][1]); p[32] = pack2(acc[0][2], acc[0][3]); p[64] = pack2(acc[2][0], acc[2][1]); p[96] = pack2(acc[2][2], acc[2][3]);
        p[256] = pack2(acc[1][0], acc[1][1]); p[288] = pack2(acc[1][2], acc[1][3]); p[320] = pack2(acc[3][0], acc[3][1]); p[352] = pack2(acc[3][2], acc[3][3]);
    };
    int ph = 0;
    auto phase_end = [&](const bool odd) {
        az = lds128(sb + SM_AZ + (ph + 1) * 512 + lane * 16);
        putacc(stash + ph * ph * 128);
#pragma unroll
        for (int i = 0; i < 16; i++) acc[i / 4][i % 4] = 0.f;
        pbase += 256; mp = 0; smask = 1; ph++;
        dcur += tphase; didx = odd ? PSTEP : 1;
        if (BATCH && odd) { sp.x -= F_WRAP; sp.y -= F_WRAP; }
        if (ph == 3) mend -= (DS + ROT) * STEPB;
        WSTAMP(ph - 1);
    };
    uint32_t t0 = now;
    auto report = [&](uint32_t cand) {
        uint32_t b0, b1;
        asm volatile("ld.volatile.shared.v2.u32 {%0,%1}, [%2+16];" : "=r"(b0), "=r"(b1) : "r"(flg) : "memory");
        asm volatile("{.reg .pred p; setp.eq.u32 p, %2, 0; @p red.max.relaxed.gpu.global.u64 [%0], %1;}"
                     :: "l"(&gs->t0), "l"((((unsigned long long)b1 << 32) | b0) + (cand - b0)), "r"(lane) : "memory");
    };
    if (w == PW) {
        asm volatile("mov.u32 %0, %%globaltimer_lo;" : "=r"(now));
        now += PTOL - PTOL0;
    }
    const uint32_t bias = w == 0 ? 1u << 20 : 0;
    if (w == 0) relay();
    dcur += bias;
    auto body = [&](const int k) -> bool {
        if (k == T0K) asm volatile("ld.volatile.shared.u32 %0, [%1+4];" : "=r"(t0) : "r"(flg));
        const bool pc = PSTEP == 1 || (k & 1);
        step(((k + ROT) & 3) * SLOTB, 0, pc);
        if (!pc) {
            if (mp == mend) {
                if (k == 3 - ROT && ph == 3) return true;
                phase_end(false);
            }
        } else if (mp == mend || now < dl) {
            if (mp == mend) {
                if (k == 3 - ROT && ph == 3) return true;
                phase_end(true);
            }
            if (w == 0) { dl -= 1u << 20; if (k & 1) relay(); }
            asm volatile("{.reg .pred p; .reg .u32 d;\n"
                         "PACE_LOOP: mov.u32 d, %%globaltimer_lo; sub.u32 d, %0, d; setp.lt.u32 p, d, 32768; @p nanosleep.u32 %1; @p bra.uni PACE_LOOP;}"
                         :: "r"(dl), "n"(PSLEEP) : "memory");
        }
        return false;
    };
    asm volatile("{.reg .pred p; .reg .u32 d;\n"
                 "PACE_LOOP: mov.u32 d, %%globaltimer_lo; sub.u32 d, %0, d; setp.lt.u32 p, d, 32768; @p nanosleep.u32 %1; @p bra.uni PACE_LOOP;}"
                 :: "r"(__shfl_sync(0xffffffff, dreg, 0) + t0), "n"(PSLEEP) : "memory");
    while (true) {
        if (w == PW) {
            const uint32_t cand = now - dl + tcur - PTOL;
            if ((int)(cand - t0) > 0) report(cand);
        }
        dcur += t0 - tcur; tcur = t0;
        body(0); body(1);
        if (body(2)) break;
        if (body(3)) break;
    }
    __syncwarp();
    step(0, 1); step(SLOTB, 2); step(2 * SLOTB, 3); step(3 * SLOTB, 4);
    if (ROT) step(0, 5);
    WSTAMP(3);

    {
        putacc((uint32_t*)(smem + SM_RING + 2 * SLOTB + w * 2048 + 512) + lane);
        const int wg = w >> 2, w4 = w & 3;
        int nd[8];
#pragma unroll
        for (int j = 0; j < 8; j++) { const int l = wg * 8 + j; nd[j] = order[(t >> 1) ? 79 - l : l]; asm volatile("" : "+r"(nd[j])); }
        const bool odd = t & 1;
        uint2* ob = (uint2*)out + (size_t)n0 * 128 + w4 * 16 + g + (odd ? 8 : 0);
        asm volatile("cp.async.wait_all;" ::: "memory");
        mbar_wait(mbarW, 0);
        asm volatile("fence.proxy.async.shared::cta;" ::: "memory");
        TSTAMP(26);
        bar_sync(2 + wg, 128);
        if ((tid & 127) == 0) {
            const uint32_t ticket = atomicAdd((uint32_t*)flag + 12, 1);
            int spins = 0;
            while (flag[13] + LEAD < ticket && ++spins < (1 << 16)) {}
        }
        bar_sync(2 + wg, 128);
        TSTAMP(27);
        const uint64_t descA0 = (uint64_t)(((sb + SM_RING) & 0x3FFFF) >> 4) | ((uint64_t)1 << 16) | ((uint64_t)(1024 >> 4) << 32) | ((uint64_t)1 << 62);
        const uint64_t descB0 = (uint64_t)(((sb + SM_RING + SLOTB + wg * 8192) & 0x3FFFF) >> 4) | ((uint64_t)(128 >> 4) << 16) | ((uint64_t)(1024 >> 4) << 32);
        float d[2][32];
        asm volatile("wgmma.fence.sync.aligned;" ::: "memory");
#pragma unroll
        for (int mt = 0; mt < 2; mt++) {
#pragma unroll
            for (int ks = 0; ks < 8; ks++) {
                const uint64_t da = descA0 + (uint64_t)((ks * 2048 + mt * 16384) >> 4), db = descB0 + (uint64_t)(((ks & 3) * 256 + (ks >> 2) * SLOTB) >> 4);
                asm volatile("{.reg .pred p; setp.ne.b32 p, %34, 0;\n"
                    "wgmma.mma_async.sync.aligned.m64n64k16.f32.bf16.bf16 "
                    "{%0,%1,%2,%3,%4,%5,%6,%7,%8,%9,%10,%11,%12,%13,%14,%15,%16,%17,%18,%19,%20,%21,%22,%23,%24,%25,%26,%27,%28,%29,%30,%31}, %32, %33, p, 1, 1, 1, 1;}"
                    : "+f"(d[mt][0]), "+f"(d[mt][1]), "+f"(d[mt][2]), "+f"(d[mt][3]), "+f"(d[mt][4]), "+f"(d[mt][5]), "+f"(d[mt][6]), "+f"(d[mt][7]),
                      "+f"(d[mt][8]), "+f"(d[mt][9]), "+f"(d[mt][10]), "+f"(d[mt][11]), "+f"(d[mt][12]), "+f"(d[mt][13]), "+f"(d[mt][14]), "+f"(d[mt][15]),
                      "+f"(d[mt][16]), "+f"(d[mt][17]), "+f"(d[mt][18]), "+f"(d[mt][19]), "+f"(d[mt][20]), "+f"(d[mt][21]), "+f"(d[mt][22]), "+f"(d[mt][23]),
                      "+f"(d[mt][24]), "+f"(d[mt][25]), "+f"(d[mt][26]), "+f"(d[mt][27]), "+f"(d[mt][28]), "+f"(d[mt][29]), "+f"(d[mt][30]), "+f"(d[mt][31])
                    : "l"(da), "l"(db), "r"(ks));
            }
            asm volatile("wgmma.commit_group.sync.aligned;" ::: "memory");
            if (mt == RELAT - 1) asm volatile("{.reg .pred p; setp.eq.u32 p, %1, 0; @p red.shared.add.u32 [%0+52], 1;}" :: "r"(flg), "r"(tid & 127) : "memory");
        }
#pragma unroll
        for (int mt = 0; mt < 2; mt++) {
            if (mt == 0) asm volatile("wgmma.wait_group.sync.aligned 1;" ::: "memory");
            else asm volatile("wgmma.wait_group.sync.aligned 0;" ::: "memory");
            if (RELAT == 0 && mt == 0 && (tid & 127) == 0) atomicAdd((uint32_t*)flag + 13, 1);
            TSTAMP(23 + mt);
#pragma unroll
            for (int i = 0; i < 32; i++) asm volatile("" : "+f"(d[mt][i]) :: "memory");
#pragma unroll
            for (int j = 0; j < 8; j++) {
                constexpr float cs = RTRUNC == 2 ? 1.0028f : 1.f;
                const uint32_t v0 = pack2(cs * d[mt][4 * j], cs * d[mt][4 * j + 1]), v1 = pack2(cs * d[mt][4 * j + 2], cs * d[mt][4 * j + 3]);
                const uint32_t rv = __shfl_xor_sync(0xffffffff, odd ? v0 : v1, 1);
                if (nd[j] < nn) ob[nd[j] * 128 + mt * 64] = odd ? make_uint2(rv, v1) : make_uint2(v0, rv);
            }
        }
    }
    TSTAMP(8);
}

}

extern "C" void kernel_launch(void* const* d_in, const int* in_sizes, int n_in, void* d_out, int out_size) {
    (void)in_sizes; (void)n_in; (void)out_size;
    cudaFuncSetAttribute(tfn_kernel, cudaFuncAttributeMaxDynamicSharedMemorySize, SM_TOTAL);
    Scratch* gs = nullptr;
    cudaGetSymbolAddress((void**)&gs, g_scratch);
    cudaLaunchConfig_t cfg = {};
    cfg.gridDim = dim3(NB); cfg.blockDim = dim3(NT); cfg.dynamicSmemBytes = SM_TOTAL; cfg.stream = cudaStreamPerThread;
    cudaLaunchAttribute at[1];
    at[0].id = cudaLaunchAttributeCooperative; at[0].val.cooperative = 1;
    cfg.attrs = at; cfg.numAttrs = 1;
    cudaLaunchKernelEx(&cfg, tfn_kernel, (const unsigned char*)d_in[0], (const int4*)d_in[1], (const int4*)d_in[2],
                       (const uint4*)d_in[3], (const uint4*)d_in[4], (const uint16_t*)d_in[5], (const uint16_t*)d_in[6],
                       (const uint4*)d_in[7], (uint32_t*)d_out, gs);
}
```

```cpp
#include <cuda_runtime.h>
#include <cuda_bf16.h>
#include <stdint.h>

namespace {

constexpr int NN = 10000;
constexpr int NE = 320000;
constexpr int NB = 132;
constexpr int NW = 20;
constexpr int NT = NW * 32;
constexpr int CW = NW - 1;
#define PWARP 10
constexpr int PW = PWARP;
constexpr int NPB = 76;
constexpr int CELL = 48;
constexpr int RCH = 2880;
constexpr int CAP = 19;
constexpr int DS = 4;
constexpr int STEPB = 160;
constexpr int NE4 = NE / 4;
constexpr int NPIECE = NB * 8;
constexpr int KB = 320, KN = 32 * KB;
constexpr uint32_t F_PAD = 0x80000000u;
constexpr uint32_t F_WRAP = 1;

constexpr int SLOTB = NW * 2048;
constexpr int SM_RING = 0;
constexpr int SM_META = SM_RING + DS * SLOTB;
constexpr int SM_AZ = SM_META + NW * CAP * STEPB;
constexpr int SM_MISC = SM_AZ + 2048;
constexpr int SM_TOTAL = SM_MISC + 2048;
constexpr int SM_STAGE = SM_RING;
constexpr int SM_HIST = SM_RING + 25600;
constexpr int SM_POS = SM_RING;
constexpr int SM_SMALL = SM_HIST + 13056;
constexpr int SM_LIST = SM_RING + SLOTB;
constexpr int SM_ROUT = SM_RING + 2 * SLOTB;
constexpr int SM_RECS = SM_RING + 3 * SLOTB;
constexpr int SM_RAWY = SM_META;
constexpr int SM_RAWE = SM_RAWY + 608 * 32;
constexpr int SM_KEYS = SM_RAWE + 608 * 32;
static_assert(SM_TOTAL <= 232448 && SM_KEYS + NPIECE * 16 <= SM_AZ, "smem");
static_assert(SM_RECS + NB * CELL * 16 + 16 <= SM_AZ && SM_KEYS + NPIECE * 16 <= SM_RECS + NB * CELL * 16 && SM_SMALL + 1152 <= SLOTB && DS == 4, "smem");

struct Scratch {
    uint4 keys[NB * NPIECE];
    uint4 recs[NB * RCH];
    uint4 stash[NB * NW * 256];
    unsigned bar[4];
    unsigned long long t0, pad;
};
__device__ Scratch g_scratch;
#define TSTAMP(i)
#define TSTAMPC(i)
#define WSTAMP(i)

__device__ __forceinline__ void mma16816(float* d, uint32_t a0, uint32_t a1, uint32_t a2, uint32_t a3, uint32_t b0, uint32_t b1) {
    asm("mma.sync.aligned.m16n8k16.row.col.f32.bf16.bf16.f32 {%0,%1,%2,%3}, {%4,%5,%6,%7}, {%8,%9}, {%0,%1,%2,%3};"
        : "+f"(d[0]), "+f"(d[1]), "+f"(d[2]), "+f"(d[3]) : "r"(a0), "r"(a1), "r"(a2), "r"(a3), "r"(b0), "r"(b1));
}
__device__ __forceinline__ void mma1688z(float* d, uint32_t a0, uint32_t a1, uint32_t b0) {
    asm("mma.sync.aligned.m16n8k8.row.col.f32.bf16.bf16.f32 {%0,%1,%2,%3}, {%4,%5}, {%6}, {%7,%7,%7,%7};"
        : "=f"(d[0]), "=f"(d[1]), "=f"(d[2]), "=f"(d[3]) : "r"(a0), "r"(a1), "r"(b0), "f"(0.f));
}
__device__ __forceinline__ uint32_t pack2(float lo, float hi) {
    uint32_t r; asm("cvt.rn.bf16x2.f32 %0, %1, %2;" : "=r"(r) : "f"(hi), "f"(lo)); return r;
}
__device__ __forceinline__ float silu_h(float h) {
    float t; asm("tanh.approx.f32 %0, %1;" : "=f"(t) : "f"(h)); return fmaf(h, t, h);
}
__device__ __forceinline__ uint32_t mul_lo(uint32_t v, uint32_t r) {
    __nv_bfloat162 a = *(__nv_bfloat162*)&v, b = *(__nv_bfloat162*)&r; __nv_bfloat162 c = __hmul2(a, __low2bfloat162(b)); return *(uint32_t*)&c;
}
__device__ __forceinline__ uint32_t mul_hi(uint32_t v, uint32_t r) {
    __nv_bfloat162 a = *(__nv_bfloat162*)&v, b = *(__nv_bfloat162*)&r; __nv_bfloat162 c = __hmul2(a, __high2bfloat162(b)); return *(uint32_t*)&c;
}
__device__ __forceinline__ uint2 lds64(uint32_t a) {
    uint2 r; asm volatile("ld.shared.v2.u32 {%0,%1}, [%2];" : "=r"(r.x), "=r"(r.y) : "r"(a)); return r;
}
__device__ __forceinline__ uint4 lds128(uint32_t a) {
    uint4 r; asm volatile("ld.shared.v4.u32 {%0,%1,%2,%3}, [%4];" : "=r"(r.x), "=r"(r.y), "=r"(r.z), "=r"(r.w) : "r"(a) : "memory"); return r;
}
__device__ __forceinline__ void bar_sync(int id, int n) { asm volatile("bar.sync %0, %1;" :: "r"(id), "r"(n) : "memory"); }
__device__ __forceinline__ void bar_arrive(int id, int n) { asm volatile("bar.arrive %0, %1;" :: "r"(id), "r"(n) : "memory"); }
__device__ __forceinline__ void mbar_wait(uint32_t bar, uint32_t ph) {
    uint32_t done; int spins = 0;
    do {
        asm volatile("{.reg .pred p; mbarrier.try_wait.parity.shared.b64 p, [%1], %2; selp.u32 %0,1,0,p;}" : "=r"(done) : "r"(bar), "r"(ph) : "memory");
    } while (!done && ++spins < (1 << 22));
}
__device__ __forceinline__ unsigned gbar_read(const unsigned* ctr) {
    unsigned v; asm volatile("ld.relaxed.gpu.global.u32 %0, [%1];" : "=r"(v) : "l"(ctr) : "memory");
    return v;
}
__device__ __forceinline__ void gbar_arrive(unsigned* ctr) {
    asm volatile("red.add.release.gpu.global.u32 [%0], 1;" :: "l"(ctr) : "memory");
}
__device__ __forceinline__ bool gbar_wait(const unsigned* ctr, unsigned target) {
    unsigned v; int spins = 0;
    while (true) {
        asm volatile("ld.acquire.gpu.global.u32 %0, [%1];" : "=r"(v) : "l"(ctr) : "memory");
        if ((int)(v - target) >= 0 || ++spins > (1 << 22)) break;
    }
    return (int)(v - target) >= 0;
}
__device__ __forceinline__ int chunk_start4(int c) { return (c * NE4) / NB; }
__device__ __forceinline__ float bf2f(uint32_t h) { return __uint_as_float(h << 16); }

__device__ __noinline__ void slow_path(unsigned char* smem, int n0, int nn, const uint16_t* x, const int* src, const int* dst,
                                       const uint16_t* Y, const uint16_t* ef, const uint16_t* w_rad, const uint16_t* cg,
                                       const uint16_t* w_mix, __nv_bfloat16* out) {
    float* agg = (float*)smem;
    const int tid = threadIdx.x, lane = tid & 31, w = tid >> 5;
    bar_sync(1, NT);
    for (int i = tid; i < NPB * 512; i += NT) agg[i] = 0.f;
    bar_sync(1, NT);
    for (int e0 = w * 32; e0 < NE; e0 += NT) {
        int dl = dst[e0 + lane] - n0;
        unsigned m = __ballot_sync(0xffffffff, dl >= 0 && dl < nn);
        while (m) {
            int l = __ffs(m) - 1; m &= m - 1;
            int e = e0 + l, d = __shfl_sync(0xffffffff, dl, l), s = src[e];
            float T[16];
            for (int i = 0; i < 4; i++) for (int o = 0; o < 4; o++) {
                float a = 0.f;
                for (int f = 0; f < 4; f++) a += bf2f(Y[e * 4 + f]) * bf2f(cg[i * 16 + f * 4 + o]);
                T[i * 4 + o] = a;
            }
            for (int k = 0; k < 4; k++) {
                int c = lane + 32 * k;
                float z = 0.f;
                for (int j = 0; j < 4; j++) z += bf2f(ef[e * 4 + j]) * bf2f(w_rad[j * 128 + c]);
                float R = z / (1.f + __expf(-z));
                for (int o = 0; o < 4; o++) {
                    float a = 0.f;
                    for (int i = 0; i < 4; i++) a += bf2f(x[(size_t)s * 512 + c * 4 + i]) * T[i * 4 + o];
                    atomicAdd(&agg[d * 512 + c * 4 + o], R * a);
                }
            }
        }
    }
    bar_sync(1, NT);
    for (int i = tid; i < nn * 512; i += NT) {
        int n = i >> 9, d = (i >> 2) & 127, o = i & 3;
        float a = 0.f;
        for (int c = 0; c < 128; c++) a += agg[n * 512 + c * 4 + o] * bf2f(w_mix[c * 128 + d]);
        out[(size_t)(n0 + n) * 512 + (i & 511)] = __float2bfloat16(a);
    }
}

#define PACE 22750
#define YDELAY 300
#define POFF 3100
#define PSLEEP 32
#define PTOL0 300
#define PTOL 900
__global__ void __launch_bounds__(NT, 1)
tfn_kernel(const unsigned char* __restrict__ x, const int4* __restrict__ src4, const int4* __restrict__ dst4,
           const uint4* __restrict__ Y, const uint4* __restrict__ ef, const uint16_t* __restrict__ w_rad,
           const uint16_t* __restrict__ cg, const uint4* __restrict__ w_mix, uint32_t* __restrict__ out, Scratch* __restrict__ gs) {
    extern __shared__ __align__(1024) unsigned char smem[];
    const uint32_t sb = (uint32_t)__cvta_generic_to_shared(smem);
    const int b = blockIdx.x, tid = threadIdx.x, lane = tid & 31, g = lane >> 2, t = lane & 3;
    const int w = __shfl_sync(0xffffffff, tid >> 5, 0);
    uint32_t* stage = (uint32_t*)(smem + SM_STAGE);
    uint32_t* hist = (uint32_t*)(smem + SM_HIST);
    uint32_t* cnt = (uint32_t*)(smem + SM_MISC);
    uint32_t* deg = cnt + 136;
    uint32_t* order = deg + 104;
    uint32_t* cnt2 = order + 80;
    volatile uint32_t* flag = cnt2 + 136;
    const uint32_t mbarK = sb + SM_MISC + 1920, mbarR = mbarK + 8, mbarW = mbarK + 16;
    const int n0 = b * NPB, nn = min(NPB, NN - n0);
    TSTAMP(0);

    const int c0 = chunk_start4(b), c1 = chunk_start4(b + 1);
    const bool has4 = c0 + tid < c1;
    int4 d4 = make_int4(0, 0, 0, 0), s4 = d4;
    if (has4) { d4 = __ldg(dst4 + c0 + tid); s4 = __ldg(src4 + c0 + tid); }
    unsigned tgt = 0;
    if (tid == NT - 1) {
        tgt = gbar_read(&gs->bar[0]);
        asm volatile("mbarrier.init.shared.b64 [%0], 1;" :: "r"(mbarK));
        asm volatile("mbarrier.init.shared.b64 [%0], 1;" :: "r"(mbarR));
        asm volatile("mbarrier.init.shared.b64 [%0], 512;" :: "r"(mbarW));
        asm volatile("fence.mbarrier_init.release.cluster;" ::: "memory");
        flag[0] = 0; flag[12] = 0; flag[13] = 0; flag[15] = 0;
    }
    if (w == CW) {
        asm volatile("cp.async.cg.shared.global [%0], [%1], 16;" :: "r"(sb + SM_SMALL + lane * 16), "l"(w_rad + lane * 8) : "memory");
        asm volatile("cp.async.cg.shared.global [%0], [%1], 16;" :: "r"(sb + SM_SMALL + 512 + lane * 16), "l"(w_rad + 256 + lane * 8) : "memory");
        if (lane < 8) asm volatile("cp.async.cg.shared.global [%0], [%1], 16;" :: "r"(sb + SM_SMALL + 1024 + lane * 16), "l"(cg + lane * 8) : "memory");
    }
    ((uint4*)hist)[tid] = make_uint4(0, 0, 0, 0);
    {
        const uint32_t dk = (80 + b % 22) * KN + (b & 31) * KB;
#pragma unroll
        for (int j = 0; j < 3; j++) if (tid + j * NT < NB * CELL / 4) ((uint4*)stage)[tid + j * NT] = make_uint4(dk, dk, dk, dk);
    }
    if (tid < 136) cnt[tid] = 0;
    if (tid == 0) { *(uint4*)(smem + SM_MISC + 1824 + 32) = make_uint4(0, 0, 0, 0); *(uint4*)(smem + SM_RECS + NB * CELL * 16) = make_uint4(0, 0, 0, 0); }
    if (tid < 80) { deg[tid] = 127 - tid; order[tid] = tid; }
    __syncthreads();
    TSTAMP(9);
    if (tid == 64) {
        if (YDELAY) __nanosleep(YDELAY);
        asm volatile("mbarrier.arrive.expect_tx.shared.b64 _, [%0], %1;" :: "r"(mbarR), "r"((c1 - c0) * 64) : "memory");
        asm volatile("cp.async.bulk.shared::cluster.global.mbarrier::complete_tx::bytes [%0], [%1], %2, [%3];"
                     :: "r"(sb + SM_RAWY), "l"(Y + 2 * c0), "r"((c1 - c0) * 32), "r"(mbarR) : "memory");
        asm volatile("cp.async.bulk.shared::cluster.global.mbarrier::complete_tx::bytes [%0], [%1], %2, [%3];"
                     :: "r"(sb + SM_RAWE), "l"(ef + 2 * c0), "r"((c1 - c0) * 32), "r"(mbarR) : "memory");
    }

    uint32_t bin[4] = {0, 0, 0, 0}, slot[4] = {0, 0, 0, 0};
    if (has4) {
        const uint32_t dd[4] = {(uint32_t)d4.x, (uint32_t)d4.y, (uint32_t)d4.z, (uint32_t)d4.w}, ss[4] = {(uint32_t)s4.x, (uint32_t)s4.y, (uint32_t)s4.z, (uint32_t)s4.w};
#pragma unroll
        for (int k = 0; k < 4; k++) { bin[k] = dd[k] / NPB; slot[k] = atomicAdd(&cnt[bin[k]], 1); }
#pragma unroll
        for (int k = 0; k < 4; k++) stage[bin[k] * CELL + min(slot[k], CELL - 1)] = (dd[k] - bin[k] * NPB) * KN + ss[k];
    }
    if (w == CW) {
        if (tid == NT - 1) { tgt = tgt / NB + 1; flag[14] = (tgt & 1) << 31; tgt *= NB; }
        asm volatile("cp.async.wait_all;" ::: "memory");
    }
    bar_sync(1, NT);
    TSTAMP(1);
    const uint32_t tag = flag[14];
#pragma unroll
    for (int j = 0; j < 2; j++) {
        const int i = tid + j * NT;
        if (i < NPIECE) {
            const uint2 sa = *(const uint2*)(stage + i * 6), sc = *(const uint2*)(stage + i * 6 + 2);
            uint2 se = *(const uint2*)(stage + i * 6 + 4);
            const uint32_t cf = cnt[i >> 3], cn = min(cf, 63u);
            if ((i & 7) == 7) {
                const uint32_t al = cf > CELL - 8 ? 7 : 0;
                uint32_t o;
                asm volatile("atom.shared.add.u32 %0, [%1], %2;" : "=r"(o) : "r"(sb + SM_MISC + 1824 + 60), "r"(cf + al) : "memory");
                se.y = (o + al) & ~al;
                cnt2[i >> 3] = se.y;
            }
            asm volatile("{.reg .b64 lo, hi; mov.b64 lo, {%1,%2}; mov.b64 hi, {%3,%4}; st.relaxed.gpu.global.v2.b64 [%0], {lo, hi};}"
                         :: "l"(gs->keys + ((i >> 3) * NB + b) * 8 + ((i ^ b) & 7)),
                            "r"(sa.x | (se.x << 20)), "r"(sa.y | ((se.x >> 12) << 20) | ((cn & 7) << 28) | tag),
                            "r"(sc.x | (se.y << 20)), "r"(sc.y | ((se.y >> 12) << 20) | ((cn >> 3) << 28) | tag) : "memory");
        }
    }
    bar_sync(1, NT);
    if (tid == NT - 1) {
        TSTAMPC(10);
        asm volatile("red.add.relaxed.gpu.global.u32 [%0], 1;" :: "l"(&gs->bar[0]) : "memory");
        asm volatile("mbarrier.arrive.expect_tx.shared.b64 _, [%0], %1;" :: "r"(mbarK), "r"(NPIECE * 16) : "memory");
        gbar_wait(&gs->bar[0], tgt);
        TSTAMPC(13);
        asm volatile("fence.proxy.async.global;" ::: "memory");
        asm volatile("cp.async.bulk.shared::cluster.global.mbarrier::complete_tx::bytes [%0], [%1], %2, [%3];"
                 :: "r"(sb + SM_KEYS), "l"(gs->keys + b * NPIECE), "r"(NPIECE * 16), "r"(mbarK) : "memory");
    }
    __syncwarp();
    uint32_t at[4];
    {
        const int o = g & 3, f = 2 * (t & 1);
#pragma unroll
        for (int i = 0; i < 4; i++) {
            const uint16_t* cp = (const uint16_t*)(smem + SM_SMALL + 1024) + i * 16 + f * 4 + o;
            at[i] = (t >> 1) == (g >> 2) ? cp[0] | ((uint32_t)cp[4] << 16) : 0;
        }
    }

    const int q = lane >> 3, c = lane & 7;
    const uint32_t ring0 = sb + SM_RING + w * 2048;
    uint32_t wdst = ring0 + q * 128 + ((c + 2 * q) & 7) * 16;
    uint32_t rsrc = ring0 + t * 128 + ((g + 2 * t) & 7) * 16;
    uint32_t recl = sb + SM_META + w * (CAP * STEPB) + g * 16 + (t & 1) * 8, srcl = sb + SM_META + w * (CAP * STEPB) + 128 + q * 8;
    uint32_t flg = sb + SM_MISC + (136 + 104 + 80 + 136) * 4;
    asm volatile("" : "+r"(wdst), "+r"(rsrc), "+r"(recl), "+r"(srcl), "+r"(flg));
    uint32_t key[2][6], ha[2][6], rk[2][6], kidx[2], ka[2];
    int nk[2];
#pragma unroll
    for (int j = 0; j < 2; j++) {
        const int i0 = j ? 2 * 608 - 1 - tid : tid, i = min(i0, NPIECE - 1), r = i / NB, cc = i - r * NB;
        ka[j] = sb + SM_KEYS + (cc * 8 + ((r ^ cc) & 7)) * 16;
        kidx[j] = (cc * CELL + r * 6) << 17;
        nk[j] = i0 < NPIECE && w < CW ? -6 * r : -1000;
    }
    asm volatile("" : "+r"(at[0]), "+r"(at[1]), "+r"(at[2]), "+r"(at[3]), "+r"(ka[0]), "+r"(ka[1]), "+r"(kidx[0]), "+r"(kidx[1]), "+r"(nk[0]), "+r"(nk[1]));
    if (w == CW) {
        __syncwarp();
        bar_sync(7, NT);
        if (tid == NT - 1) {
            TSTAMPC(11);
            asm volatile("cp.async.bulk.global.shared::cta.bulk_group [%0], [%1], %2;"
                         :: "l"(gs->recs + b * RCH), "r"(sb + SM_ROUT), "r"(((flag[15] + 1) & ~1u) * 16) : "memory");
            asm volatile("cp.async.bulk.commit_group; cp.async.bulk.wait_group 0;" ::: "memory");
            TSTAMPC(14);
            asm volatile("red.add.relaxed.gpu.global.u32 [%0], 1;" :: "l"(&gs->bar[1]) : "memory");
            TSTAMPC(15);
        }
    } else {
        if (w < 8) {
            const uint32_t* wp = (const uint32_t*)(smem + SM_SMALL) + (t & 1) * 128 + 8 * w + g;
            const uint32_t wr0 = t < 2 ? wp[0] : 0, wr1 = t < 2 ? wp[64] : 0;
            *(uint2*)(smem + SM_AZ + (w >> 1) * 512 + lane * 16 + (w & 1) * 8) =
                make_uint2(pack2(0.5f * bf2f(wr0 & 0xFFFF), 0.5f * bf2f(wr1 & 0xFFFF)), pack2(0.5f * bf2f(wr0 >> 16), 0.5f * bf2f(wr1 >> 16)));
        }
        const bool sw = g & 1;
        uint32_t rp[4];
#pragma unroll
        for (int k = 0; k < 4; k++) rp[k] = cnt2[bin[k]] + slot[k];
        uint4* ro = (uint4*)(smem + SM_ROUT);
        uint4 *p0 = ro + (sw ? rp[2] : rp[0]), *p1 = ro + (sw ? rp[3] : rp[1]), *p2 = ro + (sw ? rp[0] : rp[2]), *p3 = ro + (sw ? rp[1] : rp[3]);
        const uint32_t ya = sb + SM_RAWY + tid * 32 + (sw ? 16 : 0);
        mbar_wait(mbarR, 0);
        TSTAMP(18);
        if (has4) {
            const uint4 y0 = lds128(ya), e0 = lds128(ya + (SM_RAWE - SM_RAWY)), y1 = lds128(ya ^ 16), e1 = lds128((ya ^ 16) + (SM_RAWE - SM_RAWY));
            *p0 = make_uint4(y0.x, e0.x, y0.y, e0.y); *p1 = make_uint4(y0.z, e0.z, y0.w, e0.w);
            *p2 = make_uint4(y1.x, e1.x, y1.y, e1.y); *p3 = make_uint4(y1.z, e1.z, y1.w, e1.w);
        }
        asm volatile("fence.proxy.async.shared::cta;" ::: "memory");
        bar_arrive(7, NT);
    }
    __syncwarp();
    TSTAMP(2);

    if (w < CW) {
        mbar_wait(mbarK, 0);
        TSTAMP(3);
        uint4 v[2] = {lds128(ka[0]), lds128(ka[1])};
#pragma unroll
        for (int j = 0; j < 2; j++) {
            int spins = 0;
            while ((int)((v[j].y ^ tag) | (v[j].w ^ tag)) < 0) {
                asm volatile("{.reg .b64 lo, hi; ld.relaxed.gpu.global.v2.b64 {lo, hi}, [%4]; mov.b64 {%0,%1}, lo; mov.b64 {%2,%3}, hi;}"
                             : "=r"(v[j].x), "=r"(v[j].y), "=r"(v[j].z), "=r"(v[j].w) : "l"((const unsigned char*)(gs->keys + b * NPIECE) + (ka[j] - sb - SM_KEYS)) : "memory");
                if (++spins > (1 << 20)) { *flag = 1; break; }
            }
            const uint32_t hc = ((v[j].y >> 28) & 7) | ((v[j].w >> 25) & 0x38);
            if (j == 1 && nk[j] == -42) {
                cnt[kidx[j] / (CELL << 17)] = hc | ((v[j].z >> 20) << 8);
                v[j].w |= ((80 * KN) >> 12) << 20;
            }
            if (hc > CELL - 1) *flag = 1;
            nk[j] += hc;
            if (nk[j] > 0) {
                key[j][0] = v[j].x & 0xFFFFF; key[j][1] = v[j].y & 0xFFFFF; key[j][2] = v[j].z & 0xFFFFF; key[j][3] = v[j].w & 0xFFFFF;
                key[j][4] = (v[j].x >> 20) | ((v[j].y >> 8) & 0xFF000); key[j][5] = (v[j].z >> 20) | ((v[j].w >> 8) & 0xFF000);
#pragma unroll
                for (int u = 0; u < 6; u++) {
                    ha[j][u] = __umulhi(key[j][u], 0xFFFFFFFFu / KB + 1);
                    rk[j][u] = atomicAdd(&hist[ha[j][u]], 1);
                    atomicAdd(&deg[ha[j][u] >> 5], 128);
                }
            }
        }
        bar_sync(9, NT - 32);
        TSTAMP(20);
#pragma unroll
        for (int j = 0; j < 2; j++) kidx[j] += ((cnt[kidx[j] / (CELL << 17)] >> 8) & 7) << 17;
        const int n = tid >> 3, sub = tid & 7;
        const uint32_t me = deg[n];
        int r = 0;
#pragma unroll
        for (int k = 0; k < 5; k++) { const uint2 dd = *(const uint2*)(deg + sub * 10 + 2 * k); r += (dd.x > me) + (dd.y > me); }
        r += __shfl_xor_sync(0xffffffff, r, 1); r += __shfl_xor_sync(0xffffffff, r, 2); r += __shfl_xor_sync(0xffffffff, r, 4);
        if (sub == 0) order[r] = n;
    }
    bar_sync(1, NT);
    TSTAMP(22);
    uint32_t len2;
    {
        const uint2 na = *(const uint2*)(order + 2 * w);
        uint2 nb = *(const uint2*)(order + 78 - 2 * w);
        const uint32_t ia0 = na.x * 32 + lane, ia1 = na.y * 32 + lane;
        const uint32_t ha0 = hist[ia0], ha1 = hist[ia1];
        uint32_t hb0 = hist[nb.y * 32 + lane], hb1 = hist[nb.x * 32 + lane];
        const int su = __reduce_add_sync(0xffffffff, (int)(ha0 - ha1) * (2 * lane - 31)), sv = __reduce_add_sync(0xffffffff, (int)(hb0 - hb1) * (2 * lane - 31));
        if ((su ^ sv) >= 0) {
            nb = make_uint2(nb.y, nb.x);
            const uint32_t tmp = hb0; hb0 = hb1; hb1 = tmp;
            *(uint2*)(order + 78 - 2 * w) = nb;
        }
        const uint32_t ib0 = nb.y * 32 + lane, ib1 = nb.x * 32 + lane;
        const uint32_t ca = ha0 + (ha1 << 16), cab = ca + hb0 + (hb1 << 16);
        uint32_t inc = cab;
#pragma unroll
        for (int o = 1; o < 32; o <<= 1)
            asm volatile("{.reg .pred p; .reg .u32 u; shfl.sync.up.b32 u|p, %0, %1, 0, 0xffffffff; @p add.u32 %0, %0, u;}" : "+r"(inc) : "r"(o));
        const uint32_t ea = inc - cab, eb = ea + ca, base = sb + SM_LIST + w * 2048;
        uint2* pos = (uint2*)(smem + SM_POS);
        pos[ia0] = make_uint2(base + (ea & 0xFFFF) * 8, na.x * (0u - 4 * KN));
        pos[ib0] = make_uint2(base + (eb & 0xFFFF) * 8, nb.y * (0u - 4 * KN) + 0x10000);
        pos[ia1] = make_uint2(base + 4 + (ea >> 16) * 8, na.y * (0u - 4 * KN));
        pos[ib1] = make_uint2(base + 4 + (eb >> 16) * 8, nb.x * (0u - 4 * KN) + 0x10000);
        if (max(inc & 0xFFFF, inc >> 16) > 4 * CAP) *flag = 1;
        len2 = __shfl_sync(0xffffffff, inc, 31);
    }
    uint32_t ci = cnt[min(w + NW * lane, NB)];
    ci = ((((w + NW * lane) * (RCH / 8) + (ci >> 11)) << 8) | (ci & 0xFF)) + ((ci >> 8) & 7);
    if (w == CW) {
        unsigned long long tbase;
        asm volatile("mov.u64 %0, %%globaltimer;" : "=l"(tbase));
        tbase += POFF;
        flag[1] = (uint32_t)tbase; flag[4] = (uint32_t)tbase; flag[5] = (uint32_t)(tbase >> 32);
        if (lane == 0) {
            asm volatile("red.max.relaxed.gpu.global.u64 [%0], %1;" :: "l"(&gs->t0), "l"(tbase) : "memory");
            if (b < 128) asm volatile("cp.async.bulk.prefetch.L2.global [%0], 256;" :: "l"(w_mix + b * 16));
        }
    }
    if (w == CW) {
        bar_arrive(9, NT);
        if (tid == NT - 1) { if (!gbar_wait(&gs->bar[1], tgt)) *flag = 1; TSTAMPC(17); }
        __syncwarp();
    } else {
        bar_sync(9, NT);
        TSTAMP(21);
        const uint32_t over = *flag;
#pragma unroll
        for (int j = 0; j < 2; j++) {
            if (nk[j] > 0) {
                uint2 h[6];
#pragma unroll
                for (int u = 0; u < 6; u++) h[u] = lds64(sb + SM_POS + ha[j][u] * 8);
                if (over) nk[j] = 0;
#pragma unroll
                for (int u = 0; u < 6; u++)
                    asm volatile("{.reg .pred p; setp.gt.s32 p, %2, %3; @p st.shared.u32 [%0], %1;}"
                                 :: "r"(h[u].x + rk[j][u] * 8), "r"(key[j][u] * 4 + h[u].y + (kidx[j] + (u << 17))), "r"(nk[j]), "r"(u) : "memory");
            }
        }
    }
    bar_sync(1, NT);
    TSTAMP(4);
    if (*flag) {
        slow_path(smem, n0, nn, (const uint16_t*)x, (const int*)src4, (const int*)dst4, (const uint16_t*)Y, (const uint16_t*)ef, w_rad, cg,
                  (const uint16_t*)w_mix, (__nv_bfloat16*)out);
        return;
    }
    {
        const uint4* gp = gs->recs + lane;
        const uint32_t sp = sb + SM_RECS + (w * CELL + lane) * 16;
#pragma unroll
        for (int j = 0; j < 7; j++) {
            const uint32_t cj = __shfl_sync(0xffffffff, ci, j);
            asm volatile("{.reg .pred p; setp.lt.u32 p, %2, %3; @p cp.async.cg.shared.global [%0], [%1], 16;}"
                         :: "r"(sp + j * (NW * CELL * 16)), "l"(gp + (size_t)(cj >> 8) * 8), "r"(lane), "r"(cj & 0xFF) : "memory");
        }
        for (uint32_t m = __ballot_sync(0xffffffff, (ci & 0xFF) > 32); m; m &= m - 1) {
            const int j = __ffs(m) - 1;
            const uint32_t cj = __shfl_sync(0xffffffff, ci, j);
            if (lane + 32 < (cj & 0xFF))
                asm volatile("cp.async.cg.shared.global [%0], [%1], 16;" :: "r"(sp + j * (NW * CELL * 16) + 512), "l"(gp + (size_t)(cj >> 8) * 8 + 32) : "memory");
        }
        asm volatile("cp.async.commit_group;" ::: "memory");
    }
    const int S = __shfl_sync(0xffffffff, max((int)(max(len2 & 0xFFFF, len2 >> 16) + 3) >> 2, DS + 1), 0);
    const int mylen = (lane & 1) ? len2 >> 16 : len2 & 0xFFFF;
    constexpr int NRAW = (CAP + 3) / 4;
    uint32_t bits0 = 0, raw[NRAW];
    unsigned char* meta = smem + SM_META + w * (CAP * STEPB);
#pragma unroll
    for (int k = 0; k < NRAW; k++) raw[k] = mylen ? ((uint32_t*)(smem + SM_LIST + w * 2048))[min(k * 16 + (lane >> 1), mylen - 1) * 2 + (lane & 1)] : 4 * n0;
    const uint32_t sv0 = raw[0] & 0xFFFF;
    const unsigned char* pbase = x + c * 16;
    auto cpa2 = [&](uint32_t dstp, uint32_t sv) {
        asm volatile("cp.async.cg.shared.global [%0], [%1], 16; cp.async.cg.shared.global [%0+1024], [%1+128], 16;"
                     :: "r"(dstp), "l"(pbase + (size_t)sv * 256) : "memory");
    };
    auto cpa2p = [&](uint32_t dstp, uint32_t sv) {
        asm volatile("{.reg .pred p; setp.ge.s32 p, %2, 0; @p cp.async.cg.shared.global [%0], [%1], 16; @p cp.async.cg.shared.global [%0+1024], [%1+128], 16;}"
                     :: "r"(dstp), "l"(pbase + (size_t)sv * 256), "r"(sv) : "memory");
    };
    auto fill = [&](int i) {
        cpa2(wdst + i * SLOTB, __shfl_sync(0xffffffff, sv0, 8 * i + 2 * q)); cpa2(wdst + i * SLOTB + 512, __shfl_sync(0xffffffff, sv0, 8 * i + 2 * q + 1));
        asm volatile("cp.async.commit_group;" ::: "memory");
    };
    fill(0);
    TSTAMP(5);
    if (tid == 0) asm volatile("cp.async.cg.shared.global [%0], [%1], 16;" :: "r"(flg + 32), "l"(&gs->t0) : "memory");
    auto relay = [&]() {
        uint32_t g0, g1, b0, b1;
        asm volatile("ld.volatile.shared.v2.u32 {%0,%1}, [%4+32]; ld.volatile.shared.v2.u32 {%2,%3}, [%4+16];"
                     : "=r"(g0), "=r"(g1), "=r"(b0), "=r"(b1) : "r"(flg) : "memory");
        const unsigned long long dg = (((unsigned long long)g1 << 32) | g0) - (((unsigned long long)b1 << 32) | b0);
        asm volatile("{.reg .pred p, q; setp.eq.u32 p, %1, 0; setp.lt.u64 q, %2, 30000; @q st.shared.u32 [%3+4], %4;\n"
                     "@p cp.async.cg.shared.global [%3+32], [%0], 16;}"
                     :: "l"(&gs->t0), "r"(lane), "l"(dg), "r"(flg), "r"(g0) : "memory");
    };
    uint32_t ra[NRAW];
#pragma unroll
    for (int k = 0; k < NRAW; k++) {
        const uint32_t m = (__ballot_sync(0xffffffff, raw[k] & 0x10000) >> g) & 0x01010101u;
        bits0 |= ((m * 0x10204080u) >> 28) << (4 * k);
        ra[k] = sb + SM_RECS + (k * 16 + (lane >> 1) < mylen ? raw[k] >> 17 : NB * CELL) * 16;
    }
    if (t < 2) bits0 = ~bits0;
    asm volatile("" : "+r"(bits0), "+r"(ra[0]), "+r"(ra[1]), "+r"(ra[2]), "+r"(ra[3]), "+r"(ra[4]));
    fill(1);
    asm volatile("cp.async.wait_group 2;" ::: "memory");
    bar_sync(1, NT);
    TSTAMP(19);
    {
        uint4 rv[NRAW];
#pragma unroll
        for (int k = 0; k < NRAW - 1; k++) rv[k] = lds128(ra[k]);
        if ((NRAW - 1) * 4 < S) rv[NRAW - 1] = lds128(ra[NRAW - 1]);
        if (w == 0) relay();
        fill(2);
        bar_sync(1, NT);
        TSTAMP(12);
        unsigned char* mr = meta + (q - 1) * STEPB + c * 16;
        unsigned char* ms = meta + (q - DS - 1) * STEPB + 128 + c * 4;
#pragma unroll
        for (int k = 0; k < NRAW; k++) {
            if (k == 0) {
                *(uint4*)(mr + (q == 0 ? S * STEPB : 0)) = rv[k];
                *(uint32_t*)(ms + S * STEPB) = sv0 + F_WRAP + ((lane >> 1) >= mylen ? F_PAD : 0);
            } else if (k * 4 + q < S) {
                *(uint4*)(mr + k * 4 * STEPB) = rv[k];
                *(uint32_t*)(ms + k * 4 * STEPB + (k == 1 && q == 0 ? S * STEPB : 0)) = (raw[k] & 0xFFFF) + (k * 16 + (lane >> 1) >= mylen ? F_PAD : 0);
            }
        }
    }
    __syncwarp();
    const uint32_t tphase = PACE / 4;
    uint32_t dreg;
    {
        const int ls = lane >= S ? min(lane - S, S - 1) : lane, st = ls == 0 ? S - 1 : ls - 1;
        const uint4 u0 = *(const uint4*)(meta + st * STEPB + 128), u1 = *(const uint4*)(meta + st * STEPB + 144);
        int pos = (u0.x + u0.y + u0.z + u0.w + u1.x + u1.y + u1.z + u1.w) << 1 >> 6;
        pos += ((u0.x & F_WRAP) ? NN : 0) + (lane >= S ? NN : 0) - NN * (2 * DS + 1) / 32;
        dreg = pos * (int)tphase / NN;
    }
    fill(3);
    TSTAMP(6);

    uint32_t* stash = (uint32_t*)(gs->stash + (b * NW + w) * 256) + lane;
    float acc[4][4];
#pragma unroll
    for (int i = 0; i < 16; i++) acc[i / 4][i % 4] = 0.f;
    uint4 az = *(const uint4*)(smem + SM_AZ + lane * 16);
    uint32_t dcur = dreg, dl = 0, now = flag[1], tcur = 0;
    uint32_t mp = 0, smask = 1, didx = 2;
    uint32_t mend = S * STEPB;
    uint2 r = lds64(mend - STEPB + recl), s0 = lds64(mend - STEPB + srcl);
    auto step = [&](const uint32_t off, const int mode, const bool pc = true) {
        if (mode == 0 && pc) { unsigned long long n64; asm volatile("mov.u64 %0, %%globaltimer;" : "=l"(n64)); now = (uint32_t)n64; }
        const uint2 rc = r, sc = s0;
        if (mode != 4) r = lds64(mp + recl);
        if (mode == 0) s0 = lds64(mp + srcl);
        asm volatile("cp.async.wait_group %0;" :: "n"(DS - 1) : "memory");
        const uint4 xa = lds128(rsrc + off), xb = lds128(rsrc + off + 512), xc = lds128(rsrc + off + 1024), xd = lds128(rsrc + off + 1536);
        if (mode == 0) {
            if (pc) { dl = __shfl_sync(0xffffffff, dcur, didx); didx += 2; }
            cpa2p(wdst + off, sc.x); cpa2p(wdst + off + 512, sc.y);
        }
        if (mode == 1 && w < 16) {
#pragma unroll
            for (int j = 0; j < 4; j++) {
                const int kk = 4 * j + q, ch = 16 * (w & 7) + 2 * (kk & 7) + (kk >> 3);
                asm volatile("cp.async.cg.shared.global [%0], [%1], 16;" :: "r"(ring0 + kk * 128 + ((c ^ (kk & 7)) << 4)), "l"(w_mix + ch * 16 + (w >> 3) * 8 + c) : "memory");
            }
            asm volatile("cp.async.mbarrier.arrive.noinc.shared.b64 [%0];" :: "r"(mbarW) : "memory");
        }
        if (mode == 2 || mode == 3) {
#pragma unroll
            for (int j = 0; j < 4; j += mode - 1)
                asm volatile("cp.async.cg.shared.global [%0], [%1], 16;" :: "r"(ring0 + off + j * 512 + lane * 16), "l"(stash + (mode - 2) * 512 + j * 128 + lane * 3) : "memory");
        }
        if (mode < 4) asm volatile("cp.async.commit_group;" ::: "memory");
        float z[4], y[4], t1[4], t2[4];
        mma1688z(z, az.x, az.y, rc.y);
        mma1688z(y, az.z, az.w, rc.y);
        uint32_t bt;
        asm("{.reg .pred p; .reg .b32 m; and.b32 m, %2, %3; setp.ne.u32 p, m, 0; selp.b32 %0, %1, 0, p;}" : "=r"(bt) : "r"(rc.x), "r"(bits0), "r"(smask));
        mma1688z(t1, at[0], at[1], bt);
        mma1688z(t2, at[2], at[3], bt);
        const uint32_t T0 = pack2(t1[0], t1[2]), T1 = pack2(t2[0], t2[2]), T2 = pack2(t1[1], t1[3]), T3 = pack2(t2[1], t2[3]);
        uint32_t R[8];
#pragma unroll
        for (int i = 0; i < 4; i++) { R[i] = __float_as_uint(silu_h(z[i])); R[4 + i] = __float_as_uint(silu_h(y[i])); }
        mma16816(acc[0], mul_hi(xa.x, R[0]), mul_hi(xa.z, R[2]), mul_hi(xa.y, R[0]), mul_hi(xa.w, R[2]), T0, T1);
        mma16816(acc[1], mul_hi(xb.x, R[1]), mul_hi(xb.z, R[3]), mul_hi(xb.y, R[1]), mul_hi(xb.w, R[3]), T2, T3);
        mma16816(acc[2], mul_hi(xc.x, R[4]), mul_hi(xc.z, R[6]), mul_hi(xc.y, R[4]), mul_hi(xc.w, R[6]), T0, T1);
        mma16816(acc[3], mul_hi(xd.x, R[5]), mul_hi(xd.z, R[7]), mul_hi(xd.y, R[5]), mul_hi(xd.w, R[7]), T2, T3);
        mp += STEPB; smask <<= 1;
    };
    auto putacc = [&](uint32_t* p) {
#pragma unroll
        for (int i = 0; i < 16; i++) acc[i / 4][i % 4] *= 1.0028f;
        p[0] = pack2(acc[0][0], acc[0][1]); p[32] = pack2(acc[0][2], acc[0][3]); p[64] = pack2(acc[2][0], acc[2][1]); p[96] = pack2(acc[2][2], acc[2][3]);
        p[256] = pack2(acc[1][0], acc[1][1]); p[288] = pack2(acc[1][2], acc[1][3]); p[320] = pack2(acc[3][0], acc[3][1]); p[352] = pack2(acc[3][2], acc[3][3]);
    };
    int ph = 0;
    auto phase_end = [&](const int k) {
        az = lds128(sb + SM_AZ + (ph + 1) * 512 + lane * 16);
        putacc(stash + ph * ph * 128);
#pragma unroll
        for (int i = 0; i < 16; i++) acc[i / 4][i % 4] = 0.f;
        pbase += 256; mp = 0; smask = 1; ph++;
        dcur += tphase; didx = 1 + (k & 1);
        if (ph == 3) mend -= DS * STEPB;
        WSTAMP(ph - 1);
    };
    uint32_t t0 = now;
    auto report = [&](uint32_t cand) {
        uint32_t b0, b1;
        asm volatile("ld.volatile.shared.v2.u32 {%0,%1}, [%2+16];" : "=r"(b0), "=r"(b1) : "r"(flg) : "memory");
        asm volatile("{.reg .pred p; setp.eq.u32 p, %2, 0; @p red.max.relaxed.gpu.global.u64 [%0], %1;}"
                     :: "l"(&gs->t0), "l"((((unsigned long long)b1 << 32) | b0) + (cand - b0)), "r"(lane) : "memory");
    };
    if (w == PW) {
        asm volatile("mov.u32 %0, %%globaltimer_lo;" : "=r"(now));
        now += PTOL - PTOL0;
    }
    const uint32_t bias = w == 0 ? 1u << 20 : 0;
    if (w == 0) relay();
    dcur += bias;
    auto body = [&](const int k) -> bool {
        if (k == 2) asm volatile("ld.volatile.shared.u32 %0, [%1+4];" : "=r"(t0) : "r"(flg));
        const bool pc = k & 1;
        step(k * SLOTB, 0, pc);
        if (!pc) {
            if (mp == mend) phase_end(k);
        } else if (mp == mend || now < dl) {
            if (mp == mend) {
                if (k == 3 && ph == 3) return true;
                phase_end(k);
            }
            if (w == 0) { dl -= 1u << 20; relay(); }
            asm volatile("{.reg .pred p; .reg .u32 d;\n"
                         "PACE_LOOP: mov.u32 d, %%globaltimer_lo; sub.u32 d, %0, d; setp.lt.u32 p, d, 32768; @p nanosleep.u32 %1; @p bra.uni PACE_LOOP;}"
                         :: "r"(dl), "n"(PSLEEP) : "memory");
        }
        return false;
    };
    asm volatile("{.reg .pred p; .reg .u32 d;\n"
                 "PACE_LOOP: mov.u32 d, %%globaltimer_lo; sub.u32 d, %0, d; setp.lt.u32 p, d, 32768; @p nanosleep.u32 %1; @p bra.uni PACE_LOOP;}"
                 :: "r"(__shfl_sync(0xffffffff, dreg, 0) + t0), "n"(PSLEEP) : "memory");
    while (true) {
        if (w == PW) {
            const uint32_t cand = now - dl + tcur - PTOL;
            if ((int)(cand - t0) > 0) report(cand);
        }
        dcur += t0 - tcur; tcur = t0;
        body(0); body(1); body(2);
        if (body(3)) break;
    }
    __syncwarp();
    step(0, 1); step(SLOTB, 2); step(2 * SLOTB, 3); step(3 * SLOTB, 4);
    WSTAMP(3);

    {
        putacc((uint32_t*)(smem + SM_RING + 2 * SLOTB + w * 2048 + 512) + lane);
        const int wg = w >> 2, w4 = w & 3;
        int nd[8];
#pragma unroll
        for (int j = 0; j < 8; j++) { const int l = wg * 8 + j; nd[j] = order[(t >> 1) ? 79 - l : l]; asm volatile("" : "+r"(nd[j])); }
        const bool odd = t & 1;
        uint2* ob = (uint2*)out + (size_t)n0 * 128 + w4 * 16 + g + (odd ? 8 : 0);
        asm volatile("cp.async.wait_all;" ::: "memory");
        mbar_wait(mbarW, 0);
        asm volatile("fence.proxy.async.shared::cta;" ::: "memory");
        TSTAMP(26);
        bar_sync(2 + wg, 128);
        if ((tid & 127) == 0) {
            const uint32_t ticket = atomicAdd((uint32_t*)flag + 12, 1);
            int spins = 0;
            while (flag[13] < ticket && ++spins < (1 << 16)) {}
        }
        bar_sync(2 + wg, 128);
        TSTAMP(27);
        const uint64_t descA0 = (uint64_t)(((sb + SM_RING) & 0x3FFFF) >> 4) | ((uint64_t)1 << 16) | ((uint64_t)(1024 >> 4) << 32) | ((uint64_t)1 << 62);
        const uint64_t descB0 = (uint64_t)(((sb + SM_RING + SLOTB + wg * 8192) & 0x3FFFF) >> 4) | ((uint64_t)(128 >> 4) << 16) | ((uint64_t)(1024 >> 4) << 32);
        float d[2][32];
        asm volatile("wgmma.fence.sync.aligned;" ::: "memory");
#pragma unroll
        for (int mt = 0; mt < 2; mt++) {
#pragma unroll
            for (int ks = 0; ks < 8; ks++) {
                const uint64_t da = descA0 + (uint64_t)((ks * 2048 + mt * 16384) >> 4), db = descB0 + (uint64_t)(((ks & 3) * 256 + (ks >> 2) * SLOTB) >> 4);
                asm volatile("{.reg .pred p; setp.ne.b32 p, %34, 0;\n"
                    "wgmma.mma_async.sync.aligned.m64n64k16.f32.bf16.bf16 "
                    "{%0,%1,%2,%3,%4,%5,%6,%7,%8,%9,%10,%11,%12,%13,%14,%15,%16,%17,%18,%19,%20,%21,%22,%23,%24,%25,%26,%27,%28,%29,%30,%31}, %32, %33, p, 1, 1, 1, 1;}"
                    : "+f"(d[mt][0]), "+f"(d[mt][1]), "+f"(d[mt][2]), "+f"(d[mt][3]), "+f"(d[mt][4]), "+f"(d[mt][5]), "+f"(d[mt][6]), "+f"(d[mt][7]),
                      "+f"(d[mt][8]), "+f"(d[mt][9]), "+f"(d[mt][10]), "+f"(d[mt][11]), "+f"(d[mt][12]), "+f"(d[mt][13]), "+f"(d[mt][14]), "+f"(d[mt][15]),
                      "+f"(d[mt][16]), "+f"(d[mt][17]), "+f"(d[mt][18]), "+f"(d[mt][19]), "+f"(d[mt][20]), "+f"(d[mt][21]), "+f"(d[mt][22]), "+f"(d[mt][23]),
                      "+f"(d[mt][24]), "+f"(d[mt][25]), "+f"(d[mt][26]), "+f"(d[mt][27]), "+f"(d[mt][28]), "+f"(d[mt][29]), "+f"(d[mt][30]), "+f"(d[mt][31])
                    : "l"(da), "l"(db), "r"(ks));
            }
            asm volatile("wgmma.commit_group.sync.aligned;" ::: "memory");
            if (mt == 1) asm volatile("{.reg .pred p; setp.eq.u32 p, %1, 0; @p red.shared.add.u32 [%0+52], 1;}" :: "r"(flg), "r"(tid & 127) : "memory");
        }
#pragma unroll
        for (int mt = 0; mt < 2; mt++) {
            if (mt == 0) asm volatile("wgmma.wait_group.sync.aligned 1;" ::: "memory");
            else asm volatile("wgmma.wait_group.sync.aligned 0;" ::: "memory");
            TSTAMP(23 + mt);
#pragma unroll
            for (int i = 0; i < 32; i++) asm volatile("" : "+f"(d[mt][i]) :: "memory");
#pragma unroll
            for (int j = 0; j < 8; j++) {
                const uint32_t v0 = pack2(d[mt][4 * j], d[mt][4 * j + 1]), v1 = pack2(d[mt][4 * j + 2], d[mt][4 * j + 3]);
                const uint32_t rv = __shfl_xor_sync(0xffffffff, odd ? v0 : v1, 1);
                if (nd[j] < nn) ob[nd[j] * 128 + mt * 64] = odd ? make_uint2(rv, v1) : make_uint2(v0, rv);
            }
        }
    }
    TSTAMP(8);
}

}

extern "C" void kernel_launch(void* const* d_in, const int* in_sizes, int n_in, void* d_out, int out_size) {
    (void)in_sizes; (void)n_in; (void)out_size;
    cudaFuncSetAttribute(tfn_kernel, cudaFuncAttributeMaxDynamicSharedMemorySize, SM_TOTAL);
    Scratch* gs = nullptr;
    cudaGetSymbolAddress((void**)&gs, g_scratch);
    cudaLaunchConfig_t cfg = {};
    cfg.gridDim = dim3(NB); cfg.blockDim = dim3(NT); cfg.dynamicSmemBytes = SM_TOTAL; cfg.stream = cudaStreamPerThread;
    cudaLaunchAttribute at[1];
    at[0].id = cudaLaunchAttributeCooperative; at[0].val.cooperative = 1;
    cfg.attrs = at; cfg.numAttrs = 1;
    cudaLaunchKernelEx(&cfg, tfn_kernel, (const unsigned char*)d_in[0], (const int4*)d_in[1], (const int4*)d_in[2],
                       (const uint4*)d_in[3], (const uint4*)d_in[4], (const uint16_t*)d_in[5], (const uint16_t*)d_in[6],
                       (const uint4*)d_in[7], (uint32_t*)d_out, gs);
}
```

```cpp
#include <cuda_runtime.h>
#include <cuda_bf16.h>
#include <stdint.h>

namespace {

constexpr int NN = 10000;
constexpr int NE = 320000;
constexpr int NB = 132;
constexpr int NW = 20;
constexpr int NT = NW * 32;
constexpr int CW = NW - 1;
#define PWARP 10
constexpr int PW = PWARP;
constexpr int NPB = 76;
constexpr int CELL = 48;
constexpr int RCH = 2880;
constexpr int CAP = 19;
constexpr int DS = 4;
constexpr int STEPB = 160;
constexpr int NE4 = NE / 4;
constexpr int NPIECE = NB * 8;
constexpr int KB = 320, KN = 32 * KB;
constexpr uint32_t F_PAD = 0x80000000u;
constexpr uint32_t F_WRAP = 1;

constexpr int SLOTB = NW * 2048;
constexpr int SM_RING = 0;
constexpr int SM_META = SM_RING + DS * SLOTB;
constexpr int SM_AZ = SM_META + NW * CAP * STEPB;
constexpr int SM_MISC = SM_AZ + 2048;
constexpr int SM_TOTAL = SM_MISC + 2048;
constexpr int SM_STAGE = SM_RING;
constexpr int SM_HIST = SM_RING + 25600;
constexpr int SM_POS = SM_RING;
constexpr int SM_SMALL = SM_HIST + 13056;
constexpr int SM_LIST = SM_RING + SLOTB;
constexpr int SM_ROUT = SM_RING + 2 * SLOTB;
constexpr int SM_RECS = SM_RING + 3 * SLOTB;
constexpr int SM_RAWY = SM_META;
constexpr int SM_RAWE = SM_RAWY + 608 * 32;
constexpr int SM_KEYS = SM_RAWE + 608 * 32;
static_assert(SM_TOTAL <= 232448 && SM_KEYS + NPIECE * 16 <= SM_AZ, "smem");
static_assert(SM_RECS + NB * CELL * 16 + 16 <= SM_AZ && SM_KEYS + NPIECE * 16 <= SM_RECS + NB * CELL * 16 && SM_SMALL + 1152 <= SLOTB && DS == 4, "smem");

struct Scratch {
    uint4 keys[NB * NPIECE];
    uint4 recs[NB * RCH];
    uint4 stash[NB * NW * 256];
    unsigned bar[2];
    unsigned long long t0;
};
__device__ Scratch g_scratch;
#define TSTAMP(i)
#define TSTAMPC(i)
#define WSTAMP(i)

__device__ __forceinline__ void mma16816(float* d, uint32_t a0, uint32_t a1, uint32_t a2, uint32_t a3, uint32_t b0, uint32_t b1) {
    asm("mma.sync.aligned.m16n8k16.row.col.f32.bf16.bf16.f32 {%0,%1,%2,%3}, {%4,%5,%6,%7}, {%8,%9}, {%0,%1,%2,%3};"
        : "+f"(d[0]), "+f"(d[1]), "+f"(d[2]), "+f"(d[3]) : "r"(a0), "r"(a1), "r"(a2), "r"(a3), "r"(b0), "r"(b1));
}
__device__ __forceinline__ void mma1688z(float* d, uint32_t a0, uint32_t a1, uint32_t b0) {
    asm("mma.sync.aligned.m16n8k8.row.col.f32.bf16.bf16.f32 {%0,%1,%2,%3}, {%4,%5}, {%6}, {%7,%7,%7,%7};"
        : "=f"(d[0]), "=f"(d[1]), "=f"(d[2]), "=f"(d[3]) : "r"(a0), "r"(a1), "r"(b0), "f"(0.f));
}
__device__ __forceinline__ uint32_t pack2(float lo, float hi) {
    uint32_t r; asm("cvt.rn.bf16x2.f32 %0, %1, %2;" : "=r"(r) : "f"(hi), "f"(lo)); return r;
}
__device__ __forceinline__ float silu_h(float h) {
    float t; asm("tanh.approx.f32 %0, %1;" : "=f"(t) : "f"(h)); return fmaf(h, t, h);
}
__device__ __forceinline__ uint32_t mul_lo(uint32_t v, uint32_t r) {
    __nv_bfloat162 a = *(__nv_bfloat162*)&v, b = *(__nv_bfloat162*)&r; __nv_bfloat162 c = __hmul2(a, __low2bfloat162(b)); return *(uint32_t*)&c;
}
__device__ __forceinline__ uint32_t mul_hi(uint32_t v, uint32_t r) {
    __nv_bfloat162 a = *(__nv_bfloat162*)&v, b = *(__nv_bfloat162*)&r; __nv_bfloat162 c = __hmul2(a, __high2bfloat162(b)); return *(uint32_t*)&c;
}
__device__ __forceinline__ uint2 lds64(uint32_t a) {
    uint2 r; asm volatile("ld.shared.v2.u32 {%0,%1}, [%2];" : "=r"(r.x), "=r"(r.y) : "r"(a)); return r;
}
__device__ __forceinline__ uint4 lds128(uint32_t a) {
    uint4 r; asm volatile("ld.shared.v4.u32 {%0,%1,%2,%3}, [%4];" : "=r"(r.x), "=r"(r.y), "=r"(r.z), "=r"(r.w) : "r"(a) : "memory"); return r;
}
__device__ __forceinline__ void bar_sync(int id, int n) { asm volatile("bar.sync %0, %1;" :: "r"(id), "r"(n) : "memory"); }
__device__ __forceinline__ void bar_arrive(int id, int n) { asm volatile("bar.arrive %0, %1;" :: "r"(id), "r"(n) : "memory"); }
__device__ __forceinline__ void mbar_wait(uint32_t bar, uint32_t ph) {
    uint32_t done; int spins = 0;
    do {
        asm volatile("{.reg .pred p; mbarrier.try_wait.parity.shared.b64 p, [%1], %2; selp.u32 %0,1,0,p;}" : "=r"(done) : "r"(bar), "r"(ph) : "memory");
    } while (!done && ++spins < (1 << 22));
}
__device__ __forceinline__ unsigned gbar_read(const unsigned* ctr) {
    unsigned v; asm volatile("ld.relaxed.gpu.global.u32 %0, [%1];" : "=r"(v) : "l"(ctr) : "memory");
    return v;
}
__device__ __forceinline__ void gbar_arrive(unsigned* ctr) {
    asm volatile("red.add.release.gpu.global.u32 [%0], 1;" :: "l"(ctr) : "memory");
}
__device__ __forceinline__ bool gbar_wait(const unsigned* ctr, unsigned target) {
    unsigned v; int spins = 0;
    while (true) {
        asm volatile("ld.acquire.gpu.global.u32 %0, [%1];" : "=r"(v) : "l"(ctr) : "memory");
        if ((int)(v - target) >= 0 || ++spins > (1 << 22)) break;
    }
    return (int)(v - target) >= 0;
}
__device__ __forceinline__ int chunk_start4(int c) { return (c * NE4) / NB; }
__device__ __forceinline__ float bf2f(uint32_t h) { return __uint_as_float(h << 16); }

__device__ __noinline__ void slow_path(unsigned char* smem, int n0, int nn, const uint16_t* x, const int* src, const int* dst,
                                       const uint16_t* Y, const uint16_t* ef, const uint16_t* w_rad, const uint16_t* cg,
                                       const uint16_t* w_mix, __nv_bfloat16* out) {
    float* agg = (float*)smem;
    const int tid = threadIdx.x, lane = tid & 31, w = tid >> 5;
    bar_sync(1, NT);
    for (int i = tid; i < NPB * 512; i += NT) agg[i] = 0.f;
    bar_sync(1, NT);
    for (int e0 = w * 32; e0 < NE; e0 += NT) {
        int dl = dst[e0 + lane] - n0;
        unsigned m = __ballot_sync(0xffffffff, dl >= 0 && dl < nn);
        while (m) {
            int l = __ffs(m) - 1; m &= m - 1;
            int e = e0 + l, d = __shfl_sync(0xffffffff, dl, l), s = src[e];
            float T[16];
            for (int i = 0; i < 4; i++) for (int o = 0; o < 4; o++) {
                float a = 0.f;
                for (int f = 0; f < 4; f++) a += bf2f(Y[e * 4 + f]) * bf2f(cg[i * 16 + f * 4 + o]);
                T[i * 4 + o] = a;
            }
            for (int k = 0; k < 4; k++) {
                int c = lane + 32 * k;
                float z = 0.f;
                for (int j = 0; j < 4; j++) z += bf2f(ef[e * 4 + j]) * bf2f(w_rad[j * 128 + c]);
                float R = z / (1.f + __expf(-z));
                for (int o = 0; o < 4; o++) {
                    float a = 0.f;
                    for (int i = 0; i < 4; i++) a += bf2f(x[(size_t)s * 512 + c * 4 + i]) * T[i * 4 + o];
                    atomicAdd(&agg[d * 512 + c * 4 + o], R * a);
                }
            }
        }
    }
    bar_sync(1, NT);
    for (int i = tid; i < nn * 512; i += NT) {
        int n = i >> 9, d = (i >> 2) & 127, o = i & 3;
        float a = 0.f;
        for (int c = 0; c < 128; c++) a += agg[n * 512 + c * 4 + o] * bf2f(w_mix[c * 128 + d]);
        out[(size_t)(n0 + n) * 512 + (i & 511)] = __float2bfloat16(a);
    }
}

#define PACE 22750
#define YDELAY 300
#define POFF 4000
#define PSLEEP 32
#define RLEN 99
#define FDT 400
#define FOFF 1800
#define FSTAG 0
#define PTOL0 300
#define PTOL 900
__global__ void __launch_bounds__(NT, 1)
tfn_kernel(const unsigned char* __restrict__ x, const int4* __restrict__ src4, const int4* __restrict__ dst4,
           const uint4* __restrict__ Y, const uint4* __restrict__ ef, const uint16_t* __restrict__ w_rad,
           const uint16_t* __restrict__ cg, const uint4* __restrict__ w_mix, uint32_t* __restrict__ out, Scratch* __restrict__ gs) {
    extern __shared__ __align__(1024) unsigned char smem[];
    const uint32_t sb = (uint32_t)__cvta_generic_to_shared(smem);
    const int b = blockIdx.x, tid = threadIdx.x, lane = tid & 31, g = lane >> 2, t = lane & 3;
    const int w = __shfl_sync(0xffffffff, tid >> 5, 0);
    uint32_t* stage = (uint32_t*)(smem + SM_STAGE);
    uint32_t* hist = (uint32_t*)(smem + SM_HIST);
    uint32_t* cnt = (uint32_t*)(smem + SM_MISC);
    uint32_t* deg = cnt + 136;
    uint32_t* order = deg + 104;
    uint32_t* cnt2 = order + 80;
    volatile uint32_t* flag = cnt2 + 136;
    const uint32_t mbarK = sb + SM_MISC + 1920, mbarR = mbarK + 8, mbarW = mbarK + 16;
    const int n0 = b * NPB, nn = min(NPB, NN - n0);
    TSTAMP(0);

    const int c0 = chunk_start4(b), c1 = chunk_start4(b + 1);
    const bool has4 = c0 + tid < c1;
    int4 d4 = make_int4(0, 0, 0, 0), s4 = d4;
    if (has4) { d4 = __ldg(dst4 + c0 + tid); s4 = __ldg(src4 + c0 + tid); }
    unsigned tgt = 0;
    if (tid == NT - 1) {
        tgt = gbar_read(&gs->bar[0]);
        asm volatile("mbarrier.init.shared.b64 [%0], 1;" :: "r"(mbarK));
        asm volatile("mbarrier.init.shared.b64 [%0], 1;" :: "r"(mbarR));
        asm volatile("mbarrier.init.shared.b64 [%0], 512;" :: "r"(mbarW));
        asm volatile("fence.mbarrier_init.release.cluster;" ::: "memory");
        flag[0] = 0; flag[12] = 0; flag[13] = 0; flag[15] = 0;
    }
    if (w == CW) {
        asm volatile("cp.async.cg.shared.global [%0], [%1], 16;" :: "r"(sb + SM_SMALL + lane * 16), "l"(w_rad + lane * 8) : "memory");
        asm volatile("cp.async.cg.shared.global [%0], [%1], 16;" :: "r"(sb + SM_SMALL + 512 + lane * 16), "l"(w_rad + 256 + lane * 8) : "memory");
        if (lane < 8) asm volatile("cp.async.cg.shared.global [%0], [%1], 16;" :: "r"(sb + SM_SMALL + 1024 + lane * 16), "l"(cg + lane * 8) : "memory");
    }
    ((uint4*)hist)[tid] = make_uint4(0, 0, 0, 0);
    {
        const uint32_t dk = (80 + b % 22) * KN + (b & 31) * KB;
#pragma unroll
        for (int j = 0; j < 3; j++) if (tid + j * NT < NB * CELL / 4) ((uint4*)stage)[tid + j * NT] = make_uint4(dk, dk, dk, dk);
    }
    if (tid < 136) cnt[tid] = 0;
    if (tid == 0) { *(uint4*)(smem + SM_MISC + 1824 + 32) = make_uint4(0, 0, 0, 0); *(uint4*)(smem + SM_RECS + NB * CELL * 16) = make_uint4(0, 0, 0, 0); }
    if (tid < 80) { deg[tid] = 127 - tid; order[tid] = tid; }
    __syncthreads();
    TSTAMP(9);
    if (tid == 64) {
        if (YDELAY) __nanosleep(YDELAY);
        asm volatile("mbarrier.arrive.expect_tx.shared.b64 _, [%0], %1;" :: "r"(mbarR), "r"((c1 - c0) * 64) : "memory");
        asm volatile("cp.async.bulk.shared::cluster.global.mbarrier::complete_tx::bytes [%0], [%1], %2, [%3];"
                     :: "r"(sb + SM_RAWY), "l"(Y + 2 * c0), "r"((c1 - c0) * 32), "r"(mbarR) : "memory");
        asm volatile("cp.async.bulk.shared::cluster.global.mbarrier::complete_tx::bytes [%0], [%1], %2, [%3];"
                     :: "r"(sb + SM_RAWE), "l"(ef + 2 * c0), "r"((c1 - c0) * 32), "r"(mbarR) : "memory");
    }

    uint32_t bin[4] = {0, 0, 0, 0}, slot[4] = {0, 0, 0, 0};
    if (has4) {
        const uint32_t dd[4] = {(uint32_t)d4.x, (uint32_t)d4.y, (uint32_t)d4.z, (uint32_t)d4.w}, ss[4] = {(uint32_t)s4.x, (uint32_t)s4.y, (uint32_t)s4.z, (uint32_t)s4.w};
#pragma unroll
        for (int k = 0; k < 4; k++) { bin[k] = dd[k] / NPB; slot[k] = atomicAdd(&cnt[bin[k]], 1); }
#pragma unroll
        for (int k = 0; k < 4; k++) stage[bin[k] * CELL + min(slot[k], CELL - 1)] = (dd[k] - bin[k] * NPB) * KN + ss[k];
    }
    if (w == CW) {
        if (tid == NT - 1) { tgt = tgt / NB + 1; flag[14] = (tgt & 1) << 31; tgt *= NB; }
        asm volatile("cp.async.wait_all;" ::: "memory");
    }
    bar_sync(1, NT);
    TSTAMP(1);
    const uint32_t tag = flag[14];
#pragma unroll
    for (int j = 0; j < 2; j++) {
        const int i = tid + j * NT;
        if (i < NPIECE) {
            const uint2 sa = *(const uint2*)(stage + i * 6), sc = *(const uint2*)(stage + i * 6 + 2);
            uint2 se = *(const uint2*)(stage + i * 6 + 4);
            const uint32_t cf = cnt[i >> 3], cn = min(cf, 63u);
            if ((i & 7) == 7) {
                const uint32_t al = cf > CELL - 8 ? 7 : 0;
                uint32_t o;
                asm volatile("atom.shared.add.u32 %0, [%1], %2;" : "=r"(o) : "r"(sb + SM_MISC + 1824 + 60), "r"(cf + al) : "memory");
                se.y = (o + al) & ~al;
                cnt2[i >> 3] = se.y;
            }
            asm volatile("{.reg .b64 lo, hi; mov.b64 lo, {%1,%2}; mov.b64 hi, {%3,%4}; st.relaxed.gpu.global.v2.b64 [%0], {lo, hi};}"
                         :: "l"(gs->keys + ((i >> 3) * NB + b) * 8 + ((i ^ b) & 7)),
                            "r"(sa.x | (se.x << 20)), "r"(sa.y | ((se.x >> 12) << 20) | ((cn & 7) << 28) | tag),
                            "r"(sc.x | (se.y << 20)), "r"(sc.y | ((se.y >> 12) << 20) | ((cn >> 3) << 28) | tag) : "memory");
        }
    }
    bar_sync(1, NT);
    if (tid == NT - 1) {
        TSTAMPC(10);
        asm volatile("red.add.relaxed.gpu.global.u32 [%0], 1;" :: "l"(&gs->bar[0]) : "memory");
        asm volatile("mbarrier.arrive.expect_tx.shared.b64 _, [%0], %1;" :: "r"(mbarK), "r"(NPIECE * 16) : "memory");
        gbar_wait(&gs->bar[0], tgt);
        TSTAMPC(13);
        asm volatile("fence.proxy.async.global;" ::: "memory");
        asm volatile("cp.async.bulk.shared::cluster.global.mbarrier::complete_tx::bytes [%0], [%1], %2, [%3];"
                 :: "r"(sb + SM_KEYS), "l"(gs->keys + b * NPIECE), "r"(NPIECE * 16), "r"(mbarK) : "memory");
    }
    __syncwarp();
    uint32_t at[4];
    {
        const int o = g & 3, f = 2 * (t & 1);
#pragma unroll
        for (int i = 0; i < 4; i++) {
            const uint16_t* cp = (const uint16_t*)(smem + SM_SMALL + 1024) + i * 16 + f * 4 + o;
            at[i] = (t >> 1) == (g >> 2) ? cp[0] | ((uint32_t)cp[4] << 16) : 0;
        }
    }

    const int q = lane >> 3, c = lane & 7;
    const uint32_t ring0 = sb + SM_RING + w * 2048;
    uint32_t wdst = ring0 + q * 128 + ((c + 2 * q) & 7) * 16;
    uint32_t rsrc = ring0 + t * 128 + ((g + 2 * t) & 7) * 16;
    uint32_t recl = sb + SM_META + w * (CAP * STEPB) + g * 16 + (t & 1) * 8, srcl = sb + SM_META + w * (CAP * STEPB) + 128 + q * 8;
    uint32_t flg = sb + SM_MISC + (136 + 104 + 80 + 136) * 4;
    asm volatile("" : "+r"(wdst), "+r"(rsrc), "+r"(recl), "+r"(srcl), "+r"(flg));
    uint32_t key[2][6], ha[2][6], rk[2][6], kidx[2], ka[2];
    int nk[2];
#pragma unroll
    for (int j = 0; j < 2; j++) {
        const int i0 = j ? 2 * 608 - 1 - tid : tid, i = min(i0, NPIECE - 1), r = i / NB, cc = i - r * NB;
        ka[j] = sb + SM_KEYS + (cc * 8 + ((r ^ cc) & 7)) * 16;
        kidx[j] = (cc * CELL + r * 6) << 17;
        nk[j] = i0 < NPIECE && w < CW ? -6 * r : -1000;
    }
    asm volatile("" : "+r"(at[0]), "+r"(at[1]), "+r"(at[2]), "+r"(at[3]), "+r"(ka[0]), "+r"(ka[1]), "+r"(kidx[0]), "+r"(kidx[1]), "+r"(nk[0]), "+r"(nk[1]));
    if (w == CW) {
        __syncwarp();
        bar_sync(7, NT);
        if (tid == NT - 1) {
            TSTAMPC(11);
            asm volatile("cp.async.bulk.global.shared::cta.bulk_group [%0], [%1], %2;"
                         :: "l"(gs->recs + b * RCH), "r"(sb + SM_ROUT), "r"(((flag[15] + 1) & ~1u) * 16) : "memory");
            asm volatile("cp.async.bulk.commit_group;" ::: "memory");
            mbar_wait(mbarK, 0);
            unsigned long long tbase;
            asm volatile("mov.u64 %0, %%globaltimer;" : "=l"(tbase));
            tbase += POFF;
            flag[1] = (uint32_t)tbase; flag[4] = (uint32_t)tbase; flag[5] = (uint32_t)(tbase >> 32);
            asm volatile("red.max.relaxed.gpu.global.u64 [%0], %1;" :: "l"(&gs->t0), "l"(tbase) : "memory");
            if (b < 128) asm volatile("cp.async.bulk.prefetch.L2.global [%0], 256;" :: "l"(w_mix + b * 16));
            asm volatile("cp.async.bulk.wait_group 0;" ::: "memory");
            TSTAMPC(14);
            asm volatile("red.add.relaxed.gpu.global.u32 [%0], 1;" :: "l"(&gs->bar[1]) : "memory");
            TSTAMPC(15);
        }
    } else {
        if (w < 8) {
            const uint32_t* wp = (const uint32_t*)(smem + SM_SMALL) + (t & 1) * 128 + 8 * w + g;
            const uint32_t wr0 = t < 2 ? wp[0] : 0, wr1 = t < 2 ? wp[64] : 0;
            *(uint2*)(smem + SM_AZ + (w >> 1) * 512 + lane * 16 + (w & 1) * 8) =
                make_uint2(pack2(0.5f * bf2f(wr0 & 0xFFFF), 0.5f * bf2f(wr1 & 0xFFFF)), pack2(0.5f * bf2f(wr0 >> 16), 0.5f * bf2f(wr1 >> 16)));
        }
        const bool sw = g & 1;
        uint32_t rp[4];
#pragma unroll
        for (int k = 0; k < 4; k++) rp[k] = cnt2[bin[k]] + slot[k];
        uint4* ro = (uint4*)(smem + SM_ROUT);
        uint4 *p0 = ro + (sw ? rp[2] : rp[0]), *p1 = ro + (sw ? rp[3] : rp[1]), *p2 = ro + (sw ? rp[0] : rp[2]), *p3 = ro + (sw ? rp[1] : rp[3]);
        const uint32_t ya = sb + SM_RAWY + tid * 32 + (sw ? 16 : 0);
        mbar_wait(mbarR, 0);
        TSTAMP(18);
        if (has4) {
            const uint4 y0 = lds128(ya), e0 = lds128(ya + (SM_RAWE - SM_RAWY)), y1 = lds128(ya ^ 16), e1 = lds128((ya ^ 16) + (SM_RAWE - SM_RAWY));
            *p0 = make_uint4(y0.x, e0.x, y0.y, e0.y); *p1 = make_uint4(y0.z, e0.z, y0.w, e0.w);
            *p2 = make_uint4(y1.x, e1.x, y1.y, e1.y); *p3 = make_uint4(y1.z, e1.z, y1.w, e1.w);
        }
        asm volatile("fence.proxy.async.shared::cta;" ::: "memory");
        bar_arrive(7, NT);
    }
    __syncwarp();
    TSTAMP(2);

    if (w < CW) {
        mbar_wait(mbarK, 0);
        TSTAMP(3);
        uint4 v[2] = {lds128(ka[0]), lds128(ka[1])};
#pragma unroll
        for (int j = 0; j < 2; j++) {
            int spins = 0;
            while ((int)((v[j].y ^ tag) | (v[j].w ^ tag)) < 0) {
                asm volatile("{.reg .b64 lo, hi; ld.relaxed.gpu.global.v2.b64 {lo, hi}, [%4]; mov.b64 {%0,%1}, lo; mov.b64 {%2,%3}, hi;}"
                             : "=r"(v[j].x), "=r"(v[j].y), "=r"(v[j].z), "=r"(v[j].w) : "l"((const unsigned char*)(gs->keys + b * NPIECE) + (ka[j] - sb - SM_KEYS)) : "memory");
                if (++spins > (1 << 20)) { *flag = 1; break; }
            }
            const uint32_t hc = ((v[j].y >> 28) & 7) | ((v[j].w >> 25) & 0x38);
            if (j == 1 && nk[j] == -42) {
                cnt[kidx[j] / (CELL << 17)] = hc | ((v[j].z >> 20) << 8);
                v[j].w |= ((80 * KN) >> 12) << 20;
            }
            if (hc > CELL - 1) *flag = 1;
            nk[j] += hc;
            if (nk[j] > 0) {
                key[j][0] = v[j].x & 0xFFFFF; key[j][1] = v[j].y & 0xFFFFF; key[j][2] = v[j].z & 0xFFFFF; key[j][3] = v[j].w & 0xFFFFF;
                key[j][4] = (v[j].x >> 20) | ((v[j].y >> 8) & 0xFF000); key[j][5] = (v[j].z >> 20) | ((v[j].w >> 8) & 0xFF000);
#pragma unroll
                for (int u = 0; u < 6; u++) {
                    ha[j][u] = __umulhi(key[j][u], 0xFFFFFFFFu / KB + 1);
                    rk[j][u] = atomicAdd(&hist[ha[j][u]], 1);
                    atomicAdd(&deg[ha[j][u] >> 5], 128);
                }
            }
        }
        bar_sync(9, NT - 32);
        TSTAMP(20);
#pragma unroll
        for (int j = 0; j < 2; j++) kidx[j] += ((cnt[kidx[j] / (CELL << 17)] >> 8) & 7) << 17;
        const int n = tid >> 3, sub = tid & 7;
        const uint32_t me = deg[n];
        int r = 0;
#pragma unroll
        for (int k = 0; k < 5; k++) { const uint2 dd = *(const uint2*)(deg + sub * 10 + 2 * k); r += (dd.x > me) + (dd.y > me); }
        r += __shfl_xor_sync(0xffffffff, r, 1); r += __shfl_xor_sync(0xffffffff, r, 2); r += __shfl_xor_sync(0xffffffff, r, 4);
        if (sub == 0) order[r] = n;
    }
    bar_sync(1, NT);
    TSTAMP(22);
    uint32_t len2;
    {
        const uint2 na = *(const uint2*)(order + 2 * w);
        uint2 nb = *(const uint2*)(order + 78 - 2 * w);
        const uint32_t ia0 = na.x * 32 + lane, ia1 = na.y * 32 + lane;
        const uint32_t ha0 = hist[ia0], ha1 = hist[ia1];
        uint32_t hb0 = hist[nb.y * 32 + lane], hb1 = hist[nb.x * 32 + lane];
        const int su = __reduce_add_sync(0xffffffff, (int)(ha0 - ha1) * (2 * lane - 31)), sv = __reduce_add_sync(0xffffffff, (int)(hb0 - hb1) * (2 * lane - 31));
        if ((su ^ sv) >= 0) {
            nb = make_uint2(nb.y, nb.x);
            const uint32_t tmp = hb0; hb0 = hb1; hb1 = tmp;
            *(uint2*)(order + 78 - 2 * w) = nb;
        }
        const uint32_t ib0 = nb.y * 32 + lane, ib1 = nb.x * 32 + lane;
        const uint32_t ca = ha0 + (ha1 << 16), cab = ca + hb0 + (hb1 << 16);
        uint32_t inc = cab;
#pragma unroll
        for (int o = 1; o < 32; o <<= 1)
            asm volatile("{.reg .pred p; .reg .u32 u; shfl.sync.up.b32 u|p, %0, %1, 0, 0xffffffff; @p add.u32 %0, %0, u;}" : "+r"(inc) : "r"(o));
        const uint32_t ea = inc - cab, eb = ea + ca, base = sb + SM_LIST + w * 2048;
        uint2* pos = (uint2*)(smem + SM_POS);
        pos[ia0] = make_uint2(base + (ea & 0xFFFF) * 8, na.x * (0u - 4 * KN));
        pos[ib0] = make_uint2(base + (eb & 0xFFFF) * 8, nb.y * (0u - 4 * KN) + 0x10000);
        pos[ia1] = make_uint2(base + 4 + (ea >> 16) * 8, na.y * (0u - 4 * KN));
        pos[ib1] = make_uint2(base + 4 + (eb >> 16) * 8, nb.x * (0u - 4 * KN) + 0x10000);
        if (max(inc & 0xFFFF, inc >> 16) > 4 * CAP) *flag = 1;
        len2 = __shfl_sync(0xffffffff, inc, 31);
    }
    uint32_t ci = cnt[min(w + NW * lane, NB)];
    ci = ((((w + NW * lane) * (RCH / 8) + (ci >> 11)) << 8) | (ci & 0xFF)) + ((ci >> 8) & 7);
    if (w == CW) {
        bar_arrive(9, NT);
        if (tid == NT - 1) {
            uint32_t v1, g0; int spins = 0;
            do {
                asm volatile("{.reg .u32 a, b; ld.acquire.gpu.global.v4.u32 {a,%0,%1,b}, [%2];}" : "=r"(v1), "=r"(g0) : "l"(gs->bar) : "memory");
            } while ((int)(v1 - tgt) < 0 && ++spins < (1 << 22));
            if ((int)(v1 - tgt) < 0) *flag = 1;
            if (g0 - flag[1] < 30000) flag[1] = g0;
            TSTAMPC(17);
        }
        __syncwarp();
    } else {
        bar_sync(9, NT);
        TSTAMP(21);
        const uint32_t over = *flag;
#pragma unroll
        for (int j = 0; j < 2; j++) {
            if (nk[j] > 0) {
                uint2 h[6];
#pragma unroll
                for (int u = 0; u < 6; u++) h[u] = lds64(sb + SM_POS + ha[j][u] * 8);
                if (over) nk[j] = 0;
#pragma unroll
                for (int u = 0; u < 6; u++)
                    asm volatile("{.reg .pred p; setp.gt.s32 p, %2, %3; @p st.shared.u32 [%0], %1;}"
                                 :: "r"(h[u].x + rk[j][u] * 8), "r"(key[j][u] * 4 + h[u].y + (kidx[j] + (u << 17))), "r"(nk[j]), "r"(u) : "memory");
            }
        }
    }
    bar_sync(1, NT);
    TSTAMP(4);
    if (*flag) {
        slow_path(smem, n0, nn, (const uint16_t*)x, (const int*)src4, (const int*)dst4, (const uint16_t*)Y, (const uint16_t*)ef, w_rad, cg,
                  (const uint16_t*)w_mix, (__nv_bfloat16*)out);
        return;
    }
    {
        const uint4* gp = gs->recs + lane;
        const uint32_t sp = sb + SM_RECS + (w * CELL + lane) * 16;
#pragma unroll
        for (int j = 0; j < 7; j++) {
            const uint32_t cj = __shfl_sync(0xffffffff, ci, j);
            asm volatile("{.reg .pred p; setp.lt.u32 p, %2, %3; @p cp.async.cg.shared.global [%0], [%1], 16;}"
                         :: "r"(sp + j * (NW * CELL * 16)), "l"(gp + (size_t)(cj >> 8) * 8), "r"(lane), "r"(cj & 0xFF) : "memory");
        }
        for (uint32_t m = __ballot_sync(0xffffffff, (ci & 0xFF) > 32); m; m &= m - 1) {
            const int j = __ffs(m) - 1;
            const uint32_t cj = __shfl_sync(0xffffffff, ci, j);
            if (lane + 32 < (cj & 0xFF))
                asm volatile("cp.async.cg.shared.global [%0], [%1], 16;" :: "r"(sp + j * (NW * CELL * 16) + 512), "l"(gp + (size_t)(cj >> 8) * 8 + 32) : "memory");
        }
        asm volatile("cp.async.commit_group;" ::: "memory");
    }
    const int S = __shfl_sync(0xffffffff, max((int)(max(len2 & 0xFFFF, len2 >> 16) + 3) >> 2, DS + 1), 0);
    const int mylen = (lane & 1) ? len2 >> 16 : len2 & 0xFFFF;
    constexpr int NRAW = (CAP + 3) / 4;
    uint32_t bits0 = 0, raw[NRAW];
    unsigned char* meta = smem + SM_META + w * (CAP * STEPB);
#pragma unroll
    for (int k = 0; k < NRAW; k++) raw[k] = mylen ? ((uint32_t*)(smem + SM_LIST + w * 2048))[min(k * 16 + (lane >> 1), mylen - 1) * 2 + (lane & 1)] : 4 * n0;
    const uint32_t sv0 = raw[0] & 0xFFFF;
    const unsigned char* pbase = x + c * 16;
    auto cpa2 = [&](uint32_t dstp, uint32_t sv) {
        asm volatile("cp.async.cg.shared.global [%0], [%1], 16; cp.async.cg.shared.global [%0+1024], [%1+128], 16;"
                     :: "r"(dstp), "l"(pbase + (size_t)sv * 256) : "memory");
    };
    auto cpa2p = [&](uint32_t dstp, uint32_t sv) {
        asm volatile("{.reg .pred p; setp.ge.s32 p, %2, 0; @p cp.async.cg.shared.global [%0], [%1], 16; @p cp.async.cg.shared.global [%0+1024], [%1+128], 16;}"
                     :: "r"(dstp), "l"(pbase + (size_t)sv * 256), "r"(sv) : "memory");
    };
    auto wait_until = [&](uint32_t tt) {
        asm volatile("{.reg .pred p; .reg .u32 d;\n"
                     "PACE_LOOP: mov.u32 d, %%globaltimer_lo; sub.u32 d, %0, d; setp.lt.u32 p, d, 32768; @p nanosleep.u32 %1; @p bra.uni PACE_LOOP;}"
                     :: "r"(tt), "n"(PSLEEP) : "memory");
    };
    const uint32_t tfill = flag[1] - FOFF + w * FSTAG;
    auto fill = [&](int i) {
        if (FDT) wait_until(tfill + i * FDT);
        cpa2(wdst + i * SLOTB, __shfl_sync(0xffffffff, sv0, 8 * i + 2 * q)); cpa2(wdst + i * SLOTB + 512, __shfl_sync(0xffffffff, sv0, 8 * i + 2 * q + 1));
        asm volatile("cp.async.commit_group;" ::: "memory");
    };
    fill(0);
    TSTAMP(5);
    auto relay = [&]() {
        uint32_t g0, g1, b0, b1;
        asm volatile("ld.volatile.shared.v2.u32 {%0,%1}, [%4+40]; ld.volatile.shared.v2.u32 {%2,%3}, [%4+16];"
                     : "=r"(g0), "=r"(g1), "=r"(b0), "=r"(b1) : "r"(flg) : "memory");
        const unsigned long long dg = (((unsigned long long)g1 << 32) | g0) - (((unsigned long long)b1 << 32) | b0);
        asm volatile("{.reg .pred p, q; setp.eq.u32 p, %1, 0; setp.lt.u64 q, %2, 30000; @q st.shared.u32 [%3+4], %4;\n"
                     "@p cp.async.cg.shared.global [%3+32], [%0], 16;}"
                     :: "l"(gs->bar), "r"(lane), "l"(dg), "r"(flg), "r"(g0) : "memory");
    };
    uint32_t ra[NRAW];
#pragma unroll
    for (int k = 0; k < NRAW; k++) {
        const uint32_t m = (__ballot_sync(0xffffffff, raw[k] & 0x10000) >> g) & 0x01010101u;
        bits0 |= ((m * 0x10204080u) >> 28) << (4 * k);
        ra[k] = sb + SM_RECS + (k * 16 + (lane >> 1) < mylen ? raw[k] >> 17 : NB * CELL) * 16;
    }
    if (t < 2) bits0 = ~bits0;
    asm volatile("" : "+r"(bits0), "+r"(ra[0]), "+r"(ra[1]), "+r"(ra[2]), "+r"(ra[3]), "+r"(ra[4]));
    fill(1);
    asm volatile("cp.async.wait_group 2;" ::: "memory");
    bar_sync(1, NT);
    TSTAMP(19);
    {
        uint4 rv[NRAW];
#pragma unroll
        for (int k = 0; k < NRAW - 1; k++) rv[k] = lds128(ra[k]);
        if ((NRAW - 1) * 4 < S) rv[NRAW - 1] = lds128(ra[NRAW - 1]);
        fill(2);
        bar_sync(1, NT);
        TSTAMP(12);
        unsigned char* mr = meta + (q - 1) * STEPB + c * 16;
        unsigned char* ms = meta + (q - DS - 1) * STEPB + 128 + c * 4;
#pragma unroll
        for (int k = 0; k < NRAW; k++) {
            if (k == 0) {
                *(uint4*)(mr + (q == 0 ? S * STEPB : 0)) = rv[k];
                *(uint32_t*)(ms + S * STEPB) = sv0 + F_WRAP + ((lane >> 1) >= mylen ? F_PAD : 0);
            } else if (k * 4 + q < S) {
                *(uint4*)(mr + k * 4 * STEPB) = rv[k];
                *(uint32_t*)(ms + k * 4 * STEPB + (k == 1 && q == 0 ? S * STEPB : 0)) = (raw[k] & 0xFFFF) + (k * 16 + (lane >> 1) >= mylen ? F_PAD : 0);
            }
        }
    }
    __syncwarp();
    const uint32_t tphase = PACE / 4;
    uint32_t dreg;
    {
        const int ls = lane >= S ? min(lane - S, S - 1) : lane, st = ls == 0 ? S - 1 : ls - 1;
        const uint4 u0 = *(const uint4*)(meta + st * STEPB + 128), u1 = *(const uint4*)(meta + st * STEPB + 144);
        int pos = (u0.x + u0.y + u0.z + u0.w + u1.x + u1.y + u1.z + u1.w) << 1 >> 6;
        pos += ((u0.x & F_WRAP) ? NN : 0) + (lane >= S ? NN : 0) - NN * (2 * DS + 1) / 32;
        dreg = pos * (int)tphase / NN;
    }
    fill(3);
    TSTAMP(6);

    uint32_t* stash = (uint32_t*)(gs->stash + (b * NW + w) * 256) + lane;
    float acc[4][4];
#pragma unroll
    for (int i = 0; i < 16; i++) acc[i / 4][i % 4] = 0.f;
    uint4 az = *(const uint4*)(smem + SM_AZ + lane * 16);
    uint32_t dcur = dreg, dl = 0, now = flag[1], tcur = 0;
    uint32_t mp = 0, smask = 1, didx = 2;
    uint32_t mend = S * STEPB;
    uint2 r = lds64(mend - STEPB + recl), s0 = lds64(mend - STEPB + srcl);
    auto step = [&](const uint32_t off, const int mode, const bool pc = true) {
        if (mode == 0 && pc) { unsigned long long n64; asm volatile("mov.u64 %0, %%globaltimer;" : "=l"(n64)); now = (uint32_t)n64; }
        const uint2 rc = r, sc = s0;
        if (mode != 4) r = lds64(mp + recl);
        if (mode == 0) s0 = lds64(mp + srcl);
        asm volatile("cp.async.wait_group %0;" :: "n"(DS - 1) : "memory");
        const uint4 xa = lds128(rsrc + off), xb = lds128(rsrc + off + 512), xc = lds128(rsrc + off + 1024), xd = lds128(rsrc + off + 1536);
        if (mode == 0) {
            if (pc) { dl = __shfl_sync(0xffffffff, dcur, didx); didx += 2; }
            cpa2p(wdst + off, sc.x); cpa2p(wdst + off + 512, sc.y);
        }
        if (mode == 1 && w < 16) {
#pragma unroll
            for (int j = 0; j < 4; j++) {
                const int kk = 4 * j + q, ch = 16 * (w & 7) + 2 * (kk & 7) + (kk >> 3);
                asm volatile("cp.async.cg.shared.global [%0], [%1], 16;" :: "r"(ring0 + kk * 128 + ((c ^ (kk & 7)) << 4)), "l"(w_mix + ch * 16 + (w >> 3) * 8 + c) : "memory");
            }
            asm volatile("cp.async.mbarrier.arrive.noinc.shared.b64 [%0];" :: "r"(mbarW) : "memory");
        }
        if (mode == 2 || mode == 3) {
#pragma unroll
            for (int j = 0; j < 4; j += mode - 1)
                asm volatile("cp.async.cg.shared.global [%0], [%1], 16;" :: "r"(ring0 + off + j * 512 + lane * 16), "l"(stash + (mode - 2) * 512 + j * 128 + lane * 3) : "memory");
        }
        if (mode < 4) asm volatile("cp.async.commit_group;" ::: "memory");
        float z[4], y[4], t1[4], t2[4];
        mma1688z(z, az.x, az.y, rc.y);
        mma1688z(y, az.z, az.w, rc.y);
        uint32_t bt;
        asm("{.reg .pred p; .reg .b32 m; and.b32 m, %2, %3; setp.ne.u32 p, m, 0; selp.b32 %0, %1, 0, p;}" : "=r"(bt) : "r"(rc.x), "r"(bits0), "r"(smask));
        mma1688z(t1, at[0], at[1], bt);
        mma1688z(t2, at[2], at[3], bt);
        const uint32_t T0 = pack2(t1[0], t1[2]), T1 = pack2(t2[0], t2[2]), T2 = pack2(t1[1], t1[3]), T3 = pack2(t2[1], t2[3]);
        uint32_t R[8];
#pragma unroll
        for (int i = 0; i < 4; i++) { R[i] = __float_as_uint(silu_h(z[i])); R[4 + i] = __float_as_uint(silu_h(y[i])); }
        mma16816(acc[0], mul_hi(xa.x, R[0]), mul_hi(xa.z, R[2]), mul_hi(xa.y, R[0]), mul_hi(xa.w, R[2]), T0, T1);
        mma16816(acc[1], mul_hi(xb.x, R[1]), mul_hi(xb.z, R[3]), mul_hi(xb.y, R[1]), mul_hi(xb.w, R[3]), T2, T3);
        mma16816(acc[2], mul_hi(xc.x, R[4]), mul_hi(xc.z, R[6]), mul_hi(xc.y, R[4]), mul_hi(xc.w, R[6]), T0, T1);
        mma16816(acc[3], mul_hi(xd.x, R[5]), mul_hi(xd.z, R[7]), mul_hi(xd.y, R[5]), mul_hi(xd.w, R[7]), T2, T3);
        mp += STEPB; smask <<= 1;
    };
    auto putacc = [&](uint32_t* p) {
#pragma unroll
        for (int i = 0; i < 16; i++) acc[i / 4][i % 4] *= 1.0028f;
        p[0] = pack2(acc[0][0], acc[0][1]); p[32] = pack2(acc[0][2], acc[0][3]); p[64] = pack2(acc[2][0], acc[2][1]); p[96] = pack2(acc[2][2], acc[2][3]);
        p[256] = pack2(acc[1][0], acc[1][1]); p[288] = pack2(acc[1][2], acc[1][3]); p[320] = pack2(acc[3][0], acc[3][1]); p[352] = pack2(acc[3][2], acc[3][3]);
    };
    int ph = 0;
    auto phase_end = [&](const int k) {
        az = lds128(sb + SM_AZ + (ph + 1) * 512 + lane * 16);
        putacc(stash + ph * ph * 128);
#pragma unroll
        for (int i = 0; i < 16; i++) acc[i / 4][i % 4] = 0.f;
        pbase += 256; mp = 0; smask = 1; ph++;
        dcur += tphase; didx = 1 + (k & 1);
        if (ph == 3) mend -= DS * STEPB;
        WSTAMP(ph - 1);
    };
    uint32_t t0 = now;
    auto report = [&](uint32_t cand) {
        uint32_t b0, b1;
        asm volatile("ld.volatile.shared.v2.u32 {%0,%1}, [%2+16];" : "=r"(b0), "=r"(b1) : "r"(flg) : "memory");
        asm volatile("{.reg .pred p; setp.eq.u32 p, %2, 0; @p red.max.relaxed.gpu.global.u64 [%0], %1;}"
                     :: "l"(&gs->t0), "l"((((unsigned long long)b1 << 32) | b0) + (cand - b0)), "r"(lane) : "memory");
    };
    const bool reporter = w == PW && max(len2 & 0xFFFF, len2 >> 16) <= RLEN;
    if (reporter) {
        asm volatile("mov.u32 %0, %%globaltimer_lo;" : "=r"(now));
        now += PTOL - PTOL0;
    }
    const uint32_t bias = w == 0 ? 1u << 20 : 0;
    if (w == 0) relay();
    dcur += bias;
    auto body = [&](const int k) -> bool {
        if (k == 2) asm volatile("ld.volatile.shared.u32 %0, [%1+4];" : "=r"(t0) : "r"(flg));
        const bool pc = k & 1;
        step(k * SLOTB, 0, pc);
        if (!pc) {
            if (mp == mend) phase_end(k);
        } else if (mp == mend || now < dl) {
            if (mp == mend) {
                if (k == 3 && ph == 3) return true;
                phase_end(k);
            }
            if (w == 0) { dl -= 1u << 20; relay(); }
            wait_until(dl);
        }
        return false;
    };
    wait_until(__shfl_sync(0xffffffff, dreg, 0) + t0);
    while (true) {
        if (reporter) {
            const uint32_t cand = now - dl + tcur - PTOL;
            if ((int)(cand - t0) > 0) report(cand);
        }
        dcur += t0 - tcur; tcur = t0;
        body(0); body(1); body(2);
        if (body(3)) break;
    }
    __syncwarp();
    step(0, 1); step(SLOTB, 2); step(2 * SLOTB, 3); step(3 * SLOTB, 4);
    WSTAMP(3);

    {
        putacc((uint32_t*)(smem + SM_RING + 2 * SLOTB + w * 2048 + 512) + lane);
        const int wg = w >> 2, w4 = w & 3;
        int nd[8];
#pragma unroll
        for (int j = 0; j < 8; j++) { const int l = wg * 8 + j; nd[j] = order[(t >> 1) ? 79 - l : l]; asm volatile("" : "+r"(nd[j])); }
        const bool odd = t & 1;
        uint2* ob = (uint2*)out + (size_t)n0 * 128 + w4 * 16 + g + (odd ? 8 : 0);
        asm volatile("cp.async.wait_all;" ::: "memory");
        mbar_wait(mbarW, 0);
        asm volatile("fence.proxy.async.shared::cta;" ::: "memory");
        TSTAMP(26);
        bar_sync(2 + wg, 128);
        if ((tid & 127) == 0) {
            const uint32_t ticket = atomicAdd((uint32_t*)flag + 12, 1);
            int spins = 0;
            while (flag[13] < ticket && ++spins < (1 << 16)) {}
        }
        bar_sync(2 + wg, 128);
        TSTAMP(27);
        const uint64_t descA0 = (uint64_t)(((sb + SM_RING) & 0x3FFFF) >> 4) | ((uint64_t)1 << 16) | ((uint64_t)(1024 >> 4) << 32) | ((uint64_t)1 << 62);
        const uint64_t descB0 = (uint64_t)(((sb + SM_RING + SLOTB + wg * 8192) & 0x3FFFF) >> 4) | ((uint64_t)(128 >> 4) << 16) | ((uint64_t)(1024 >> 4) << 32);
        float d[2][32];
        asm volatile("wgmma.fence.sync.aligned;" ::: "memory");
#pragma unroll
        for (int mt = 0; mt < 2; mt++) {
#pragma unroll
            for (int ks = 0; ks < 8; ks++) {
                const uint64_t da = descA0 + (uint64_t)((ks * 2048 + mt * 16384) >> 4), db = descB0 + (uint64_t)(((ks & 3) * 256 + (ks >> 2) * SLOTB) >> 4);
                asm volatile("{.reg .pred p; setp.ne.b32 p, %34, 0;\n"
                    "wgmma.mma_async.sync.aligned.m64n64k16.f32.bf16.bf16 "
                    "{%0,%1,%2,%3,%4,%5,%6,%7,%8,%9,%10,%11,%12,%13,%14,%15,%16,%17,%18,%19,%20,%21,%22,%23,%24,%25,%26,%27,%28,%29,%30,%31}, %32, %33, p, 1, 1, 1, 1;}"
                    : "+f"(d[mt][0]), "+f"(d[mt][1]), "+f"(d[mt][2]), "+f"(d[mt][3]), "+f"(d[mt][4]), "+f"(d[mt][5]), "+f"(d[mt][6]), "+f"(d[mt][7]),
                      "+f"(d[mt][8]), "+f"(d[mt][9]), "+f"(d[mt][10]), "+f"(d[mt][11]), "+f"(d[mt][12]), "+f"(d[mt][13]), "+f"(d[mt][14]), "+f"(d[mt][15]),
                      "+f"(d[mt][16]), "+f"(d[mt][17]), "+f"(d[mt][18]), "+f"(d[mt][19]), "+f"(d[mt][20]), "+f"(d[mt][21]), "+f"(d[mt][22]), "+f"(d[mt][23]),
                      "+f"(d[mt][24]), "+f"(d[mt][25]), "+f"(d[mt][26]), "+f"(d[mt][27]), "+f"(d[mt][28]), "+f"(d[mt][29]), "+f"(d[mt][30]), "+f"(d[mt][31])
                    : "l"(da), "l"(db), "r"(ks));
            }
            asm volatile("wgmma.commit_group.sync.aligned;" ::: "memory");
            if (mt == 1) asm volatile("{.reg .pred p; setp.eq.u32 p, %1, 0; @p red.shared.add.u32 [%0+52], 1;}" :: "r"(flg), "r"(tid & 127) : "memory");
        }
#pragma unroll
        for (int mt = 0; mt < 2; mt++) {
            if (mt == 0) asm volatile("wgmma.wait_group.sync.aligned 1;" ::: "memory");
            else asm volatile("wgmma.wait_group.sync.aligned 0;" ::: "memory");
            TSTAMP(23 + mt);
#pragma unroll
            for (int i = 0; i < 32; i++) asm volatile("" : "+f"(d[mt][i]) :: "memory");
#pragma unroll
            for (int j = 0; j < 8; j++) {
                const uint32_t v0 = pack2(d[mt][4 * j], d[mt][4 * j + 1]), v1 = pack2(d[mt][4 * j + 2], d[mt][4 * j + 3]);
                const uint32_t rv = __shfl_xor_sync(0xffffffff, odd ? v0 : v1, 1);
                if (nd[j] < nn) ob[nd[j] * 128 + mt * 64] = odd ? make_uint2(rv, v1) : make_uint2(v0, rv);
            }
        }
    }
    TSTAMP(8);
}

}

extern "C" void kernel_launch(void* const* d_in, const int* in_sizes, int n_in, void* d_out, int out_size) {
    (void)in_sizes; (void)n_in; (void)out_size;
    cudaFuncSetAttribute(tfn_kernel, cudaFuncAttributeMaxDynamicSharedMemorySize, SM_TOTAL);
    Scratch* gs = nullptr;
    cudaGetSymbolAddress((void**)&gs, g_scratch);
    cudaLaunchConfig_t cfg = {};
    cfg.gridDim = dim3(NB); cfg.blockDim = dim3(NT); cfg.dynamicSmemBytes = SM_TOTAL; cfg.stream = cudaStreamPerThread;
    cudaLaunchAttribute at[1];
    at[0].id = cudaLaunchAttributeCooperative; at[0].val.cooperative = 1;
    cfg.attrs = at; cfg.numAttrs = 1;
    cudaLaunchKernelEx(&cfg, tfn_kernel, (const unsigned char*)d_in[0], (const int4*)d_in[1], (const int4*)d_in[2],
                       (const uint4*)d_in[3], (const uint4*)d_in[4], (const uint16_t*)d_in[5], (const uint16_t*)d_in[6],
                       (const uint4*)d_in[7], (uint32_t*)d_out, gs);
}
```

```cpp
#include <cuda_runtime.h>
#include <cuda_bf16.h>
#include <stdint.h>

namespace {

constexpr int NN = 10000;
constexpr int NE = 320000;
constexpr int NB = 132;
constexpr int NW = 20;
constexpr int NT = NW * 32;
constexpr int CW = NW - 1;
#define PWARP 10
constexpr int PW = PWARP;
constexpr int NPB = 76;
constexpr int CELL = 48;
constexpr int RCH = 2880;
constexpr int CAP = 19;
constexpr int DS = 4;
constexpr int STEPB = 160;
constexpr int NE4 = NE / 4;
constexpr int NPIECE = NB * 8;
constexpr int KB = 320, KN = 32 * KB;
constexpr uint32_t F_PAD = 0x80000000u;
constexpr uint32_t F_WRAP = 1;

constexpr int SLOTB = NW * 2048;
constexpr int SM_RING = 0;
constexpr int SM_META = SM_RING + DS * SLOTB;
constexpr int SM_AZ = SM_META + NW * CAP * STEPB;
constexpr int SM_MISC = SM_AZ + 2048;
constexpr int SM_TOTAL = SM_MISC + 2048;
constexpr int SM_STAGE = SM_RING;
constexpr int SM_HIST = SM_RING + 25600;
constexpr int SM_POS = SM_RING;
constexpr int SM_SMALL = SM_HIST + 13056;
constexpr int SM_LIST = SM_RING + SLOTB;
constexpr int SM_ROUT = SM_RING + 2 * SLOTB;
constexpr int SM_RECS = SM_RING + 3 * SLOTB;
constexpr int SM_RAWY = SM_META;
constexpr int SM_RAWE = SM_RAWY + 608 * 32;
constexpr int SM_KEYS = SM_RAWE + 608 * 32;
static_assert(SM_TOTAL <= 232448 && SM_KEYS + NPIECE * 16 <= SM_AZ, "smem");
static_assert(SM_RECS + NB * CELL * 16 + 16 <= SM_AZ && SM_KEYS + NPIECE * 16 <= SM_RECS + NB * CELL * 16 && SM_SMALL + 1152 <= SLOTB && DS == 4, "smem");

struct Scratch {
    uint4 keys[NB * NPIECE];
    uint4 recs[NB * RCH];
    uint4 stash[NB * NW * 256];
    unsigned bar[2];
    unsigned long long t0;
};
__device__ Scratch g_scratch;
#define TSTAMP(i)
#define TSTAMPC(i)
#define WSTAMP(i)
#define ESTAMP(i)

__device__ __forceinline__ void mma16816(float* d, uint32_t a0, uint32_t a1, uint32_t a2, uint32_t a3, uint32_t b0, uint32_t b1) {
    asm("mma.sync.aligned.m16n8k16.row.col.f32.bf16.bf16.f32 {%0,%1,%2,%3}, {%4,%5,%6,%7}, {%8,%9}, {%0,%1,%2,%3};"
        : "+f"(d[0]), "+f"(d[1]), "+f"(d[2]), "+f"(d[3]) : "r"(a0), "r"(a1), "r"(a2), "r"(a3), "r"(b0), "r"(b1));
}
__device__ __forceinline__ void mma1688z(float* d, uint32_t a0, uint32_t a1, uint32_t b0) {
    asm("mma.sync.aligned.m16n8k8.row.col.f32.bf16.bf16.f32 {%0,%1,%2,%3}, {%4,%5}, {%6}, {%7,%7,%7,%7};"
        : "=f"(d[0]), "=f"(d[1]), "=f"(d[2]), "=f"(d[3]) : "r"(a0), "r"(a1), "r"(b0), "f"(0.f));
}
__device__ __forceinline__ uint32_t pack2(float lo, float hi) {
    uint32_t r; asm("cvt.rn.bf16x2.f32 %0, %1, %2;" : "=r"(r) : "f"(hi), "f"(lo)); return r;
}
__device__ __forceinline__ float silu_h(float h) {
    float t; asm("tanh.approx.f32 %0, %1;" : "=f"(t) : "f"(h)); return fmaf(h, t, h);
}
__device__ __forceinline__ uint32_t mul_lo(uint32_t v, uint32_t r) {
    __nv_bfloat162 a = *(__nv_bfloat162*)&v, b = *(__nv_bfloat162*)&r; __nv_bfloat162 c = __hmul2(a, __low2bfloat162(b)); return *(uint32_t*)&c;
}
__device__ __forceinline__ uint32_t mul_hi(uint32_t v, uint32_t r) {
    __nv_bfloat162 a = *(__nv_bfloat162*)&v, b = *(__nv_bfloat162*)&r; __nv_bfloat162 c = __hmul2(a, __high2bfloat162(b)); return *(uint32_t*)&c;
}
__device__ __forceinline__ uint2 lds64(uint32_t a) {
    uint2 r; asm volatile("ld.shared.v2.u32 {%0,%1}, [%2];" : "=r"(r.x), "=r"(r.y) : "r"(a)); return r;
}
__device__ __forceinline__ uint4 lds128(uint32_t a) {
    uint4 r; asm volatile("ld.shared.v4.u32 {%0,%1,%2,%3}, [%4];" : "=r"(r.x), "=r"(r.y), "=r"(r.z), "=r"(r.w) : "r"(a) : "memory"); return r;
}
__device__ __forceinline__ void bar_sync(int id, int n) { asm volatile("bar.sync %0, %1;" :: "r"(id), "r"(n) : "memory"); }
__device__ __forceinline__ void bar_arrive(int id, int n) { asm volatile("bar.arrive %0, %1;" :: "r"(id), "r"(n) : "memory"); }
__device__ __forceinline__ void mbar_wait(uint32_t bar, uint32_t ph) {
    uint32_t done; int spins = 0;
    do {
        asm volatile("{.reg .pred p; mbarrier.try_wait.parity.shared.b64 p, [%1], %2; selp.u32 %0,1,0,p;}" : "=r"(done) : "r"(bar), "r"(ph) : "memory");
    } while (!done && ++spins < (1 << 22));
}
__device__ __forceinline__ unsigned gbar_read(const unsigned* ctr) {
    unsigned v; asm volatile("ld.relaxed.gpu.global.u32 %0, [%1];" : "=r"(v) : "l"(ctr) : "memory");
    return v;
}
__device__ __forceinline__ void gbar_arrive(unsigned* ctr) {
    asm volatile("red.add.release.gpu.global.u32 [%0], 1;" :: "l"(ctr) : "memory");
}
__device__ __forceinline__ bool gbar_wait(const unsigned* ctr, unsigned target) {
    unsigned v; int spins = 0;
    while (true) {
        asm volatile("ld.acquire.gpu.global.u32 %0, [%1];" : "=r"(v) : "l"(ctr) : "memory");
        if ((int)(v - target) >= 0 || ++spins > (1 << 22)) break;
    }
    return (int)(v - target) >= 0;
}
__device__ __forceinline__ int chunk_start4(int c) { return (c * NE4) / NB; }
__device__ __forceinline__ float bf2f(uint32_t h) { return __uint_as_float(h << 16); }

__device__ __noinline__ void slow_path(unsigned char* smem, int n0, int nn, const uint16_t* x, const int* src, const int* dst,
                                       const uint16_t* Y, const uint16_t* ef, const uint16_t* w_rad, const uint16_t* cg,
                                       const uint16_t* w_mix, __nv_bfloat16* out) {
    float* agg = (float*)smem;
    const int tid = threadIdx.x, lane = tid & 31, w = tid >> 5;
    bar_sync(1, NT);
    for (int i = tid; i < NPB * 512; i += NT) agg[i] = 0.f;
    bar_sync(1, NT);
    for (int e0 = w * 32; e0 < NE; e0 += NT) {
        int dl = dst[e0 + lane] - n0;
        unsigned m = __ballot_sync(0xffffffff, dl >= 0 && dl < nn);
        while (m) {
            int l = __ffs(m) - 1; m &= m - 1;
            int e = e0 + l, d = __shfl_sync(0xffffffff, dl, l), s = src[e];
            float T[16];
            for (int i = 0; i < 4; i++) for (int o = 0; o < 4; o++) {
                float a = 0.f;
                for (int f = 0; f < 4; f++) a += bf2f(Y[e * 4 + f]) * bf2f(cg[i * 16 + f * 4 + o]);
                T[i * 4 + o] = a;
            }
            for (int k = 0; k < 4; k++) {
                int c = lane + 32 * k;
                float z = 0.f;
                for (int j = 0; j < 4; j++) z += bf2f(ef[e * 4 + j]) * bf2f(w_rad[j * 128 + c]);
                float R = z / (1.f + __expf(-z));
                for (int o = 0; o < 4; o++) {
                    float a = 0.f;
                    for (int i = 0; i < 4; i++) a += bf2f(x[(size_t)s * 512 + c * 4 + i]) * T[i * 4 + o];
                    atomicAdd(&agg[d * 512 + c * 4 + o], R * a);
                }
            }
        }
    }
    bar_sync(1, NT);
    for (int i = tid; i < nn * 512; i += NT) {
        int n = i >> 9, d = (i >> 2) & 127, o = i & 3;
        float a = 0.f;
        for (int c = 0; c < 128; c++) a += agg[n * 512 + c * 4 + o] * bf2f(w_mix[c * 128 + d]);
        out[(size_t)(n0 + n) * 512 + (i & 511)] = __float2bfloat16(a);
    }
}

#define PACE 22750
#define YDELAY 300
#define POFF 4000
#define PSLEEP 32
#define RLEN 99
#define FDT 400
#define FOFF 1800
#define FSTAG 0
#define RELK 12
#define ILV 0
#define SPINS 40
#define ONEBAR 0
#define LEAD 0
#define PTOL0 300
#define PTOL 900
__global__ void __launch_bounds__(NT, 1)
tfn_kernel(const unsigned char* __restrict__ x, const int4* __restrict__ src4, const int4* __restrict__ dst4,
           const uint4* __restrict__ Y, const uint4* __restrict__ ef, const uint16_t* __restrict__ w_rad,
           const uint16_t* __restrict__ cg, const uint4* __restrict__ w_mix, uint32_t* __restrict__ out, Scratch* __restrict__ gs) {
    extern __shared__ __align__(1024) unsigned char smem[];
    const uint32_t sb = (uint32_t)__cvta_generic_to_shared(smem);
    const int b = blockIdx.x, tid = threadIdx.x, lane = tid & 31, g = lane >> 2, t = lane & 3;
    const int w = __shfl_sync(0xffffffff, tid >> 5, 0);
    uint32_t* stage = (uint32_t*)(smem + SM_STAGE);
    uint32_t* hist = (uint32_t*)(smem + SM_HIST);
    uint32_t* cnt = (uint32_t*)(smem + SM_MISC);
    uint32_t* deg = cnt + 136;
    uint32_t* order = deg + 104;
    uint32_t* cnt2 = order + 80;
    volatile uint32_t* flag = cnt2 + 136;
    const uint32_t mbarK = sb + SM_MISC + 1920, mbarR = mbarK + 8, mbarW = mbarK + 16;
    const int n0 = b * NPB, nn = min(NPB, NN - n0);
    TSTAMP(0);

    const int c0 = chunk_start4(b), c1 = chunk_start4(b + 1);
    const bool has4 = c0 + tid < c1;
    int4 d4 = make_int4(0, 0, 0, 0), s4 = d4;
    if (has4) { d4 = __ldg(dst4 + c0 + tid); s4 = __ldg(src4 + c0 + tid); }
    unsigned tgt = 0;
    if (tid == NT - 1) {
        tgt = gbar_read(&gs->bar[0]);
        asm volatile("mbarrier.init.shared.b64 [%0], 1;" :: "r"(mbarK));
        asm volatile("mbarrier.init.shared.b64 [%0], 1;" :: "r"(mbarR));
        asm volatile("mbarrier.init.shared.b64 [%0], 512;" :: "r"(mbarW));
        asm volatile("fence.mbarrier_init.release.cluster;" ::: "memory");
        flag[0] = 0; flag[12] = 0; flag[13] = 0; flag[15] = 0;
    }
    if (w == CW) {
        asm volatile("cp.async.cg.shared.global [%0], [%1], 16;" :: "r"(sb + SM_SMALL + lane * 16), "l"(w_rad + lane * 8) : "memory");
        asm volatile("cp.async.cg.shared.global [%0], [%1], 16;" :: "r"(sb + SM_SMALL + 512 + lane * 16), "l"(w_rad + 256 + lane * 8) : "memory");
        if (lane < 8) asm volatile("cp.async.cg.shared.global [%0], [%1], 16;" :: "r"(sb + SM_SMALL + 1024 + lane * 16), "l"(cg + lane * 8) : "memory");
    }
    ((uint4*)hist)[tid] = make_uint4(0, 0, 0, 0);
    {
        const uint32_t dk = (80 + b % 22) * KN + (b & 31) * KB;
#pragma unroll
        for (int j = 0; j < 3; j++) if (tid + j * NT < NB * CELL / 4) ((uint4*)stage)[tid + j * NT] = make_uint4(dk, dk, dk, dk);
    }
    if (tid < 136) cnt[tid] = 0;
    if (tid == 0) { *(uint4*)(smem + SM_MISC + 1824 + 32) = make_uint4(0, 0, 0, 0); *(uint4*)(smem + SM_RECS + NB * CELL * 16) = make_uint4(0, 0, 0, 0); }
    if (tid < 80) { deg[tid] = 127 - tid; order[tid] = tid; }
    __syncthreads();
    TSTAMP(9);
    if (tid == 64) {
        if (YDELAY) __nanosleep(YDELAY);
        asm volatile("mbarrier.arrive.expect_tx.shared.b64 _, [%0], %1;" :: "r"(mbarR), "r"((c1 - c0) * 64) : "memory");
        asm volatile("cp.async.bulk.shared::cluster.global.mbarrier::complete_tx::bytes [%0], [%1], %2, [%3];"
                     :: "r"(sb + SM_RAWY), "l"(Y + 2 * c0), "r"((c1 - c0) * 32), "r"(mbarR) : "memory");
        asm volatile("cp.async.bulk.shared::cluster.global.mbarrier::complete_tx::bytes [%0], [%1], %2, [%3];"
                     :: "r"(sb + SM_RAWE), "l"(ef + 2 * c0), "r"((c1 - c0) * 32), "r"(mbarR) : "memory");
    }

    uint32_t bin[4] = {0, 0, 0, 0}, slot[4] = {0, 0, 0, 0};
    if (has4) {
        const uint32_t dd[4] = {(uint32_t)d4.x, (uint32_t)d4.y, (uint32_t)d4.z, (uint32_t)d4.w}, ss[4] = {(uint32_t)s4.x, (uint32_t)s4.y, (uint32_t)s4.z, (uint32_t)s4.w};
#pragma unroll
        for (int k = 0; k < 4; k++) { bin[k] = dd[k] / NPB; slot[k] = atomicAdd(&cnt[bin[k]], 1); }
#pragma unroll
        for (int k = 0; k < 4; k++) stage[bin[k] * CELL + min(slot[k], CELL - 1)] = (dd[k] - bin[k] * NPB) * KN + ss[k];
    }
    if (w == CW) {
        if (tid == NT - 1) { tgt = tgt / NB + 1; flag[14] = (tgt & 1) << 31; tgt *= NB; }
        asm volatile("cp.async.wait_all;" ::: "memory");
    }
    bar_sync(1, NT);
    TSTAMP(1);
    const uint32_t tag = flag[14];
#pragma unroll
    for (int j = 0; j < 2; j++) {
        const int i = tid + j * NT;
        if (i < NPIECE) {
            const uint2 sa = *(const uint2*)(stage + i * 6), sc = *(const uint2*)(stage + i * 6 + 2);
            uint2 se = *(const uint2*)(stage + i * 6 + 4);
            const uint32_t cf = cnt[i >> 3], cn = min(cf, 63u);
            if ((i & 7) == 7) {
                const uint32_t al = cf > CELL - 8 ? 7 : 0;
                uint32_t o;
                asm volatile("atom.shared.add.u32 %0, [%1], %2;" : "=r"(o) : "r"(sb + SM_MISC + 1824 + 60), "r"(cf + al) : "memory");
                se.y = (o + al) & ~al;
                cnt2[i >> 3] = se.y;
            }
            asm volatile("{.reg .b64 lo, hi; mov.b64 lo, {%1,%2}; mov.b64 hi, {%3,%4}; st.relaxed.gpu.global.v2.b64 [%0], {lo, hi};}"
                         :: "l"(gs->keys + ((i >> 3) * NB + b) * 8 + ((i ^ b) & 7)),
                            "r"(sa.x | (se.x << 20)), "r"(sa.y | ((se.x >> 12) << 20) | ((cn & 7) << 28) | tag),
                            "r"(sc.x | (se.y << 20)), "r"(sc.y | ((se.y >> 12) << 20) | ((cn >> 3) << 28) | tag) : "memory");
        }
    }
    bar_sync(1, NT);
    if (tid == NT - 1) {
        TSTAMPC(10);
        asm volatile("red.add.relaxed.gpu.global.u32 [%0], 1;" :: "l"(&gs->bar[0]) : "memory");
        asm volatile("mbarrier.arrive.expect_tx.shared.b64 _, [%0], %1;" :: "r"(mbarK), "r"(NPIECE * 16) : "memory");
        gbar_wait(&gs->bar[0], tgt);
        TSTAMPC(13);
        asm volatile("fence.proxy.async.global;" ::: "memory");
        asm volatile("cp.async.bulk.shared::cluster.global.mbarrier::complete_tx::bytes [%0], [%1], %2, [%3];"
                 :: "r"(sb + SM_KEYS), "l"(gs->keys + b * NPIECE), "r"(NPIECE * 16), "r"(mbarK) : "memory");
    }
    __syncwarp();
    uint32_t at[4];
    {
        const int o = g & 3, f = 2 * (t & 1);
#pragma unroll
        for (int i = 0; i < 4; i++) {
            const uint16_t* cp = (const uint16_t*)(smem + SM_SMALL + 1024) + i * 16 + f * 4 + o;
            at[i] = (t >> 1) == (g >> 2) ? cp[0] | ((uint32_t)cp[4] << 16) : 0;
        }
    }

    const int q = lane >> 3, c = lane & 7;
    const uint32_t ring0 = sb + SM_RING + w * 2048;
    uint32_t wdst = ring0 + q * 128 + ((c + 2 * q) & 7) * 16;
    uint32_t rsrc = ring0 + t * 128 + ((g + 2 * t) & 7) * 16;
    uint32_t recl = sb + SM_META + w * (CAP * STEPB) + g * 16 + (t & 1) * 8, srcl = sb + SM_META + w * (CAP * STEPB) + 128 + q * 8;
    uint32_t flg = sb + SM_MISC + (136 + 104 + 80 + 136) * 4;
    asm volatile("" : "+r"(wdst), "+r"(rsrc), "+r"(recl), "+r"(srcl), "+r"(flg));
    uint32_t key[2][6], ha[2][6], rk[2][6], kidx[2], ka[2];
    int nk[2];
#pragma unroll
    for (int j = 0; j < 2; j++) {
        const int i0 = j ? 2 * 608 - 1 - tid : tid, i = min(i0, NPIECE - 1), r = i / NB, cc = i - r * NB;
        ka[j] = sb + SM_KEYS + (cc * 8 + ((r ^ cc) & 7)) * 16;
        kidx[j] = (cc * CELL + r * 6) << 17;
        nk[j] = i0 < NPIECE && w < CW ? -6 * r : -1000;
    }
    asm volatile("" : "+r"(at[0]), "+r"(at[1]), "+r"(at[2]), "+r"(at[3]), "+r"(ka[0]), "+r"(ka[1]), "+r"(kidx[0]), "+r"(kidx[1]), "+r"(nk[0]), "+r"(nk[1]));
    if (w == CW) {
        __syncwarp();
        bar_sync(7, NT);
        if (tid == NT - 1) {
            TSTAMPC(11);
            asm volatile("cp.async.bulk.global.shared::cta.bulk_group [%0], [%1], %2;"
                         :: "l"(gs->recs + b * RCH), "r"(sb + SM_ROUT), "r"(((flag[15] + 1) & ~1u) * 16) : "memory");
            asm volatile("cp.async.bulk.commit_group;" ::: "memory");
            mbar_wait(mbarK, 0);
            unsigned long long tbase;
            asm volatile("mov.u64 %0, %%globaltimer;" : "=l"(tbase));
            tbase += POFF;
            flag[1] = (uint32_t)tbase; flag[4] = (uint32_t)tbase; flag[5] = (uint32_t)(tbase >> 32);
            asm volatile("red.max.relaxed.gpu.global.u64 [%0], %1;" :: "l"(&gs->t0), "l"(tbase) : "memory");
            if (b < 128) asm volatile("cp.async.bulk.prefetch.L2.global [%0], 256;" :: "l"(w_mix + b * 16));
            asm volatile("cp.async.bulk.wait_group 0;" ::: "memory");
            TSTAMPC(14);
            asm volatile("red.add.relaxed.gpu.global.u32 [%0], 1;" :: "l"(&gs->bar[1]) : "memory");
            TSTAMPC(15);
        }
    } else {
        if (w < 8) {
            const uint32_t* wp = (const uint32_t*)(smem + SM_SMALL) + (t & 1) * 128 + 8 * w + g;
            const uint32_t wr0 = t < 2 ? wp[0] : 0, wr1 = t < 2 ? wp[64] : 0;
            *(uint2*)(smem + SM_AZ + (w >> 1) * 512 + lane * 16 + (w & 1) * 8) =
                make_uint2(pack2(0.5f * bf2f(wr0 & 0xFFFF), 0.5f * bf2f(wr1 & 0xFFFF)), pack2(0.5f * bf2f(wr0 >> 16), 0.5f * bf2f(wr1 >> 16)));
        }
        const bool sw = g & 1;
        uint32_t rp[4];
#pragma unroll
        for (int k = 0; k < 4; k++) rp[k] = cnt2[bin[k]] + slot[k];
        uint4* ro = (uint4*)(smem + SM_ROUT);
        uint4 *p0 = ro + (sw ? rp[2] : rp[0]), *p1 = ro + (sw ? rp[3] : rp[1]), *p2 = ro + (sw ? rp[0] : rp[2]), *p3 = ro + (sw ? rp[1] : rp[3]);
        const uint32_t ya = sb + SM_RAWY + tid * 32 + (sw ? 16 : 0);
        mbar_wait(mbarR, 0);
        TSTAMP(18);
        if (has4) {
            const uint4 y0 = lds128(ya), e0 = lds128(ya + (SM_RAWE - SM_RAWY)), y1 = lds128(ya ^ 16), e1 = lds128((ya ^ 16) + (SM_RAWE - SM_RAWY));
            *p0 = make_uint4(y0.x, e0.x, y0.y, e0.y); *p1 = make_uint4(y0.z, e0.z, y0.w, e0.w);
            *p2 = make_uint4(y1.x, e1.x, y1.y, e1.y); *p3 = make_uint4(y1.z, e1.z, y1.w, e1.w);
        }
        asm volatile("fence.proxy.async.shared::cta;" ::: "memory");
        bar_arrive(7, NT);
    }
    __syncwarp();
    TSTAMP(2);

    if (w < CW) {
        mbar_wait(mbarK, 0);
        TSTAMP(3);
        uint4 v[2] = {lds128(ka[0]), lds128(ka[1])};
#pragma unroll
        for (int j = 0; j < 2; j++) {
            int spins = 0;
            while ((int)((v[j].y ^ tag) | (v[j].w ^ tag)) < 0) {
                asm volatile("{.reg .b64 lo, hi; ld.relaxed.gpu.global.v2.b64 {lo, hi}, [%4]; mov.b64 {%0,%1}, lo; mov.b64 {%2,%3}, hi;}"
                             : "=r"(v[j].x), "=r"(v[j].y), "=r"(v[j].z), "=r"(v[j].w) : "l"((const unsigned char*)(gs->keys + b * NPIECE) + (ka[j] - sb - SM_KEYS)) : "memory");
                if (++spins > (1 << 20)) { *flag = 1; break; }
            }
            const uint32_t hc = ((v[j].y >> 28) & 7) | ((v[j].w >> 25) & 0x38);
            if (j == 1 && nk[j] == -42) {
                cnt[kidx[j] / (CELL << 17)] = hc | ((v[j].z >> 20) << 8);
                v[j].w |= ((80 * KN) >> 12) << 20;
            }
            if (hc > CELL - 1) *flag = 1;
            nk[j] += hc;
            if (nk[j] > 0) {
                key[j][0] = v[j].x & 0xFFFFF; key[j][1] = v[j].y & 0xFFFFF; key[j][2] = v[j].z & 0xFFFFF; key[j][3] = v[j].w & 0xFFFFF;
                key[j][4] = (v[j].x >> 20) | ((v[j].y >> 8) & 0xFF000); key[j][5] = (v[j].z >> 20) | ((v[j].w >> 8) & 0xFF000);
#pragma unroll
                for (int u = 0; u < 6; u++) {
                    ha[j][u] = __umulhi(key[j][u], 0xFFFFFFFFu / KB + 1);
                    rk[j][u] = atomicAdd(&hist[ha[j][u]], 1);
                    atomicAdd(&deg[ha[j][u] >> 5], 128);
                }
            }
        }
        bar_sync(9, NT - 32);
        TSTAMP(20);
#pragma unroll
        for (int j = 0; j < 2; j++) kidx[j] += ((cnt[kidx[j] / (CELL << 17)] >> 8) & 7) << 17;
        const int n = tid >> 3, sub = tid & 7;
        const uint32_t me = deg[n];
        int r = 0;
#pragma unroll
        for (int k = 0; k < 5; k++) { const uint2 dd = *(const uint2*)(deg + sub * 10 + 2 * k); r += (dd.x > me) + (dd.y > me); }
        r += __shfl_xor_sync(0xffffffff, r, 1); r += __shfl_xor_sync(0xffffffff, r, 2); r += __shfl_xor_sync(0xffffffff, r, 4);
        if (sub == 0) order[r] = n;
    }
    bar_sync(1, NT);
    TSTAMP(22);
    uint32_t len2;
    {
        const uint2 na = *(const uint2*)(order + 2 * w);
        uint2 nb = *(const uint2*)(order + 78 - 2 * w);
        const uint32_t ia0 = na.x * 32 + lane, ia1 = na.y * 32 + lane;
        const uint32_t ha0 = hist[ia0], ha1 = hist[ia1];
        uint32_t hb0 = hist[nb.y * 32 + lane], hb1 = hist[nb.x * 32 + lane];
        const int su = __reduce_add_sync(0xffffffff, (int)(ha0 - ha1) * (2 * lane - 31)), sv = __reduce_add_sync(0xffffffff, (int)(hb0 - hb1) * (2 * lane - 31));
        if ((su ^ sv) >= 0) {
            nb = make_uint2(nb.y, nb.x);
            const uint32_t tmp = hb0; hb0 = hb1; hb1 = tmp;
            *(uint2*)(order + 78 - 2 * w) = nb;
        }
        const uint32_t ib0 = nb.y * 32 + lane, ib1 = nb.x * 32 + lane;
        const uint32_t ca = ha0 + (ha1 << 16), cab = ca + hb0 + (hb1 << 16);
        uint32_t inc = cab;
#pragma unroll
        for (int o = 1; o < 32; o <<= 1)
            asm volatile("{.reg .pred p; .reg .u32 u; shfl.sync.up.b32 u|p, %0, %1, 0, 0xffffffff; @p add.u32 %0, %0, u;}" : "+r"(inc) : "r"(o));
        const uint32_t ea = inc - cab, eb = ea + ca, base = sb + SM_LIST + w * 2048;
        uint2* pos = (uint2*)(smem + SM_POS);
        pos[ia0] = make_uint2(base + (ea & 0xFFFF) * 8, na.x * (0u - 4 * KN));
        pos[ib0] = make_uint2(base + (eb & 0xFFFF) * 8, nb.y * (0u - 4 * KN) + 0x10000);
        pos[ia1] = make_uint2(base + 4 + (ea >> 16) * 8, na.y * (0u - 4 * KN));
        pos[ib1] = make_uint2(base + 4 + (eb >> 16) * 8, nb.x * (0u - 4 * KN) + 0x10000);
        if (max(inc & 0xFFFF, inc >> 16) > 4 * CAP) *flag = 1;
        len2 = __shfl_sync(0xffffffff, inc, 31);
    }
    uint32_t ci = cnt[min(w + NW * lane, NB)];
    ci = ((((w + NW * lane) * (RCH / 8) + (ci >> 11)) << 8) | (ci & 0xFF)) + ((ci >> 8) & 7);
    if (w == CW) {
        bar_arrive(9, NT);
        if (tid == NT - 1) {
            uint32_t v1, g0; int spins = 0;
            do {
                asm volatile("{.reg .u32 a, b; ld.acquire.gpu.global.v4.u32 {a,%0,%1,b}, [%2];}" : "=r"(v1), "=r"(g0) : "l"(gs->bar) : "memory");
            } while ((int)(v1 - tgt) < 0 && ++spins < (1 << 22));
            if ((int)(v1 - tgt) < 0) *flag = 1;
            if (g0 - flag[1] < 30000) flag[1] = g0;
            TSTAMPC(17);
        }
        __syncwarp();
    } else {
        bar_sync(9, NT);
        TSTAMP(21);
        const uint32_t over = *flag;
#pragma unroll
        for (int j = 0; j < 2; j++) {
            if (nk[j] > 0) {
                uint2 h[6];
#pragma unroll
                for (int u = 0; u < 6; u++) h[u] = lds64(sb + SM_POS + ha[j][u] * 8);
                if (over) nk[j] = 0;
#pragma unroll
                for (int u = 0; u < 6; u++)
                    asm volatile("{.reg .pred p; setp.gt.s32 p, %2, %3; @p st.shared.u32 [%0], %1;}"
                                 :: "r"(h[u].x + rk[j][u] * 8), "r"(key[j][u] * 4 + h[u].y + (kidx[j] + (u << 17))), "r"(nk[j]), "r"(u) : "memory");
            }
        }
    }
    bar_sync(1, NT);
    TSTAMP(4);
    if (*flag) {
        slow_path(smem, n0, nn, (const uint16_t*)x, (const int*)src4, (const int*)dst4, (const uint16_t*)Y, (const uint16_t*)ef, w_rad, cg,
                  (const uint16_t*)w_mix, (__nv_bfloat16*)out);
        return;
    }
    {
        const uint4* gp = gs->recs + lane;
        const uint32_t sp = sb + SM_RECS + (w * CELL + lane) * 16;
#pragma unroll
        for (int j = 0; j < 7; j++) {
            const uint32_t cj = __shfl_sync(0xffffffff, ci, j);
            asm volatile("{.reg .pred p; setp.lt.u32 p, %2, %3; @p cp.async.cg.shared.global [%0], [%1], 16;}"
                         :: "r"(sp + j * (NW * CELL * 16)), "l"(gp + (size_t)(cj >> 8) * 8), "r"(lane), "r"(cj & 0xFF) : "memory");
        }
        for (uint32_t m = __ballot_sync(0xffffffff, (ci & 0xFF) > 32); m; m &= m - 1) {
            const int j = __ffs(m) - 1;
            const uint32_t cj = __shfl_sync(0xffffffff, ci, j);
            if (lane + 32 < (cj & 0xFF))
                asm volatile("cp.async.cg.shared.global [%0], [%1], 16;" :: "r"(sp + j * (NW * CELL * 16) + 512), "l"(gp + (size_t)(cj >> 8) * 8 + 32) : "memory");
        }
        asm volatile("cp.async.commit_group;" ::: "memory");
    }
    const int S = __shfl_sync(0xffffffff, max((int)(max(len2 & 0xFFFF, len2 >> 16) + 3) >> 2, DS + 1), 0);
    const int mylen = (lane & 1) ? len2 >> 16 : len2 & 0xFFFF;
    constexpr int NRAW = (CAP + 3) / 4;
    uint32_t bits0 = 0, raw[NRAW];
    unsigned char* meta = smem + SM_META + w * (CAP * STEPB);
#pragma unroll
    for (int k = 0; k < NRAW; k++) raw[k] = mylen ? ((uint32_t*)(smem + SM_LIST + w * 2048))[min(k * 16 + (lane >> 1), mylen - 1) * 2 + (lane & 1)] : 4 * n0;
    const uint32_t sv0 = raw[0] & 0xFFFF;
    const unsigned char* pbase = x + c * 16;
    auto cpa2 = [&](uint32_t dstp, uint32_t sv) {
        asm volatile("cp.async.cg.shared.global [%0], [%1], 16; cp.async.cg.shared.global [%0+1024], [%1+128], 16;"
                     :: "r"(dstp), "l"(pbase + (size_t)sv * 256) : "memory");
    };
    auto cpa2p = [&](uint32_t dstp, uint32_t sv) {
        asm volatile("{.reg .pred p; setp.ge.s32 p, %2, 0; @p cp.async.cg.shared.global [%0], [%1], 16; @p cp.async.cg.shared.global [%0+1024], [%1+128], 16;}"
                     :: "r"(dstp), "l"(pbase + (size_t)sv * 256), "r"(sv) : "memory");
    };
    auto wait_until = [&](uint32_t tt) {
        asm volatile("{.reg .pred p; .reg .u32 d;\n"
                     "PACE_LOOP: mov.u32 d, %%globaltimer_lo; sub.u32 d, %0, d; setp.lt.u32 p, d, 32768; @p nanosleep.u32 %1; @p bra.uni PACE_LOOP;}"
                     :: "r"(tt), "n"(PSLEEP) : "memory");
    };
    const uint32_t tfill = flag[1] - FOFF + w * FSTAG;
    auto fill = [&](int i) {
        if (FDT) wait_until(tfill + i * FDT);
        cpa2(wdst + i * SLOTB, __shfl_sync(0xffffffff, sv0, 8 * i + 2 * q)); cpa2(wdst + i * SLOTB + 512, __shfl_sync(0xffffffff, sv0, 8 * i + 2 * q + 1));
        asm volatile("cp.async.commit_group;" ::: "memory");
    };
    fill(0);
    TSTAMP(5);
    auto relay = [&]() {
        uint32_t g0, g1, b0, b1;
        asm volatile("ld.volatile.shared.v2.u32 {%0,%1}, [%4+40]; ld.volatile.shared.v2.u32 {%2,%3}, [%4+16];"
                     : "=r"(g0), "=r"(g1), "=r"(b0), "=r"(b1) : "r"(flg) : "memory");
        const unsigned long long dg = (((unsigned long long)g1 << 32) | g0) - (((unsigned long long)b1 << 32) | b0);
        asm volatile("{.reg .pred p, q; setp.eq.u32 p, %1, 0; setp.lt.u64 q, %2, 30000; @q st.shared.u32 [%3+4], %4;\n"
                     "@p cp.async.cg.shared.global [%3+32], [%0], 16;}"
                     :: "l"(gs->bar), "r"(lane), "l"(dg), "r"(flg), "r"(g0) : "memory");
    };
    uint32_t ra[NRAW];
#pragma unroll
    for (int k = 0; k < NRAW; k++) {
        const uint32_t m = (__ballot_sync(0xffffffff, raw[k] & 0x10000) >> g) & 0x01010101u;
        bits0 |= ((m * 0x10204080u) >> 28) << (4 * k);
        ra[k] = sb + SM_RECS + (k * 16 + (lane >> 1) < mylen ? raw[k] >> 17 : NB * CELL) * 16;
    }
    if (t < 2) bits0 = ~bits0;
    asm volatile("" : "+r"(bits0), "+r"(ra[0]), "+r"(ra[1]), "+r"(ra[2]), "+r"(ra[3]), "+r"(ra[4]));
    fill(1);
    asm volatile("cp.async.wait_group 2;" ::: "memory");
    bar_sync(1, NT);
    TSTAMP(19);
    {
        uint4 rv[NRAW];
#pragma unroll
        for (int k = 0; k < NRAW - 1; k++) rv[k] = lds128(ra[k]);
        if ((NRAW - 1) * 4 < S) rv[NRAW - 1] = lds128(ra[NRAW - 1]);
        fill(2);
        bar_sync(1, NT);
        TSTAMP(12);
        unsigned char* mr = meta + (q - 1) * STEPB + c * 16;
        unsigned char* ms = meta + (q - DS - 1) * STEPB + 128 + c * 4;
#pragma unroll
        for (int k = 0; k < NRAW; k++) {
            if (k == 0) {
                *(uint4*)(mr + (q == 0 ? S * STEPB : 0)) = rv[k];
                *(uint32_t*)(ms + S * STEPB) = sv0 + F_WRAP + ((lane >> 1) >= mylen ? F_PAD : 0);
            } else if (k * 4 + q < S) {
                *(uint4*)(mr + k * 4 * STEPB) = rv[k];
                *(uint32_t*)(ms + k * 4 * STEPB + (k == 1 && q == 0 ? S * STEPB : 0)) = (raw[k] & 0xFFFF) + (k * 16 + (lane >> 1) >= mylen ? F_PAD : 0);
            }
        }
    }
    __syncwarp();
    const uint32_t tphase = PACE / 4;
    uint32_t dreg;
    {
        const int ls = lane >= S ? min(lane - S, S - 1) : lane, st = ls == 0 ? S - 1 : ls - 1;
        const uint4 u0 = *(const uint4*)(meta + st * STEPB + 128), u1 = *(const uint4*)(meta + st * STEPB + 144);
        int pos = (u0.x + u0.y + u0.z + u0.w + u1.x + u1.y + u1.z + u1.w) << 1 >> 6;
        pos += ((u0.x & F_WRAP) ? NN : 0) + (lane >= S ? NN : 0) - NN * (2 * DS + 1) / 32;
        dreg = pos * (int)tphase / NN;
    }
    fill(3);
    TSTAMP(6);

    uint32_t* stash = (uint32_t*)(gs->stash + (b * NW + w) * 256) + lane;
    float acc[4][4];
#pragma unroll
    for (int i = 0; i < 16; i++) acc[i / 4][i % 4] = 0.f;
    uint4 az = *(const uint4*)(smem + SM_AZ + lane * 16);
    uint32_t dcur = dreg, dl = 0, now = flag[1], tcur = 0;
    uint32_t mp = 0, smask = 1, didx = 2;
    uint32_t mend = S * STEPB;
    uint2 r = lds64(mend - STEPB + recl), s0 = lds64(mend - STEPB + srcl);
    auto step = [&](const uint32_t off, const int mode, const bool pc = true) {
        if (mode == 0 && pc) { unsigned long long n64; asm volatile("mov.u64 %0, %%globaltimer;" : "=l"(n64)); now = (uint32_t)n64; }
        const uint2 rc = r, sc = s0;
        if (mode != 4) r = lds64(mp + recl);
        if (mode == 0) s0 = lds64(mp + srcl);
        asm volatile("cp.async.wait_group %0;" :: "n"(DS - 1) : "memory");
        const uint4 xa = lds128(rsrc + off), xb = lds128(rsrc + off + 512), xc = lds128(rsrc + off + 1024), xd = lds128(rsrc + off + 1536);
        if (mode == 0) {
            if (pc) { dl = __shfl_sync(0xffffffff, dcur, didx); didx += 2; }
            cpa2p(wdst + off, sc.x); cpa2p(wdst + off + 512, sc.y);
        }
        if (mode == 1 && w < 16) {
#pragma unroll
            for (int j = 0; j < 4; j++) {
                const int kk = 4 * j + q, ch = 16 * (w & 7) + 2 * (kk & 7) + (kk >> 3);
                asm volatile("cp.async.cg.shared.global [%0], [%1], 16;" :: "r"(ring0 + kk * 128 + ((c ^ (kk & 7)) << 4)), "l"(w_mix + ch * 16 + (w >> 3) * 8 + c) : "memory");
            }
            asm volatile("cp.async.mbarrier.arrive.noinc.shared.b64 [%0];" :: "r"(mbarW) : "memory");
        }
        if (mode == 2 || mode == 3) {
#pragma unroll
            for (int j = 0; j < 4; j += mode - 1)
                asm volatile("cp.async.cg.shared.global [%0], [%1], 16;" :: "r"(ring0 + off + j * 512 + lane * 16), "l"(stash + (mode - 2) * 512 + j * 128 + lane * 3) : "memory");
        }
        if (mode < 4) asm volatile("cp.async.commit_group;" ::: "memory");
        float z[4], y[4], t1[4], t2[4];
        mma1688z(z, az.x, az.y, rc.y);
        mma1688z(y, az.z, az.w, rc.y);
        uint32_t bt;
        asm("{.reg .pred p; .reg .b32 m; and.b32 m, %2, %3; setp.ne.u32 p, m, 0; selp.b32 %0, %1, 0, p;}" : "=r"(bt) : "r"(rc.x), "r"(bits0), "r"(smask));
        mma1688z(t1, at[0], at[1], bt);
        mma1688z(t2, at[2], at[3], bt);
        const uint32_t T0 = pack2(t1[0], t1[2]), T1 = pack2(t2[0], t2[2]), T2 = pack2(t1[1], t1[3]), T3 = pack2(t2[1], t2[3]);
        uint32_t R[8];
#pragma unroll
        for (int i = 0; i < 4; i++) { R[i] = __float_as_uint(silu_h(z[i])); R[4 + i] = __float_as_uint(silu_h(y[i])); }
        mma16816(acc[0], mul_hi(xa.x, R[0]), mul_hi(xa.z, R[2]), mul_hi(xa.y, R[0]), mul_hi(xa.w, R[2]), T0, T1);
        mma16816(acc[1], mul_hi(xb.x, R[1]), mul_hi(xb.z, R[3]), mul_hi(xb.y, R[1]), mul_hi(xb.w, R[3]), T2, T3);
        mma16816(acc[2], mul_hi(xc.x, R[4]), mul_hi(xc.z, R[6]), mul_hi(xc.y, R[4]), mul_hi(xc.w, R[6]), T0, T1);
        mma16816(acc[3], mul_hi(xd.x, R[5]), mul_hi(xd.z, R[7]), mul_hi(xd.y, R[5]), mul_hi(xd.w, R[7]), T2, T3);
        mp += STEPB; smask <<= 1;
    };
    auto putacc = [&](uint32_t* p) {
#pragma unroll
        for (int i = 0; i < 16; i++) acc[i / 4][i % 4] *= 1.0028f;
        p[0] = pack2(acc[0][0], acc[0][1]); p[32] = pack2(acc[0][2], acc[0][3]); p[64] = pack2(acc[2][0], acc[2][1]); p[96] = pack2(acc[2][2], acc[2][3]);
        p[256] = pack2(acc[1][0], acc[1][1]); p[288] = pack2(acc[1][2], acc[1][3]); p[320] = pack2(acc[3][0], acc[3][1]); p[352] = pack2(acc[3][2], acc[3][3]);
    };
    int ph = 0;
    auto phase_end = [&](const int k) {
        az = lds128(sb + SM_AZ + (ph + 1) * 512 + lane * 16);
        putacc(stash + ph * ph * 128);
#pragma unroll
        for (int i = 0; i < 16; i++) acc[i / 4][i % 4] = 0.f;
        pbase += 256; mp = 0; smask = 1; ph++;
        dcur += tphase; didx = 1 + (k & 1);
        if (ph == 3) mend -= DS * STEPB;
        WSTAMP(ph - 1);
    };
    uint32_t t0 = now;
    auto report = [&](uint32_t cand) {
        uint32_t b0, b1;
        asm volatile("ld.volatile.shared.v2.u32 {%0,%1}, [%2+16];" : "=r"(b0), "=r"(b1) : "r"(flg) : "memory");
        asm volatile("{.reg .pred p; setp.eq.u32 p, %2, 0; @p red.max.relaxed.gpu.global.u64 [%0], %1;}"
                     :: "l"(&gs->t0), "l"((((unsigned long long)b1 << 32) | b0) + (cand - b0)), "r"(lane) : "memory");
    };
    const bool reporter = w == PW && max(len2 & 0xFFFF, len2 >> 16) <= RLEN;
    if (reporter) {
        asm volatile("mov.u32 %0, %%globaltimer_lo;" : "=r"(now));
        now += PTOL - PTOL0;
    }
    const uint32_t bias = w == 0 ? 1u << 20 : 0;
    if (w == 0) relay();
    dcur += bias;
    auto body = [&](const int k) -> bool {
        if (k == 2) asm volatile("ld.volatile.shared.u32 %0, [%1+4];" : "=r"(t0) : "r"(flg));
        const bool pc = k & 1;
        step(k * SLOTB, 0, pc);
        if (!pc) {
            if (mp == mend) phase_end(k);
        } else if (mp == mend || now < dl) {
            if (mp == mend) {
                if (k == 3 && ph == 3) return true;
                phase_end(k);
            }
            if (w == 0) { dl -= 1u << 20; relay(); }
            wait_until(dl);
        }
        return false;
    };
    wait_until(__shfl_sync(0xffffffff, dreg, 0) + t0);
    while (true) {
        if (reporter) {
            const uint32_t cand = now - dl + tcur - PTOL;
            if ((int)(cand - t0) > 0) report(cand);
        }
        dcur += t0 - tcur; tcur = t0;
        body(0); body(1); body(2);
        if (body(3)) break;
    }
    __syncwarp();
    step(0, 1); step(SLOTB, 2); step(2 * SLOTB, 3); step(3 * SLOTB, 4);
    WSTAMP(3); ESTAMP(0);

    {
        putacc((uint32_t*)(smem + SM_RING + 2 * SLOTB + w * 2048 + 512) + lane);
        const int wg = w >> 2, w4 = w & 3;
        int nd[8];
#pragma unroll
        for (int j = 0; j < 8; j++) { const int l = wg * 8 + j; nd[j] = order[(t >> 1) ? 79 - l : l]; asm volatile("" : "+r"(nd[j])); }
        const bool odd = t & 1;
        uint2* ob = (uint2*)out + (size_t)n0 * 128 + w4 * 16 + g + (odd ? 8 : 0);
        asm volatile("cp.async.wait_all;" ::: "memory");
        mbar_wait(mbarW, 0);
        asm volatile("fence.proxy.async.shared::cta;" ::: "memory");
        ESTAMP(1);
        if (!ONEBAR) bar_sync(2 + wg, 128);
        uint32_t ticket = 0;
        if ((tid & 127) == 0) {
            asm volatile("atom.shared.add.u32 %0, [%1+48], 1;" : "=r"(ticket) : "r"(flg) : "memory");
            int spins = 0;
            while (flag[13] + LEAD < ticket && ++spins < (1 << 16)) { if (SPINS) __nanosleep(SPINS); }
        }
        bar_sync(2 + wg, 128);
        const uint64_t descA0 = (uint64_t)(((sb + SM_RING) & 0x3FFFF) >> 4) | ((uint64_t)1 << 16) | ((uint64_t)(1024 >> 4) << 32) | ((uint64_t)1 << 62);
        const uint64_t descB0 = (uint64_t)(((sb + SM_RING + SLOTB + wg * 8192) & 0x3FFFF) >> 4) | ((uint64_t)(128 >> 4) << 16) | ((uint64_t)(1024 >> 4) << 32);
        auto release = [&]() { asm volatile("{.reg .pred p; setp.eq.u32 p, %1, 0; @p st.volatile.shared.u32 [%0+52], %2;}" :: "r"(flg), "r"(tid & 127), "r"(ticket + 1) : "memory"); };
        float d[2][32];
        asm volatile("wgmma.fence.sync.aligned;" ::: "memory");
        ESTAMP(2);
#pragma unroll
        for (int i1 = 0; i1 < 2; i1++) {
#pragma unroll
            for (int i0 = 0; i0 < 8; i0++) {
                const int mt = ILV ? i0 & 1 : i1, ks = ILV ? i1 * 4 + (i0 >> 1) : i0;
                if (i1 * 8 + i0 == RELK) release();
                const uint64_t da = descA0 + (uint64_t)((ks * 2048 + mt * 16384) >> 4), db = descB0 + (uint64_t)(((ks & 3) * 256 + (ks >> 2) * SLOTB) >> 4);
                asm volatile("{.reg .pred p; setp.ne.b32 p, %34, 0;\n"
                    "wgmma.mma_async.sync.aligned.m64n64k16.f32.bf16.bf16 "
                    "{%0,%1,%2,%3,%4,%5,%6,%7,%8,%9,%10,%11,%12,%13,%14,%15,%16,%17,%18,%19,%20,%21,%22,%23,%24,%25,%26,%27,%28,%29,%30,%31}, %32, %33, p, 1, 1, 1, 1;}"
                    : "+f"(d[mt][0]), "+f"(d[mt][1]), "+f"(d[mt][2]), "+f"(d[mt][3]), "+f"(d[mt][4]), "+f"(d[mt][5]), "+f"(d[mt][6]), "+f"(d[mt][7]),
                      "+f"(d[mt][8]), "+f"(d[mt][9]), "+f"(d[mt][10]), "+f"(d[mt][11]), "+f"(d[mt][12]), "+f"(d[mt][13]), "+f"(d[mt][14]), "+f"(d[mt][15]),
                      "+f"(d[mt][16]), "+f"(d[mt][17]), "+f"(d[mt][18]), "+f"(d[mt][19]), "+f"(d[mt][20]), "+f"(d[mt][21]), "+f"(d[mt][22]), "+f"(d[mt][23]),
                      "+f"(d[mt][24]), "+f"(d[mt][25]), "+f"(d[mt][26]), "+f"(d[mt][27]), "+f"(d[mt][28]), "+f"(d[mt][29]), "+f"(d[mt][30]), "+f"(d[mt][31])
                    : "l"(da), "l"(db), "r"(ks));
            }
            asm volatile("wgmma.commit_group.sync.aligned;" ::: "memory");
        }
        if (RELK == 16) release();
#pragma unroll
        for (int mt = 0; mt < 2; mt++) {
            if (mt == 0 && !ILV) asm volatile("wgmma.wait_group.sync.aligned 1;" ::: "memory");
            else asm volatile("wgmma.wait_group.sync.aligned 0;" ::: "memory");
            if (RELK == 17 + mt) release();
            ESTAMP(3 + mt);
#pragma unroll
            for (int i = 0; i < 32; i++) asm volatile("" : "+f"(d[mt][i]) :: "memory");
#pragma unroll
            for (int j = 0; j < 8; j++) {
                const uint32_t v0 = pack2(d[mt][4 * j], d[mt][4 * j + 1]), v1 = pack2(d[mt][4 * j + 2], d[mt][4 * j + 3]);
                const uint32_t rv = __shfl_xor_sync(0xffffffff, odd ? v0 : v1, 1);
                if (nd[j] < nn) ob[nd[j] * 128 + mt * 64] = odd ? make_uint2(rv, v1) : make_uint2(v0, rv);
            }
        }
    }
    TSTAMP(8); ESTAMP(5);
}

}

extern "C" void kernel_launch(void* const* d_in, const int* in_sizes, int n_in, void* d_out, int out_size) {
    (void)in_sizes; (void)n_in; (void)out_size;
    cudaFuncSetAttribute(tfn_kernel, cudaFuncAttributeMaxDynamicSharedMemorySize, SM_TOTAL);
    Scratch* gs = nullptr;
    cudaGetSymbolAddress((void**)&gs, g_scratch);
    cudaLaunchConfig_t cfg = {};
    cfg.gridDim = dim3(NB); cfg.blockDim = dim3(NT); cfg.dynamicSmemBytes = SM_TOTAL; cfg.stream = cudaStreamPerThread;
    cudaLaunchAttribute at[1];
    at[0].id = cudaLaunchAttributeCooperative; at[0].val.cooperative = 1;
    cfg.attrs = at; cfg.numAttrs = 1;
    cudaLaunchKernelEx(&cfg, tfn_kernel, (const unsigned char*)d_in[0], (const int4*)d_in[1], (const int4*)d_in[2],
                       (const uint4*)d_in[3], (const uint4*)d_in[4], (const uint16_t*)d_in[5], (const uint16_t*)d_in[6],
                       (const uint4*)d_in[7], (uint32_t*)d_out, gs);
}
```

```cpp
#include <cuda_runtime.h>
#include <cuda_bf16.h>
#include <stdint.h>

namespace {

constexpr int NN = 10000;
constexpr int NE = 320000;
constexpr int NB = 132;
constexpr int NW = 20;
constexpr int NT = NW * 32;
constexpr int CW = NW - 1;
#define PWARP 10
constexpr int PW = PWARP;
constexpr int NPB = 76;
constexpr int CELL = 48;
constexpr int RCH = 2880;
constexpr int CAP = 19;
constexpr int DS = 4;
constexpr int STEPB = 160;
constexpr int NE4 = NE / 4;
constexpr int NPIECE = NB * 8;
constexpr int KB = 320, KN = 32 * KB;
constexpr uint32_t F_PAD = 0x80000000u;
constexpr uint32_t F_WRAP = 1;

constexpr int SLOTB = NW * 2048;
constexpr int SM_RING = 0;
constexpr int SM_META = SM_RING + DS * SLOTB;
constexpr int SM_AZ = SM_META + NW * CAP * STEPB;
constexpr int SM_MISC = SM_AZ + 2048;
constexpr int SM_TOTAL = SM_MISC + 2048;
constexpr int SM_STAGE = SM_RING;
constexpr int SM_HIST = SM_RING + 25600;
constexpr int SM_POS = SM_RING;
constexpr int SM_SMALL = SM_HIST + 13056;
constexpr int SM_LIST = SM_RING + SLOTB;
constexpr int SM_ROUT = SM_RING + 2 * SLOTB;
constexpr int SM_RECS = SM_RING + 3 * SLOTB;
constexpr int SM_RAWY = SM_META;
constexpr int SM_RAWE = SM_RAWY + 608 * 32;
constexpr int SM_KEYS = SM_RAWE + 608 * 32;
static_assert(SM_TOTAL <= 232448 && SM_KEYS + NPIECE * 16 <= SM_AZ, "smem");
static_assert(SM_RECS + NB * CELL * 16 + 16 <= SM_AZ && SM_KEYS + NPIECE * 16 <= SM_RECS + NB * CELL * 16 && SM_SMALL + 1152 <= SLOTB && DS == 4, "smem");

struct Scratch {
    uint4 keys[NB * NPIECE];
    uint4 recs[NB * RCH];
    uint4 stash[NB * NW * 256];
    unsigned bar[2];
    unsigned long long t0;
};
__device__ Scratch g_scratch;
#define TSTAMP(i)
#define TSTAMPC(i)
#define WSTAMP(i)
#define ESTAMP(i)

__device__ __forceinline__ void mma16816(float* d, uint32_t a0, uint32_t a1, uint32_t a2, uint32_t a3, uint32_t b0, uint32_t b1) {
    asm("mma.sync.aligned.m16n8k16.row.col.f32.bf16.bf16.f32 {%0,%1,%2,%3}, {%4,%5,%6,%7}, {%8,%9}, {%0,%1,%2,%3};"
        : "+f"(d[0]), "+f"(d[1]), "+f"(d[2]), "+f"(d[3]) : "r"(a0), "r"(a1), "r"(a2), "r"(a3), "r"(b0), "r"(b1));
}
__device__ __forceinline__ void mma1688z(float* d, uint32_t a0, uint32_t a1, uint32_t b0) {
    asm("mma.sync.aligned.m16n8k8.row.col.f32.bf16.bf16.f32 {%0,%1,%2,%3}, {%4,%5}, {%6}, {%7,%7,%7,%7};"
        : "=f"(d[0]), "=f"(d[1]), "=f"(d[2]), "=f"(d[3]) : "r"(a0), "r"(a1), "r"(b0), "f"(0.f));
}
__device__ __forceinline__ uint32_t pack2(float lo, float hi) {
    uint32_t r; asm("cvt.rn.bf16x2.f32 %0, %1, %2;" : "=r"(r) : "f"(hi), "f"(lo)); return r;
}
__device__ __forceinline__ float silu_h(float h) {
    float t; asm("tanh.approx.f32 %0, %1;" : "=f"(t) : "f"(h)); return fmaf(h, t, h);
}
__device__ __forceinline__ uint32_t mul_lo(uint32_t v, uint32_t r) {
    __nv_bfloat162 a = *(__nv_bfloat162*)&v, b = *(__nv_bfloat162*)&r; __nv_bfloat162 c = __hmul2(a, __low2bfloat162(b)); return *(uint32_t*)&c;
}
__device__ __forceinline__ uint32_t mul_hi(uint32_t v, uint32_t r) {
    __nv_bfloat162 a = *(__nv_bfloat162*)&v, b = *(__nv_bfloat162*)&r; __nv_bfloat162 c = __hmul2(a, __high2bfloat162(b)); return *(uint32_t*)&c;
}
__device__ __forceinline__ uint2 lds64(uint32_t a) {
    uint2 r; asm volatile("ld.shared.v2.u32 {%0,%1}, [%2];" : "=r"(r.x), "=r"(r.y) : "r"(a)); return r;
}
__device__ __forceinline__ uint4 lds128(uint32_t a) {
    uint4 r; asm volatile("ld.shared.v4.u32 {%0,%1,%2,%3}, [%4];" : "=r"(r.x), "=r"(r.y), "=r"(r.z), "=r"(r.w) : "r"(a) : "memory"); return r;
}
__device__ __forceinline__ void bar_sync(int id, int n) { asm volatile("bar.sync %0, %1;" :: "r"(id), "r"(n) : "memory"); }
__device__ __forceinline__ void bar_arrive(int id, int n) { asm volatile("bar.arrive %0, %1;" :: "r"(id), "r"(n) : "memory"); }
__device__ __forceinline__ void mbar_wait(uint32_t bar, uint32_t ph) {
    uint32_t done; int spins = 0;
    do {
        asm volatile("{.reg .pred p; mbarrier.try_wait.parity.shared.b64 p, [%1], %2; selp.u32 %0,1,0,p;}" : "=r"(done) : "r"(bar), "r"(ph) : "memory");
    } while (!done && ++spins < (1 << 22));
}
__device__ __forceinline__ unsigned gbar_read(const unsigned* ctr) {
    unsigned v; asm volatile("ld.relaxed.gpu.global.u32 %0, [%1];" : "=r"(v) : "l"(ctr) : "memory");
    return v;
}
__device__ __forceinline__ void gbar_arrive(unsigned* ctr) {
    asm volatile("red.add.release.gpu.global.u32 [%0], 1;" :: "l"(ctr) : "memory");
}
__device__ __forceinline__ bool gbar_wait(const unsigned* ctr, unsigned target) {
    unsigned v; int spins = 0;
    while (true) {
        asm volatile("ld.acquire.gpu.global.u32 %0, [%1];" : "=r"(v) : "l"(ctr) : "memory");
        if ((int)(v - target) >= 0 || ++spins > (1 << 22)) break;
    }
    return (int)(v - target) >= 0;
}
__device__ __forceinline__ int chunk_start4(int c) { return (c * NE4) / NB; }
__device__ __forceinline__ float bf2f(uint32_t h) { return __uint_as_float(h << 16); }

__device__ __noinline__ void slow_path(unsigned char* smem, int n0, int nn, const uint16_t* x, const int* src, const int* dst,
                                       const uint16_t* Y, const uint16_t* ef, const uint16_t* w_rad, const uint16_t* cg,
                                       const uint16_t* w_mix, __nv_bfloat16* out) {
    float* agg = (float*)smem;
    const int tid = threadIdx.x, lane = tid & 31, w = tid >> 5;
    bar_sync(1, NT);
    for (int i = tid; i < NPB * 512; i += NT) agg[i] = 0.f;
    bar_sync(1, NT);
    for (int e0 = w * 32; e0 < NE; e0 += NT) {
        int dl = dst[e0 + lane] - n0;
        unsigned m = __ballot_sync(0xffffffff, dl >= 0 && dl < nn);
        while (m) {
            int l = __ffs(m) - 1; m &= m - 1;
            int e = e0 + l, d = __shfl_sync(0xffffffff, dl, l), s = src[e];
            float T[16];
            for (int i = 0; i < 4; i++) for (int o = 0; o < 4; o++) {
                float a = 0.f;
                for (int f = 0; f < 4; f++) a += bf2f(Y[e * 4 + f]) * bf2f(cg[i * 16 + f * 4 + o]);
                T[i * 4 + o] = a;
            }
            for (int k = 0; k < 4; k++) {
                int c = lane + 32 * k;
                float z = 0.f;
                for (int j = 0; j < 4; j++) z += bf2f(ef[e * 4 + j]) * bf2f(w_rad[j * 128 + c]);
                float R = z / (1.f + __expf(-z));
                for (int o = 0; o < 4; o++) {
                    float a = 0.f;
                    for (int i = 0; i < 4; i++) a += bf2f(x[(size_t)s * 512 + c * 4 + i]) * T[i * 4 + o];
                    atomicAdd(&agg[d * 512 + c * 4 + o], R * a);
                }
            }
        }
    }
    bar_sync(1, NT);
    for (int i = tid; i < nn * 512; i += NT) {
        int n = i >> 9, d = (i >> 2) & 127, o = i & 3;
        float a = 0.f;
        for (int c = 0; c < 128; c++) a += agg[n * 512 + c * 4 + o] * bf2f(w_mix[c * 128 + d]);
        out[(size_t)(n0 + n) * 512 + (i & 511)] = __float2bfloat16(a);
    }
}

#define PACE 22750
#define YDELAY 300
#define POFF 4000
#define PSLEEP 32
#define RLEN 99
#define FDT 400
#define FOFF 1800
#define FSTAG 0
#define RELK 12
#define ILV 0
#define SPINS 40
#define ONEBAR 0
#define LEAD 0
#define FAN 16
#define FANC 2
#define TDEL 100
#define PTOL0 300
#define PTOL 900
__global__ void __launch_bounds__(NT, 1)
tfn_kernel(const unsigned char* __restrict__ x, const int4* __restrict__ src4, const int4* __restrict__ dst4,
           const uint4* __restrict__ Y, const uint4* __restrict__ ef, const uint16_t* __restrict__ w_rad,
           const uint16_t* __restrict__ cg, const uint4* __restrict__ w_mix, uint32_t* __restrict__ out, Scratch* __restrict__ gs) {
    extern __shared__ __align__(1024) unsigned char smem[];
    const uint32_t sb = (uint32_t)__cvta_generic_to_shared(smem);
    const int b = blockIdx.x, tid = threadIdx.x, lane = tid & 31, g = lane >> 2, t = lane & 3;
    const int w = __shfl_sync(0xffffffff, tid >> 5, 0);
    uint32_t* stage = (uint32_t*)(smem + SM_STAGE);
    uint32_t* hist = (uint32_t*)(smem + SM_HIST);
    uint32_t* cnt = (uint32_t*)(smem + SM_MISC);
    uint32_t* deg = cnt + 136;
    uint32_t* order = deg + 104;
    uint32_t* cnt2 = order + 80;
    volatile uint32_t* flag = cnt2 + 136;
    const uint32_t mbarK = sb + SM_MISC + 1920, mbarR = mbarK + 8, mbarW = mbarK + 16;
    const int n0 = b * NPB, nn = min(NPB, NN - n0);
    TSTAMP(0);

    const int c0 = chunk_start4(b), c1 = chunk_start4(b + 1);
    const bool has4 = c0 + tid < c1;
    int4 d4 = make_int4(0, 0, 0, 0), s4 = d4;
    if (has4) { d4 = __ldg(dst4 + c0 + tid); s4 = __ldg(src4 + c0 + tid); }
    unsigned tgt = 0;
    if (tid == NT - 1) {
        tgt = gbar_read(&gs->bar[0]);
        asm volatile("mbarrier.init.shared.b64 [%0], 1;" :: "r"(mbarK));
        asm volatile("mbarrier.init.shared.b64 [%0], 1;" :: "r"(mbarR));
        asm volatile("mbarrier.init.shared.b64 [%0], 512;" :: "r"(mbarW));
        asm volatile("fence.mbarrier_init.release.cluster;" ::: "memory");
        flag[0] = 0; flag[12] = 0; flag[13] = 0; flag[15] = 0;
    }
    if (w == CW) {
        asm volatile("cp.async.cg.shared.global [%0], [%1], 16;" :: "r"(sb + SM_SMALL + lane * 16), "l"(w_rad + lane * 8) : "memory");
        asm volatile("cp.async.cg.shared.global [%0], [%1], 16;" :: "r"(sb + SM_SMALL + 512 + lane * 16), "l"(w_rad + 256 + lane * 8) : "memory");
        if (lane < 8) asm volatile("cp.async.cg.shared.global [%0], [%1], 16;" :: "r"(sb + SM_SMALL + 1024 + lane * 16), "l"(cg + lane * 8) : "memory");
    }
    ((uint4*)hist)[tid] = make_uint4(0, 0, 0, 0);
    {
        const uint32_t dk = (80 + b % 22) * KN + (b & 31) * KB;
#pragma unroll
        for (int j = 0; j < 3; j++) if (tid + j * NT < NB * CELL / 4) ((uint4*)stage)[tid + j * NT] = make_uint4(dk, dk, dk, dk);
    }
    if (tid < 136) cnt[tid] = 0;
    if (tid == 0) { *(uint4*)(smem + SM_MISC + 1824 + 32) = make_uint4(0, 0, 0, 0); *(uint4*)(smem + SM_RECS + NB * CELL * 16) = make_uint4(0, 0, 0, 0); }
    if (tid < 80) { deg[tid] = 127 - tid; order[tid] = tid; }
    __syncthreads();
    TSTAMP(9);
    if (tid == 64) {
        if (YDELAY) __nanosleep(YDELAY);
        asm volatile("mbarrier.arrive.expect_tx.shared.b64 _, [%0], %1;" :: "r"(mbarR), "r"((c1 - c0) * 64) : "memory");
        asm volatile("cp.async.bulk.shared::cluster.global.mbarrier::complete_tx::bytes [%0], [%1], %2, [%3];"
                     :: "r"(sb + SM_RAWY), "l"(Y + 2 * c0), "r"((c1 - c0) * 32), "r"(mbarR) : "memory");
        asm volatile("cp.async.bulk.shared::cluster.global.mbarrier::complete_tx::bytes [%0], [%1], %2, [%3];"
                     :: "r"(sb + SM_RAWE), "l"(ef + 2 * c0), "r"((c1 - c0) * 32), "r"(mbarR) : "memory");
    }

    uint32_t bin[4] = {0, 0, 0, 0}, slot[4] = {0, 0, 0, 0};
    if (has4) {
        const uint32_t dd[4] = {(uint32_t)d4.x, (uint32_t)d4.y, (uint32_t)d4.z, (uint32_t)d4.w}, ss[4] = {(uint32_t)s4.x, (uint32_t)s4.y, (uint32_t)s4.z, (uint32_t)s4.w};
#pragma unroll
        for (int k = 0; k < 4; k++) { bin[k] = dd[k] / NPB; slot[k] = atomicAdd(&cnt[bin[k]], 1); }
#pragma unroll
        for (int k = 0; k < 4; k++) stage[bin[k] * CELL + min(slot[k], CELL - 1)] = (dd[k] - bin[k] * NPB) * KN + ss[k];
    }
    if (w == CW) {
        if (tid == NT - 1) { tgt = tgt / NB + 1; flag[14] = (tgt & 1) << 31; tgt *= NB; }
        asm volatile("cp.async.wait_all;" ::: "memory");
    }
    bar_sync(1, NT);
    TSTAMP(1);
    const uint32_t tag = flag[14];
#pragma unroll
    for (int j = 0; j < 2; j++) {
        const int i = tid + j * NT;
        if (i < NPIECE) {
            const uint2 sa = *(const uint2*)(stage + i * 6), sc = *(const uint2*)(stage + i * 6 + 2);
            uint2 se = *(const uint2*)(stage + i * 6 + 4);
            const uint32_t cf = cnt[i >> 3], cn = min(cf, 63u);
            if ((i & 7) == 7) {
                const uint32_t al = cf > CELL - 8 ? 7 : 0;
                uint32_t o;
                asm volatile("atom.shared.add.u32 %0, [%1], %2;" : "=r"(o) : "r"(sb + SM_MISC + 1824 + 60), "r"(cf + al) : "memory");
                se.y = (o + al) & ~al;
                cnt2[i >> 3] = se.y;
            }
            asm volatile("{.reg .b64 lo, hi; mov.b64 lo, {%1,%2}; mov.b64 hi, {%3,%4}; st.relaxed.gpu.global.v2.b64 [%0], {lo, hi};}"
                         :: "l"(gs->keys + ((i >> 3) * NB + b) * 8 + ((i ^ b) & 7)),
                            "r"(sa.x | (se.x << 20)), "r"(sa.y | ((se.x >> 12) << 20) | ((cn & 7) << 28) | tag),
                            "r"(sc.x | (se.y << 20)), "r"(sc.y | ((se.y >> 12) << 20) | ((cn >> 3) << 28) | tag) : "memory");
        }
    }
    bar_sync(1, NT);
    if (tid == NT - 1) {
        TSTAMPC(10);
        asm volatile("red.add.relaxed.gpu.global.u32 [%0], 1;" :: "l"(&gs->bar[0]) : "memory");
        asm volatile("mbarrier.arrive.expect_tx.shared.b64 _, [%0], %1;" :: "r"(mbarK), "r"(NPIECE * 16) : "memory");
        gbar_wait(&gs->bar[0], tgt);
        TSTAMPC(13);
        asm volatile("fence.proxy.async.global;" ::: "memory");
        asm volatile("cp.async.bulk.shared::cluster.global.mbarrier::complete_tx::bytes [%0], [%1], %2, [%3];"
                 :: "r"(sb + SM_KEYS), "l"(gs->keys + b * NPIECE), "r"(NPIECE * 16), "r"(mbarK) : "memory");
    }
    __syncwarp();
    uint32_t at[4];
    {
        const int o = g & 3, f = 2 * (t & 1);
#pragma unroll
        for (int i = 0; i < 4; i++) {
            const uint16_t* cp = (const uint16_t*)(smem + SM_SMALL + 1024) + i * 16 + f * 4 + o;
            at[i] = (t >> 1) == (g >> 2) ? cp[0] | ((uint32_t)cp[4] << 16) : 0;
        }
    }

    const int q = lane >> 3, c = lane & 7;
    const uint32_t ring0 = sb + SM_RING + w * 2048;
    uint32_t wdst = ring0 + q * 128 + ((c + 2 * q) & 7) * 16;
    uint32_t rsrc = ring0 + t * 128 + ((g + 2 * t) & 7) * 16;
    uint32_t recl = sb + SM_META + w * (CAP * STEPB) + g * 16 + (t & 1) * 8, srcl = sb + SM_META + w * (CAP * STEPB) + 128 + q * 8;
    uint32_t flg = sb + SM_MISC + (136 + 104 + 80 + 136) * 4;
    asm volatile("" : "+r"(wdst), "+r"(rsrc), "+r"(recl), "+r"(srcl), "+r"(flg));
    uint32_t key[2][6], ha[2][6], rk[2][6], kidx[2], ka[2];
    int nk[2];
#pragma unroll
    for (int j = 0; j < 2; j++) {
        const int i0 = j ? 2 * 608 - 1 - tid : tid, i = min(i0, NPIECE - 1), r = i / NB, cc = i - r * NB;
        ka[j] = sb + SM_KEYS + (cc * 8 + ((r ^ cc) & 7)) * 16;
        kidx[j] = (cc * CELL + r * 6) << 17;
        nk[j] = i0 < NPIECE && w < CW ? -6 * r : -1000;
    }
    asm volatile("" : "+r"(at[0]), "+r"(at[1]), "+r"(at[2]), "+r"(at[3]), "+r"(ka[0]), "+r"(ka[1]), "+r"(kidx[0]), "+r"(kidx[1]), "+r"(nk[0]), "+r"(nk[1]));
    if (w == CW) {
        __syncwarp();
        bar_sync(7, NT);
        if (tid == NT - 1) {
            TSTAMPC(11);
            asm volatile("cp.async.bulk.global.shared::cta.bulk_group [%0], [%1], %2;"
                         :: "l"(gs->recs + b * RCH), "r"(sb + SM_ROUT), "r"(((flag[15] + 1) & ~1u) * 16) : "memory");
            asm volatile("cp.async.bulk.commit_group;" ::: "memory");
            mbar_wait(mbarK, 0);
            unsigned long long tbase;
            asm volatile("mov.u64 %0, %%globaltimer;" : "=l"(tbase));
            tbase += POFF;
            flag[1] = (uint32_t)tbase; flag[4] = (uint32_t)tbase; flag[5] = (uint32_t)(tbase >> 32);
            asm volatile("red.max.relaxed.gpu.global.u64 [%0], %1;" :: "l"(&gs->t0), "l"(tbase) : "memory");
            if (b < 128) asm volatile("cp.async.bulk.prefetch.L2.global [%0], 256;" :: "l"(w_mix + b * 16));
            asm volatile("cp.async.bulk.wait_group 0;" ::: "memory");
            TSTAMPC(14);
            asm volatile("red.add.relaxed.gpu.global.u32 [%0], 1;" :: "l"(&gs->bar[1]) : "memory");
            TSTAMPC(15);
        }
    } else {
        if (w < 8) {
            const uint32_t* wp = (const uint32_t*)(smem + SM_SMALL) + (t & 1) * 128 + 8 * w + g;
            const uint32_t wr0 = t < 2 ? wp[0] : 0, wr1 = t < 2 ? wp[64] : 0;
            *(uint2*)(smem + SM_AZ + (w >> 1) * 512 + lane * 16 + (w & 1) * 8) =
                make_uint2(pack2(0.5f * bf2f(wr0 & 0xFFFF), 0.5f * bf2f(wr1 & 0xFFFF)), pack2(0.5f * bf2f(wr0 >> 16), 0.5f * bf2f(wr1 >> 16)));
        }
        const bool sw = g & 1;
        uint32_t rp[4];
#pragma unroll
        for (int k = 0; k < 4; k++) rp[k] = cnt2[bin[k]] + slot[k];
        uint4* ro = (uint4*)(smem + SM_ROUT);
        uint4 *p0 = ro + (sw ? rp[2] : rp[0]), *p1 = ro + (sw ? rp[3] : rp[1]), *p2 = ro + (sw ? rp[0] : rp[2]), *p3 = ro + (sw ? rp[1] : rp[3]);
        const uint32_t ya = sb + SM_RAWY + tid * 32 + (sw ? 16 : 0);
        mbar_wait(mbarR, 0);
        TSTAMP(18);
        if (has4) {
            const uint4 y0 = lds128(ya), e0 = lds128(ya + (SM_RAWE - SM_RAWY)), y1 = lds128(ya ^ 16), e1 = lds128((ya ^ 16) + (SM_RAWE - SM_RAWY));
            *p0 = make_uint4(y0.x, e0.x, y0.y, e0.y); *p1 = make_uint4(y0.z, e0.z, y0.w, e0.w);
            *p2 = make_uint4(y1.x, e1.x, y1.y, e1.y); *p3 = make_uint4(y1.z, e1.z, y1.w, e1.w);
        }
        asm volatile("fence.proxy.async.shared::cta;" ::: "memory");
        bar_arrive(7, NT);
    }
    __syncwarp();
    TSTAMP(2);

    if (w < CW) {
        mbar_wait(mbarK, 0);
        TSTAMP(3);
        uint4 v[2] = {lds128(ka[0]), lds128(ka[1])};
#pragma unroll
        for (int j = 0; j < 2; j++) {
            int spins = 0;
            while ((int)((v[j].y ^ tag) | (v[j].w ^ tag)) < 0) {
                asm volatile("{.reg .b64 lo, hi; ld.relaxed.gpu.global.v2.b64 {lo, hi}, [%4]; mov.b64 {%0,%1}, lo; mov.b64 {%2,%3}, hi;}"
                             : "=r"(v[j].x), "=r"(v[j].y), "=r"(v[j].z), "=r"(v[j].w) : "l"((const unsigned char*)(gs->keys + b * NPIECE) + (ka[j] - sb - SM_KEYS)) : "memory");
                if (++spins > (1 << 20)) { *flag = 1; break; }
            }
            const uint32_t hc = ((v[j].y >> 28) & 7) | ((v[j].w >> 25) & 0x38);
            if (j == 1 && nk[j] == -42) {
                cnt[kidx[j] / (CELL << 17)] = hc | ((v[j].z >> 20) << 8);
                v[j].w |= ((80 * KN) >> 12) << 20;
            }
            if (hc > CELL - 1) *flag = 1;
            nk[j] += hc;
            if (nk[j] > 0) {
                key[j][0] = v[j].x & 0xFFFFF; key[j][1] = v[j].y & 0xFFFFF; key[j][2] = v[j].z & 0xFFFFF; key[j][3] = v[j].w & 0xFFFFF;
                key[j][4] = (v[j].x >> 20) | ((v[j].y >> 8) & 0xFF000); key[j][5] = (v[j].z >> 20) | ((v[j].w >> 8) & 0xFF000);
#pragma unroll
                for (int u = 0; u < 6; u++) {
                    ha[j][u] = __umulhi(key[j][u], 0xFFFFFFFFu / KB + 1);
                    rk[j][u] = atomicAdd(&hist[ha[j][u]], 1);
                    atomicAdd(&deg[ha[j][u] >> 5], 128);
                }
            }
        }
        bar_sync(9, NT - 32);
        TSTAMP(20);
#pragma unroll
        for (int j = 0; j < 2; j++) kidx[j] += ((cnt[kidx[j] / (CELL << 17)] >> 8) & 7) << 17;
        const int n = tid >> 3, sub = tid & 7;
        const uint32_t me = deg[n];
        int r = 0;
#pragma unroll
        for (int k = 0; k < 5; k++) { const uint2 dd = *(const uint2*)(deg + sub * 10 + 2 * k); r += (dd.x > me) + (dd.y > me); }
        r += __shfl_xor_sync(0xffffffff, r, 1); r += __shfl_xor_sync(0xffffffff, r, 2); r += __shfl_xor_sync(0xffffffff, r, 4);
        if (sub == 0) order[r] = n;
    }
    bar_sync(1, NT);
    TSTAMP(22);
    uint32_t len2;
    {
        const uint2 na = *(const uint2*)(order + 2 * w);
        uint2 nb = *(const uint2*)(order + 78 - 2 * w);
        const uint32_t ia0 = na.x * 32 + lane, ia1 = na.y * 32 + lane;
        const uint32_t ha0 = hist[ia0], ha1 = hist[ia1];
        uint32_t hb0 = hist[nb.y * 32 + lane], hb1 = hist[nb.x * 32 + lane];
        const int su = __reduce_add_sync(0xffffffff, (int)(ha0 - ha1) * (2 * lane - 31)), sv = __reduce_add_sync(0xffffffff, (int)(hb0 - hb1) * (2 * lane - 31));
        if ((su ^ sv) >= 0) {
            nb = make_uint2(nb.y, nb.x);
            const uint32_t tmp = hb0; hb0 = hb1; hb1 = tmp;
            *(uint2*)(order + 78 - 2 * w) = nb;
        }
        const uint32_t ib0 = nb.y * 32 + lane, ib1 = nb.x * 32 + lane;
        const uint32_t ca = ha0 + (ha1 << 16), cab = ca + hb0 + (hb1 << 16);
        uint32_t inc = cab;
#pragma unroll
        for (int o = 1; o < 32; o <<= 1)
            asm volatile("{.reg .pred p; .reg .u32 u; shfl.sync.up.b32 u|p, %0, %1, 0, 0xffffffff; @p add.u32 %0, %0, u;}" : "+r"(inc) : "r"(o));
        const uint32_t ea = inc - cab, eb = ea + ca, base = sb + SM_LIST + w * 2048;
        uint2* pos = (uint2*)(smem + SM_POS);
        pos[ia0] = make_uint2(base + (ea & 0xFFFF) * 8, na.x * (0u - 4 * KN));
        pos[ib0] = make_uint2(base + (eb & 0xFFFF) * 8, nb.y * (0u - 4 * KN) + 0x10000);
        pos[ia1] = make_uint2(base + 4 + (ea >> 16) * 8, na.y * (0u - 4 * KN));
        pos[ib1] = make_uint2(base + 4 + (eb >> 16) * 8, nb.x * (0u - 4 * KN) + 0x10000);
        if (max(inc & 0xFFFF, inc >> 16) > 4 * CAP) *flag = 1;
        len2 = __shfl_sync(0xffffffff, inc, 31);
    }
    uint32_t ci = cnt[min(w + NW * lane, NB)];
    ci = ((((w + NW * lane) * (RCH / 8) + (ci >> 11)) << 8) | (ci & 0xFF)) + ((ci >> 8) & 7);
    if (w == CW) {
        bar_arrive(9, NT);
        if (tid == NT - 1) {
            uint32_t v1, g0; int spins = 0;
            do {
                asm volatile("{.reg .u32 a, b; ld.acquire.gpu.global.v4.u32 {a,%0,%1,b}, [%2];}" : "=r"(v1), "=r"(g0) : "l"(gs->bar) : "memory");
            } while ((int)(v1 - tgt) < 0 && ++spins < (1 << 22));
            if ((int)(v1 - tgt) < 0) *flag = 1;
            if (g0 - flag[1] < 30000) flag[1] = g0;
            TSTAMPC(17);
        }
        __syncwarp();
    } else {
        bar_sync(9, NT);
        TSTAMP(21);
        const uint32_t over = *flag;
#pragma unroll
        for (int j = 0; j < 2; j++) {
            if (nk[j] > 0) {
                uint2 h[6];
#pragma unroll
                for (int u = 0; u < 6; u++) h[u] = lds64(sb + SM_POS + ha[j][u] * 8);
                if (over) nk[j] = 0;
#pragma unroll
                for (int u = 0; u < 6; u++)
                    asm volatile("{.reg .pred p; setp.gt.s32 p, %2, %3; @p st.shared.u32 [%0], %1;}"
                                 :: "r"(h[u].x + rk[j][u] * 8), "r"(key[j][u] * 4 + h[u].y + (kidx[j] + (u << 17))), "r"(nk[j]), "r"(u) : "memory");
            }
        }
    }
    bar_sync(1, NT);
    TSTAMP(4);
    if (*flag) {
        slow_path(smem, n0, nn, (const uint16_t*)x, (const int*)src4, (const int*)dst4, (const uint16_t*)Y, (const uint16_t*)ef, w_rad, cg,
                  (const uint16_t*)w_mix, (__nv_bfloat16*)out);
        return;
    }
    {
        const uint4* gp = gs->recs + lane;
        const uint32_t sp = sb + SM_RECS + (w * CELL + lane) * 16;
#pragma unroll
        for (int j = 0; j < 7; j++) {
            const uint32_t cj = __shfl_sync(0xffffffff, ci, j);
            asm volatile("{.reg .pred p; setp.lt.u32 p, %2, %3; @p cp.async.cg.shared.global [%0], [%1], 16;}"
                         :: "r"(sp + j * (NW * CELL * 16)), "l"(gp + (size_t)(cj >> 8) * 8), "r"(lane), "r"(cj & 0xFF) : "memory");
        }
        for (uint32_t m = __ballot_sync(0xffffffff, (ci & 0xFF) > 32); m; m &= m - 1) {
            const int j = __ffs(m) - 1;
            const uint32_t cj = __shfl_sync(0xffffffff, ci, j);
            if (lane + 32 < (cj & 0xFF))
                asm volatile("cp.async.cg.shared.global [%0], [%1], 16;" :: "r"(sp + j * (NW * CELL * 16) + 512), "l"(gp + (size_t)(cj >> 8) * 8 + 32) : "memory");
        }
        asm volatile("cp.async.commit_group;" ::: "memory");
    }
    const int S = __shfl_sync(0xffffffff, max((int)(max(len2 & 0xFFFF, len2 >> 16) + 3) >> 2, DS + 1), 0);
    const int mylen = (lane & 1) ? len2 >> 16 : len2 & 0xFFFF;
    constexpr int NRAW = (CAP + 3) / 4;
    uint32_t bits0 = 0, raw[NRAW];
    unsigned char* meta = smem + SM_META + w * (CAP * STEPB);
#pragma unroll
    for (int k = 0; k < NRAW; k++) raw[k] = mylen ? ((uint32_t*)(smem + SM_LIST + w * 2048))[min(k * 16 + (lane >> 1), mylen - 1) * 2 + (lane & 1)] : 4 * n0;
    const uint32_t sv0 = raw[0] & 0xFFFF;
    const unsigned char* pbase = x + c * 16;
    auto cpa2 = [&](uint32_t dstp, uint32_t sv) {
        asm volatile("cp.async.cg.shared.global [%0], [%1], 16; cp.async.cg.shared.global [%0+1024], [%1+128], 16;"
                     :: "r"(dstp), "l"(pbase + (size_t)sv * 256) : "memory");
    };
    auto cpa2p = [&](uint32_t dstp, uint32_t sv) {
        asm volatile("{.reg .pred p; setp.ge.s32 p, %2, 0; @p cp.async.cg.shared.global [%0], [%1], 16; @p cp.async.cg.shared.global [%0+1024], [%1+128], 16;}"
                     :: "r"(dstp), "l"(pbase + (size_t)sv * 256), "r"(sv) : "memory");
    };
    auto wait_until = [&](uint32_t tt) {
        asm volatile("{.reg .pred p; .reg .u32 d;\n"
                     "PACE_LOOP: mov.u32 d, %%globaltimer_lo; sub.u32 d, %0, d; setp.lt.u32 p, d, 32768; @p nanosleep.u32 %1; @p bra.uni PACE_LOOP;}"
                     :: "r"(tt), "n"(PSLEEP) : "memory");
    };
    const uint32_t tfill = flag[1] - FOFF + w * FSTAG;
    auto fill = [&](int i) {
        if (FDT) wait_until(tfill + i * FDT);
        cpa2(wdst + i * SLOTB, __shfl_sync(0xffffffff, sv0, 8 * i + 2 * q)); cpa2(wdst + i * SLOTB + 512, __shfl_sync(0xffffffff, sv0, 8 * i + 2 * q + 1));
        asm volatile("cp.async.commit_group;" ::: "memory");
    };
    fill(0);
    TSTAMP(5);
    auto relay = [&]() {
        uint32_t g0, g1, b0, b1;
        asm volatile("ld.volatile.shared.v2.u32 {%0,%1}, [%4+40]; ld.volatile.shared.v2.u32 {%2,%3}, [%4+16];"
                     : "=r"(g0), "=r"(g1), "=r"(b0), "=r"(b1) : "r"(flg) : "memory");
        const unsigned long long dg = (((unsigned long long)g1 << 32) | g0) - (((unsigned long long)b1 << 32) | b0);
        asm volatile("{.reg .pred p, q; setp.eq.u32 p, %1, 0; setp.lt.u64 q, %2, 30000; @q st.shared.u32 [%3+4], %4;\n"
                     "@p cp.async.cg.shared.global [%3+32], [%0], 16;}"
                     :: "l"(gs->bar), "r"(lane), "l"(dg), "r"(flg), "r"(g0) : "memory");
    };
    uint32_t ra[NRAW];
#pragma unroll
    for (int k = 0; k < NRAW; k++) {
        const uint32_t m = (__ballot_sync(0xffffffff, raw[k] & 0x10000) >> g) & 0x01010101u;
        bits0 |= ((m * 0x10204080u) >> 28) << (4 * k);
        ra[k] = sb + SM_RECS + (k * 16 + (lane >> 1) < mylen ? raw[k] >> 17 : NB * CELL) * 16;
    }
    if (t < 2) bits0 = ~bits0;
    asm volatile("" : "+r"(bits0), "+r"(ra[0]), "+r"(ra[1]), "+r"(ra[2]), "+r"(ra[3]), "+r"(ra[4]));
    fill(1);
    asm volatile("cp.async.wait_group 2;" ::: "memory");
    bar_sync(1, NT);
    TSTAMP(19);
    {
        uint4 rv[NRAW];
#pragma unroll
        for (int k = 0; k < NRAW - 1; k++) rv[k] = lds128(ra[k]);
        if ((NRAW - 1) * 4 < S) rv[NRAW - 1] = lds128(ra[NRAW - 1]);
        fill(2);
        bar_sync(1, NT);
        TSTAMP(12);
        unsigned char* mr = meta + (q - 1) * STEPB + c * 16;
        unsigned char* ms = meta + (q - DS - 1) * STEPB + 128 + c * 4;
#pragma unroll
        for (int k = 0; k < NRAW; k++) {
            if (k == 0) {
                *(uint4*)(mr + (q == 0 ? S * STEPB : 0)) = rv[k];
                *(uint32_t*)(ms + S * STEPB) = sv0 + F_WRAP + ((lane >> 1) >= mylen ? F_PAD : 0);
            } else if (k * 4 + q < S) {
                *(uint4*)(mr + k * 4 * STEPB) = rv[k];
                *(uint32_t*)(ms + k * 4 * STEPB + (k == 1 && q == 0 ? S * STEPB : 0)) = (raw[k] & 0xFFFF) + (k * 16 + (lane >> 1) >= mylen ? F_PAD : 0);
            }
        }
    }
    __syncwarp();
    const uint32_t tphase = PACE / 4;
    uint32_t dreg;
    {
        const int ls = lane >= S ? min(lane - S, S - 1) : lane, st = ls == 0 ? S - 1 : ls - 1;
        const uint4 u0 = *(const uint4*)(meta + st * STEPB + 128), u1 = *(const uint4*)(meta + st * STEPB + 144);
        int pos = (u0.x + u0.y + u0.z + u0.w + u1.x + u1.y + u1.z + u1.w) << 1 >> 6;
        pos += ((u0.x & F_WRAP) ? NN : 0) + (lane >= S ? NN : 0) - NN * (2 * DS + 1) / 32;
        dreg = pos * (int)tphase / NN;
    }
    fill(3);
    TSTAMP(6);

    uint32_t* stash = (uint32_t*)(gs->stash + (b * NW + w) * 256) + lane;
    float acc[4][4];
#pragma unroll
    for (int i = 0; i < 16; i++) acc[i / 4][i % 4] = 0.f;
    uint4 az = *(const uint4*)(smem + SM_AZ + lane * 16);
    uint32_t dcur = dreg, dl = 0, now = flag[1], tcur = 0;
    uint32_t mp = 0, smask = 1, didx = 2;
    uint32_t mend = S * STEPB;
    uint2 r = lds64(mend - STEPB + recl), s0 = lds64(mend - STEPB + srcl);
    auto step = [&](const uint32_t off, const int mode, const bool pc = true) {
        if (mode == 0 && pc) { unsigned long long n64; asm volatile("mov.u64 %0, %%globaltimer;" : "=l"(n64)); now = (uint32_t)n64; }
        const uint2 rc = r, sc = s0;
        if (mode != 4) r = lds64(mp + recl);
        if (mode == 0) s0 = lds64(mp + srcl);
        asm volatile("cp.async.wait_group %0;" :: "n"(DS - 1) : "memory");
        const uint4 xa = lds128(rsrc + off), xb = lds128(rsrc + off + 512), xc = lds128(rsrc + off + 1024), xd = lds128(rsrc + off + 1536);
        if (mode == 0) {
            if (pc) { dl = __shfl_sync(0xffffffff, dcur, didx); didx += 2; }
            cpa2p(wdst + off, sc.x); cpa2p(wdst + off + 512, sc.y);
        }
        if (mode == 1 && w < 16) {
#pragma unroll
            for (int j = 0; j < 4; j++) {
                const int kk = 4 * j + q, ch = 16 * (w & 7) + 2 * (kk & 7) + (kk >> 3);
                asm volatile("cp.async.cg.shared.global [%0], [%1], 16;" :: "r"(ring0 + kk * 128 + ((c ^ (kk & 7)) << 4)), "l"(w_mix + ch * 16 + (w >> 3) * 8 + c) : "memory");
            }
            asm volatile("cp.async.mbarrier.arrive.noinc.shared.b64 [%0];" :: "r"(mbarW) : "memory");
        }
        if (mode == 2 || mode == 3) {
#pragma unroll
            for (int j = 0; j < 4; j += mode - 1)
                asm volatile("cp.async.cg.shared.global [%0], [%1], 16;" :: "r"(ring0 + off + j * 512 + lane * 16), "l"(stash + (mode - 2) * 512 + j * 128 + lane * 3) : "memory");
        }
        if (mode < 4) asm volatile("cp.async.commit_group;" ::: "memory");
        float z[4], y[4], t1[4], t2[4];
        mma1688z(z, az.x, az.y, rc.y);
        mma1688z(y, az.z, az.w, rc.y);
        uint32_t bt;
        asm("{.reg .pred p; .reg .b32 m; and.b32 m, %2, %3; setp.ne.u32 p, m, 0; selp.b32 %0, %1, 0, p;}" : "=r"(bt) : "r"(rc.x), "r"(bits0), "r"(smask));
        mma1688z(t1, at[0], at[1], bt);
        mma1688z(t2, at[2], at[3], bt);
        const uint32_t T0 = pack2(t1[0], t1[2]), T1 = pack2(t2[0], t2[2]), T2 = pack2(t1[1], t1[3]), T3 = pack2(t2[1], t2[3]);
        uint32_t R[8];
#pragma unroll
        for (int i = 0; i < 4; i++) { R[i] = __float_as_uint(silu_h(z[i])); R[4 + i] = __float_as_uint(silu_h(y[i])); }
        mma16816(acc[0], mul_hi(xa.x, R[0]), mul_hi(xa.z, R[2]), mul_hi(xa.y, R[0]), mul_hi(xa.w, R[2]), T0, T1);
        mma16816(acc[1], mul_hi(xb.x, R[1]), mul_hi(xb.z, R[3]), mul_hi(xb.y, R[1]), mul_hi(xb.w, R[3]), T2, T3);
        mma16816(acc[2], mul_hi(xc.x, R[4]), mul_hi(xc.z, R[6]), mul_hi(xc.y, R[4]), mul_hi(xc.w, R[6]), T0, T1);
        mma16816(acc[3], mul_hi(xd.x, R[5]), mul_hi(xd.z, R[7]), mul_hi(xd.y, R[5]), mul_hi(xd.w, R[7]), T2, T3);
        mp += STEPB; smask <<= 1;
    };
    auto putacc = [&](uint32_t* p) {
#pragma unroll
        for (int i = 0; i < 16; i++) acc[i / 4][i % 4] *= 1.0028f;
        p[0] = pack2(acc[0][0], acc[0][1]); p[32] = pack2(acc[0][2], acc[0][3]); p[64] = pack2(acc[2][0], acc[2][1]); p[96] = pack2(acc[2][2], acc[2][3]);
        p[256] = pack2(acc[1][0], acc[1][1]); p[288] = pack2(acc[1][2], acc[1][3]); p[320] = pack2(acc[3][0], acc[3][1]); p[352] = pack2(acc[3][2], acc[3][3]);
    };
    int ph = 0;
    auto phase_end = [&](const int k) {
        az = lds128(sb + SM_AZ + (ph + 1) * 512 + lane * 16);
        putacc(stash + ph * ph * 128);
#pragma unroll
        for (int i = 0; i < 16; i++) acc[i / 4][i % 4] = 0.f;
        pbase += 256; mp = 0; smask = 1; ph++;
        dcur += tphase; didx = 1 + (k & 1);
        if (ph == 3) {
            mend -= DS * STEPB;
            if (FAN) dcur += (int)(dcur - __shfl_sync(0xffffffff, dcur, 0)) * (((w >> 2) - FANC) * FAN) >> 8;
        }
        WSTAMP(ph - 1);
    };
    uint32_t t0 = now;
    auto report = [&](uint32_t cand) {
        uint32_t b0, b1;
        asm volatile("ld.volatile.shared.v2.u32 {%0,%1}, [%2+16];" : "=r"(b0), "=r"(b1) : "r"(flg) : "memory");
        asm volatile("{.reg .pred p; setp.eq.u32 p, %2, 0; @p red.max.relaxed.gpu.global.u64 [%0], %1;}"
                     :: "l"(&gs->t0), "l"((((unsigned long long)b1 << 32) | b0) + (cand - b0)), "r"(lane) : "memory");
    };
    const bool reporter = w == PW && max(len2 & 0xFFFF, len2 >> 16) <= RLEN;
    if (reporter) {
        asm volatile("mov.u32 %0, %%globaltimer_lo;" : "=r"(now));
        now += PTOL - PTOL0;
    }
    const uint32_t bias = w == 0 ? 1u << 20 : 0;
    if (w == 0) relay();
    dcur += bias;
    auto body = [&](const int k) -> bool {
        if (k == 2) asm volatile("ld.volatile.shared.u32 %0, [%1+4];" : "=r"(t0) : "r"(flg));
        const bool pc = k & 1;
        step(k * SLOTB, 0, pc);
        if (!pc) {
            if (mp == mend) phase_end(k);
        } else if (mp == mend || now < dl) {
            if (mp == mend) {
                if (k == 3 && ph == 3) return true;
                phase_end(k);
            }
            if (w == 0) { dl -= 1u << 20; relay(); }
            wait_until(dl);
        }
        return false;
    };
    wait_until(__shfl_sync(0xffffffff, dreg, 0) + t0);
    while (true) {
        if (reporter) {
            const uint32_t cand = now - dl + tcur - PTOL;
            if ((int)(cand - t0) > 0) report(cand);
        }
        dcur += t0 - tcur; tcur = t0;
        body(0); body(1); body(2);
        if (body(3)) break;
    }
    __syncwarp();
    step(0, 1);
    if (TDEL) { uint32_t tn; asm volatile("mov.u32 %0, %%globaltimer_lo;" : "=r"(tn)); wait_until(tn + (w >> 2) * TDEL); }
    step(SLOTB, 2); step(2 * SLOTB, 3); step(3 * SLOTB, 4);
    WSTAMP(3); ESTAMP(0);

    {
        putacc((uint32_t*)(smem + SM_RING + 2 * SLOTB + w * 2048 + 512) + lane);
        const int wg = w >> 2, w4 = w & 3;
        int nd[8];
#pragma unroll
        for (int j = 0; j < 8; j++) { const int l = wg * 8 + j; nd[j] = order[(t >> 1) ? 79 - l : l]; asm volatile("" : "+r"(nd[j])); }
        const bool odd = t & 1;
        uint2* ob = (uint2*)out + (size_t)n0 * 128 + w4 * 16 + g + (odd ? 8 : 0);
        asm volatile("cp.async.wait_all;" ::: "memory");
        mbar_wait(mbarW, 0);
        asm volatile("fence.proxy.async.shared::cta;" ::: "memory");
        ESTAMP(1);
        if (!ONEBAR) bar_sync(2 + wg, 128);
        uint32_t ticket = 0;
        if ((tid & 127) == 0) {
            asm volatile("atom.shared.add.u32 %0, [%1+48], 1;" : "=r"(ticket) : "r"(flg) : "memory");
            int spins = 0;
            while (flag[13] + LEAD < ticket && ++spins < (1 << 16)) { if (SPINS) __nanosleep(SPINS); }
        }
        bar_sync(2 + wg, 128);
        const uint64_t descA0 = (uint64_t)(((sb + SM_RING) & 0x3FFFF) >> 4) | ((uint64_t)1 << 16) | ((uint64_t)(1024 >> 4) << 32) | ((uint64_t)1 << 62);
        const uint64_t descB0 = (uint64_t)(((sb + SM_RING + SLOTB + wg * 8192) & 0x3FFFF) >> 4) | ((uint64_t)(128 >> 4) << 16) | ((uint64_t)(1024 >> 4) << 32);
        auto release = [&]() { asm volatile("{.reg .pred p; setp.eq.u32 p, %1, 0; @p st.volatile.shared.u32 [%0+52], %2;}" :: "r"(flg), "r"(tid & 127), "r"(ticket + 1) : "memory"); };
        float d[2][32];
        asm volatile("wgmma.fence.sync.aligned;" ::: "memory");
        ESTAMP(2);
#pragma unroll
        for (int i1 = 0; i1 < 2; i1++) {
#pragma unroll
            for (int i0 = 0; i0 < 8; i0++) {
                const int mt = ILV ? i0 & 1 : i1, ks = ILV ? i1 * 4 + (i0 >> 1) : i0;
                if (i1 * 8 + i0 == RELK) release();
                const uint64_t da = descA0 + (uint64_t)((ks * 2048 + mt * 16384) >> 4), db = descB0 + (uint64_t)(((ks & 3) * 256 + (ks >> 2) * SLOTB) >> 4);
                asm volatile("{.reg .pred p; setp.ne.b32 p, %34, 0;\n"
                    "wgmma.mma_async.sync.aligned.m64n64k16.f32.bf16.bf16 "
                    "{%0,%1,%2,%3,%4,%5,%6,%7,%8,%9,%10,%11,%12,%13,%14,%15,%16,%17,%18,%19,%20,%21,%22,%23,%24,%25,%26,%27,%28,%29,%30,%31}, %32, %33, p, 1, 1, 1, 1;}"
                    : "+f"(d[mt][0]), "+f"(d[mt][1]), "+f"(d[mt][2]), "+f"(d[mt][3]), "+f"(d[mt][4]), "+f"(d[mt][5]), "+f"(d[mt][6]), "+f"(d[mt][7]),
                      "+f"(d[mt][8]), "+f"(d[mt][9]), "+f"(d[mt][10]), "+f"(d[mt][11]), "+f"(d[mt][12]), "+f"(d[mt][13]), "+f"(d[mt][14]), "+f"(d[mt][15]),
                      "+f"(d[mt][16]), "+f"(d[mt][17]), "+f"(d[mt][18]), "+f"(d[mt][19]), "+f"(d[mt][20]), "+f"(d[mt][21]), "+f"(d[mt][22]), "+f"(d[mt][23]),
                      "+f"(d[mt][24]), "+f"(d[mt][25]), "+f"(d[mt][26]), "+f"(d[mt][27]), "+f"(d[mt][28]), "+f"(d[mt][29]), "+f"(d[mt][30]), "+f"(d[mt][31])
                    : "l"(da), "l"(db), "r"(ks));
            }
            asm volatile("wgmma.commit_group.sync.aligned;" ::: "memory");
        }
        if (RELK == 16) release();
#pragma unroll
        for (int mt = 0; mt < 2; mt++) {
            if (mt == 0 && !ILV) asm volatile("wgmma.wait_group.sync.aligned 1;" ::: "memory");
            else asm volatile("wgmma.wait_group.sync.aligned 0;" ::: "memory");
            if (RELK == 17 + mt) release();
            ESTAMP(3 + mt);
#pragma unroll
            for (int i = 0; i < 32; i++) asm volatile("" : "+f"(d[mt][i]) :: "memory");
#pragma unroll
            for (int j = 0; j < 8; j++) {
                const uint32_t v0 = pack2(d[mt][4 * j], d[mt][4 * j + 1]), v1 = pack2(d[mt][4 * j + 2], d[mt][4 * j + 3]);
                const uint32_t rv = __shfl_xor_sync(0xffffffff, odd ? v0 : v1, 1);
                if (nd[j] < nn) ob[nd[j] * 128 + mt * 64] = odd ? make_uint2(rv, v1) : make_uint2(v0, rv);
            }
        }
    }
    TSTAMP(8); ESTAMP(5);
}

}

extern "C" void kernel_launch(void* const* d_in, const int* in_sizes, int n_in, void* d_out, int out_size) {
    (void)in_sizes; (void)n_in; (void)out_size;
    cudaFuncSetAttribute(tfn_kernel, cudaFuncAttributeMaxDynamicSharedMemorySize, SM_TOTAL);
    Scratch* gs = nullptr;
    cudaGetSymbolAddress((void**)&gs, g_scratch);
    cudaLaunchConfig_t cfg = {};
    cfg.gridDim = dim3(NB); cfg.blockDim = dim3(NT); cfg.dynamicSmemBytes = SM_TOTAL; cfg.stream = cudaStreamPerThread;
    cudaLaunchAttribute at[1];
    at[0].id = cudaLaunchAttributeCooperative; at[0].val.cooperative = 1;
    cfg.attrs = at; cfg.numAttrs = 1;
    cudaLaunchKernelEx(&cfg, tfn_kernel, (const unsigned char*)d_in[0], (const int4*)d_in[1], (const int4*)d_in[2],
                       (const uint4*)d_in[3], (const uint4*)d_in[4], (const uint16_t*)d_in[5], (const uint16_t*)d_in[6],
                       (const uint4*)d_in[7], (uint32_t*)d_out, gs);
}
```

```cpp
#include <cuda_runtime.h>
#include <cuda_bf16.h>
#include <stdint.h>

namespace {

constexpr int NN = 10000;
constexpr int NE = 320000;
constexpr int NB = 132;
constexpr int NW = 20;
constexpr int NT = NW * 32;
constexpr int CW = NW - 1;
#define PWARP 10
constexpr int PW = PWARP;
constexpr int NPB = 76;
constexpr int CELL = 48;
constexpr int RCH = 2880;
constexpr int CAP = 19;
constexpr int DS = 4;
constexpr int STEPB = 160;
constexpr int NE4 = NE / 4;
constexpr int NPIECE = NB * 8;
constexpr int KB = 320, KN = 32 * KB;
constexpr uint32_t F_PAD = 0x80000000u;
constexpr uint32_t F_WRAP = 1;

constexpr int SLOTB = NW * 2048;
constexpr int SM_RING = 0;
constexpr int SM_META = SM_RING + DS * SLOTB;
constexpr int SM_AZ = SM_META + NW * CAP * STEPB;
constexpr int SM_MISC = SM_AZ + 2048;
constexpr int SM_TOTAL = SM_MISC + 2048;
constexpr int SM_STAGE = SM_RING;
constexpr int SM_HIST = SM_RING + 25600;
constexpr int SM_POS = SM_RING;
constexpr int SM_SMALL = SM_HIST + 13056;
constexpr int SM_LIST = SM_RING + SLOTB;
constexpr int SM_ROUT = SM_RING + 2 * SLOTB;
constexpr int SM_RECS = SM_RING + 3 * SLOTB;
constexpr int SM_RAWY = SM_META;
constexpr int SM_RAWE = SM_RAWY + 608 * 32;
constexpr int SM_KEYS = SM_RAWE + 608 * 32;
static_assert(SM_TOTAL <= 232448 && SM_KEYS + NPIECE * 16 <= SM_AZ, "smem");
static_assert(SM_RECS + NB * CELL * 16 + 16 <= SM_AZ && SM_KEYS + NPIECE * 16 <= SM_RECS + NB * CELL * 16 && SM_SMALL + 1152 <= SLOTB && DS == 4, "smem");

struct Scratch {
    uint4 keys[NB * NPIECE];
    uint4 recs[NB * RCH];
    uint4 stash[NB * NW * 256];
    unsigned bar[2];
    unsigned long long t0;
};
__device__ Scratch g_scratch;
#define TSTAMP(i)
#define TSTAMPC(i)
#define WSTAMP(i)
#define ESTAMP(i)

__device__ __forceinline__ void mma16816(float* d, uint32_t a0, uint32_t a1, uint32_t a2, uint32_t a3, uint32_t b0, uint32_t b1) {
    asm("mma.sync.aligned.m16n8k16.row.col.f32.bf16.bf16.f32 {%0,%1,%2,%3}, {%4,%5,%6,%7}, {%8,%9}, {%0,%1,%2,%3};"
        : "+f"(d[0]), "+f"(d[1]), "+f"(d[2]), "+f"(d[3]) : "r"(a0), "r"(a1), "r"(a2), "r"(a3), "r"(b0), "r"(b1));
}
__device__ __forceinline__ void mma1688z(float* d, uint32_t a0, uint32_t a1, uint32_t b0) {
    asm("mma.sync.aligned.m16n8k8.row.col.f32.bf16.bf16.f32 {%0,%1,%2,%3}, {%4,%5}, {%6}, {%7,%7,%7,%7};"
        : "=f"(d[0]), "=f"(d[1]), "=f"(d[2]), "=f"(d[3]) : "r"(a0), "r"(a1), "r"(b0), "f"(0.f));
}
__device__ __forceinline__ uint32_t pack2(float lo, float hi) {
    uint32_t r; asm("cvt.rn.bf16x2.f32 %0, %1, %2;" : "=r"(r) : "f"(hi), "f"(lo)); return r;
}
__device__ __forceinline__ float silu_h(float h) {
    float t; asm("tanh.approx.f32 %0, %1;" : "=f"(t) : "f"(h)); return fmaf(h, t, h);
}
__device__ __forceinline__ uint32_t mul_lo(uint32_t v, uint32_t r) {
    __nv_bfloat162 a = *(__nv_bfloat162*)&v, b = *(__nv_bfloat162*)&r; __nv_bfloat162 c = __hmul2(a, __low2bfloat162(b)); return *(uint32_t*)&c;
}
__device__ __forceinline__ uint32_t mul_hi(uint32_t v, uint32_t r) {
    __nv_bfloat162 a = *(__nv_bfloat162*)&v, b = *(__nv_bfloat162*)&r; __nv_bfloat162 c = __hmul2(a, __high2bfloat162(b)); return *(uint32_t*)&c;
}
__device__ __forceinline__ uint32_t lds32(uint32_t a) {
    uint32_t r; asm volatile("ld.shared.u32 %0, [%1];" : "=r"(r) : "r"(a) : "memory"); return r;
}
__device__ __forceinline__ void sts32(uint32_t a, uint32_t v) { asm volatile("st.shared.u32 [%0], %1;" :: "r"(a), "r"(v) : "memory"); }
__device__ __forceinline__ uint2 lds64(uint32_t a) {
    uint2 r; asm volatile("ld.shared.v2.u32 {%0,%1}, [%2];" : "=r"(r.x), "=r"(r.y) : "r"(a)); return r;
}
__device__ __forceinline__ uint4 lds128(uint32_t a) {
    uint4 r; asm volatile("ld.shared.v4.u32 {%0,%1,%2,%3}, [%4];" : "=r"(r.x), "=r"(r.y), "=r"(r.z), "=r"(r.w) : "r"(a) : "memory"); return r;
}
__device__ __forceinline__ void bar_sync(int id, int n) { asm volatile("bar.sync %0, %1;" :: "r"(id), "r"(n) : "memory"); }
__device__ __forceinline__ void bar_arrive(int id, int n) { asm volatile("bar.arrive %0, %1;" :: "r"(id), "r"(n) : "memory"); }
__device__ __forceinline__ void mbar_wait(uint32_t bar, uint32_t ph) {
    uint32_t done; int spins = 0;
    do {
        asm volatile("{.reg .pred p; mbarrier.try_wait.parity.shared.b64 p, [%1], %2; selp.u32 %0,1,0,p;}" : "=r"(done) : "r"(bar), "r"(ph) : "memory");
    } while (!done && ++spins < (1 << 22));
}
__device__ __forceinline__ unsigned gbar_read(const unsigned* ctr) {
    unsigned v; asm volatile("ld.relaxed.gpu.global.u32 %0, [%1];" : "=r"(v) : "l"(ctr) : "memory");
    return v;
}
__device__ __forceinline__ void gbar_arrive(unsigned* ctr) {
    asm volatile("red.add.release.gpu.global.u32 [%0], 1;" :: "l"(ctr) : "memory");
}
__device__ __forceinline__ bool gbar_wait(const unsigned* ctr, unsigned target) {
    unsigned v; int spins = 0;
    while (true) {
        asm volatile("ld.acquire.gpu.global.u32 %0, [%1];" : "=r"(v) : "l"(ctr) : "memory");
        if ((int)(v - target) >= 0 || ++spins > (1 << 22)) break;
    }
    return (int)(v - target) >= 0;
}
__device__ __forceinline__ int chunk_start4(int c) { return (c * NE4) / NB; }
__device__ __forceinline__ float bf2f(uint32_t h) { return __uint_as_float(h << 16); }

__device__ __noinline__ void slow_path(unsigned char* smem, int n0, int nn, const uint16_t* x, const int* src, const int* dst,
                                       const uint16_t* Y, const uint16_t* ef, const uint16_t* w_rad, const uint16_t* cg,
                                       const uint16_t* w_mix, __nv_bfloat16* out) {
    float* agg = (float*)smem;
    const int tid = threadIdx.x, lane = tid & 31, w = tid >> 5;
    bar_sync(1, NT);
    for (int i = tid; i < NPB * 512; i += NT) agg[i] = 0.f;
    bar_sync(1, NT);
    for (int e0 = w * 32; e0 < NE; e0 += NT) {
        int dl = dst[e0 + lane] - n0;
        unsigned m = __ballot_sync(0xffffffff, dl >= 0 && dl < nn);
        while (m) {
            int l = __ffs(m) - 1; m &= m - 1;
            int e = e0 + l, d = __shfl_sync(0xffffffff, dl, l), s = src[e];
            float T[16];
            for (int i = 0; i < 4; i++) for (int o = 0; o < 4; o++) {
                float a = 0.f;
                for (int f = 0; f < 4; f++) a += bf2f(Y[e * 4 + f]) * bf2f(cg[i * 16 + f * 4 + o]);
                T[i * 4 + o] = a;
            }
            for (int k = 0; k < 4; k++) {
                int c = lane + 32 * k;
                float z = 0.f;
                for (int j = 0; j < 4; j++) z += bf2f(ef[e * 4 + j]) * bf2f(w_rad[j * 128 + c]);
                float R = z / (1.f + __expf(-z));
                for (int o = 0; o < 4; o++) {
                    float a = 0.f;
                    for (int i = 0; i < 4; i++) a += bf2f(x[(size_t)s * 512 + c * 4 + i]) * T[i * 4 + o];
                    atomicAdd(&agg[d * 512 + c * 4 + o], R * a);
                }
            }
        }
    }
    bar_sync(1, NT);
    for (int i = tid; i < nn * 512; i += NT) {
        int n = i >> 9, d = (i >> 2) & 127, o = i & 3;
        float a = 0.f;
        for (int c = 0; c < 128; c++) a += agg[n * 512 + c * 4 + o] * bf2f(w_mix[c * 128 + d]);
        out[(size_t)(n0 + n) * 512 + (i & 511)] = __float2bfloat16(a);
    }
}

#define PACE 22750
#define YDELAY 300
#define POFF 3800
#define PSLEEP 32
#define RLEN 99
#define FDT 400
#define FOFF 1700
#define FSTAG 0
#define RELK 12
#define ILV 0
#define SPINS 40
#define ONEBAR 0
#define LEAD 0
#define FAN 16
#define FANC 2
#define TDEL 100
#define RDY 850
#define PTOL0 300
#define PTOL 900
__global__ void __launch_bounds__(NT, 1)
tfn_kernel(const unsigned char* __restrict__ x, const int4* __restrict__ src4, const int4* __restrict__ dst4,
           const uint4* __restrict__ Y, const uint4* __restrict__ ef, const uint16_t* __restrict__ w_rad,
           const uint16_t* __restrict__ cg, const uint4* __restrict__ w_mix, uint32_t* __restrict__ out, Scratch* __restrict__ gs) {
    extern __shared__ __align__(1024) unsigned char smem[];
    const uint32_t sb = (uint32_t)__cvta_generic_to_shared(smem);
    const int b = blockIdx.x, tid = threadIdx.x, lane = tid & 31, g = lane >> 2, t = lane & 3;
    const int w = __shfl_sync(0xffffffff, tid >> 5, 0);
    uint32_t* stage = (uint32_t*)(smem + SM_STAGE);
    uint32_t* hist = (uint32_t*)(smem + SM_HIST);
    uint32_t* cnt = (uint32_t*)(smem + SM_MISC);
    uint32_t* deg = cnt + 136;
    uint32_t* order = deg + 104;
    uint32_t* cnt2 = order + 80;
    volatile uint32_t* flag = cnt2 + 136;
    const uint32_t mbarK = sb + SM_MISC + 1920, mbarR = mbarK + 8, mbarW = mbarK + 16;
    const int n0 = b * NPB, nn = min(NPB, NN - n0);
    TSTAMP(0);

    const int c0 = chunk_start4(b), c1 = chunk_start4(b + 1);
    const bool has4 = c0 + tid < c1;
    int4 d4 = make_int4(0, 0, 0, 0), s4 = d4;
    if (has4) { d4 = __ldg(dst4 + c0 + tid); s4 = __ldg(src4 + c0 + tid); }
    unsigned tgt = 0;
    if (tid == NT - 1) {
        tgt = gbar_read(&gs->bar[0]);
        asm volatile("mbarrier.init.shared.b64 [%0], 1;" :: "r"(mbarK));
        asm volatile("mbarrier.init.shared.b64 [%0], 1;" :: "r"(mbarR));
        asm volatile("mbarrier.init.shared.b64 [%0], 512;" :: "r"(mbarW));
        asm volatile("fence.mbarrier_init.release.cluster;" ::: "memory");
        flag[0] = 0; flag[12] = 0; flag[13] = 0; flag[15] = 0;
    }
    if (w == CW) {
        asm volatile("cp.async.cg.shared.global [%0], [%1], 16;" :: "r"(sb + SM_SMALL + lane * 16), "l"(w_rad + lane * 8) : "memory");
        asm volatile("cp.async.cg.shared.global [%0], [%1], 16;" :: "r"(sb + SM_SMALL + 512 + lane * 16), "l"(w_rad + 256 + lane * 8) : "memory");
        if (lane < 8) asm volatile("cp.async.cg.shared.global [%0], [%1], 16;" :: "r"(sb + SM_SMALL + 1024 + lane * 16), "l"(cg + lane * 8) : "memory");
    }
    ((uint4*)hist)[tid] = make_uint4(0, 0, 0, 0);
    {
        const uint32_t dk = (80 + b % 22) * KN + (b & 31) * KB;
#pragma unroll
        for (int j = 0; j < 3; j++) if (tid + j * NT < NB * CELL / 4) ((uint4*)stage)[tid + j * NT] = make_uint4(dk, dk, dk, dk);
    }
    if (tid < 136) cnt[tid] = 0;
    if (tid == 0) { *(uint4*)(smem + SM_MISC + 1824 + 32) = make_uint4(0, 0, 0, 0); *(uint4*)(smem + SM_RECS + NB * CELL * 16) = make_uint4(0, 0, 0, 0); }
    if (tid < 80) { deg[tid] = 127 - tid; order[tid] = tid; }
    __syncthreads();
    TSTAMP(9);
    if (tid == 64) {
        if (YDELAY) __nanosleep(YDELAY);
        asm volatile("mbarrier.arrive.expect_tx.shared.b64 _, [%0], %1;" :: "r"(mbarR), "r"((c1 - c0) * 64) : "memory");
        asm volatile("cp.async.bulk.shared::cluster.global.mbarrier::complete_tx::bytes [%0], [%1], %2, [%3];"
                     :: "r"(sb + SM_RAWY), "l"(Y + 2 * c0), "r"((c1 - c0) * 32), "r"(mbarR) : "memory");
        asm volatile("cp.async.bulk.shared::cluster.global.mbarrier::complete_tx::bytes [%0], [%1], %2, [%3];"
                     :: "r"(sb + SM_RAWE), "l"(ef + 2 * c0), "r"((c1 - c0) * 32), "r"(mbarR) : "memory");
    }

    uint32_t bin[4] = {0, 0, 0, 0}, slot[4] = {0, 0, 0, 0};
    if (has4) {
        const uint32_t dd[4] = {(uint32_t)d4.x, (uint32_t)d4.y, (uint32_t)d4.z, (uint32_t)d4.w}, ss[4] = {(uint32_t)s4.x, (uint32_t)s4.y, (uint32_t)s4.z, (uint32_t)s4.w};
#pragma unroll
        for (int k = 0; k < 4; k++) { bin[k] = dd[k] / NPB; slot[k] = atomicAdd(&cnt[bin[k]], 1); }
#pragma unroll
        for (int k = 0; k < 4; k++) stage[bin[k] * CELL + min(slot[k], CELL - 1)] = (dd[k] - bin[k] * NPB) * KN + ss[k];
    }
    if (w == CW) {
        if (tid == NT - 1) { tgt = tgt / NB + 1; flag[14] = (tgt & 1) << 31; tgt *= NB; }
        asm volatile("cp.async.wait_all;" ::: "memory");
    }
    bar_sync(1, NT);
    TSTAMP(1);
    const uint32_t tag = flag[14];
#pragma unroll
    for (int j = 0; j < 2; j++) {
        const int i = tid + j * NT;
        if (i < NPIECE) {
            const uint2 sa = *(const uint2*)(stage + i * 6), sc = *(const uint2*)(stage + i * 6 + 2);
            uint2 se = *(const uint2*)(stage + i * 6 + 4);
            const uint32_t cf = cnt[i >> 3], cn = min(cf, 63u);
            if ((i & 7) == 7) {
                const uint32_t al = cf > CELL - 8 ? 7 : 0;
                uint32_t o;
                asm volatile("atom.shared.add.u32 %0, [%1], %2;" : "=r"(o) : "r"(sb + SM_MISC + 1824 + 60), "r"(cf + al) : "memory");
                se.y = (o + al) & ~al;
                cnt2[i >> 3] = se.y;
            }
            asm volatile("{.reg .b64 lo, hi; mov.b64 lo, {%1,%2}; mov.b64 hi, {%3,%4}; st.relaxed.gpu.global.v2.b64 [%0], {lo, hi};}"
                         :: "l"(gs->keys + ((i >> 3) * NB + b) * 8 + ((i ^ b) & 7)),
                            "r"(sa.x | (se.x << 20)), "r"(sa.y | ((se.x >> 12) << 20) | ((cn & 7) << 28) | tag),
                            "r"(sc.x | (se.y << 20)), "r"(sc.y | ((se.y >> 12) << 20) | ((cn >> 3) << 28) | tag) : "memory");
        }
    }
    bar_sync(1, NT);
    if (tid == NT - 1) {
        TSTAMPC(10);
        asm volatile("red.add.relaxed.gpu.global.u32 [%0], 1;" :: "l"(&gs->bar[0]) : "memory");
        asm volatile("mbarrier.arrive.expect_tx.shared.b64 _, [%0], %1;" :: "r"(mbarK), "r"(NPIECE * 16) : "memory");
        gbar_wait(&gs->bar[0], tgt);
        TSTAMPC(13);
        asm volatile("fence.proxy.async.global;" ::: "memory");
        asm volatile("cp.async.bulk.shared::cluster.global.mbarrier::complete_tx::bytes [%0], [%1], %2, [%3];"
                 :: "r"(sb + SM_KEYS), "l"(gs->keys + b * NPIECE), "r"(NPIECE * 16), "r"(mbarK) : "memory");
    }
    __syncwarp();
    uint32_t at[4];
    {
        const int o = g & 3, f = 2 * (t & 1);
#pragma unroll
        for (int i = 0; i < 4; i++) {
            const uint16_t* cp = (const uint16_t*)(smem + SM_SMALL + 1024) + i * 16 + f * 4 + o;
            at[i] = (t >> 1) == (g >> 2) ? cp[0] | ((uint32_t)cp[4] << 16) : 0;
        }
    }

    const int q = lane >> 3, c = lane & 7;
    const uint32_t ring0 = sb + SM_RING + w * 2048;
    uint32_t wdst = ring0 + q * 128 + ((c + 2 * q) & 7) * 16;
    uint32_t rsrc = ring0 + t * 128 + ((g + 2 * t) & 7) * 16;
    uint32_t recl = sb + SM_META + w * (CAP * STEPB) + g * 16 + (t & 1) * 8, srcl = sb + SM_META + w * (CAP * STEPB) + 128 + q * 8;
    uint32_t flg = sb + SM_MISC + (136 + 104 + 80 + 136) * 4;
    asm volatile("" : "+r"(wdst), "+r"(rsrc), "+r"(recl), "+r"(srcl), "+r"(flg));
    auto setflag = [&]() { sts32(flg, 1); };
    uint32_t key[2][6], ha[2][6], rk[2][6], kidx[2], ka[2], kc[2];
    int nk[2];
#pragma unroll
    for (int j = 0; j < 2; j++) {
        const int i0 = j ? 2 * 608 - 1 - tid : tid, i = min(i0, NPIECE - 1), r = i / NB, cc = i - r * NB;
        ka[j] = sb + SM_KEYS + (cc * 8 + ((r ^ cc) & 7)) * 16;
        kidx[j] = (cc * CELL + r * 6) << 17;
        kc[j] = sb + SM_MISC + cc * 4;
        nk[j] = i0 < NPIECE && w < CW ? -6 * r : -1000;
    }
    asm volatile("" : "+r"(at[0]), "+r"(at[1]), "+r"(at[2]), "+r"(at[3]), "+r"(ka[0]), "+r"(ka[1]), "+r"(kidx[0]), "+r"(kidx[1]), "+r"(kc[0]), "+r"(kc[1]), "+r"(nk[0]), "+r"(nk[1]));
    if (w == CW) {
        __syncwarp();
        bar_sync(7, NT);
        if (tid == NT - 1) {
            TSTAMPC(11);
            asm volatile("cp.async.bulk.global.shared::cta.bulk_group [%0], [%1], %2;"
                         :: "l"(gs->recs + b * RCH), "r"(sb + SM_ROUT), "r"(((flag[15] + 1) & ~1u) * 16) : "memory");
            asm volatile("cp.async.bulk.commit_group;" ::: "memory");
            mbar_wait(mbarK, 0);
            unsigned long long tbase;
            asm volatile("mov.u64 %0, %%globaltimer;" : "=l"(tbase));
            tbase += POFF;
            flag[1] = (uint32_t)tbase; flag[4] = (uint32_t)tbase; flag[5] = (uint32_t)(tbase >> 32);
            asm volatile("red.max.relaxed.gpu.global.u64 [%0], %1;" :: "l"(&gs->t0), "l"(tbase) : "memory");
            if (b < 128) asm volatile("cp.async.bulk.prefetch.L2.global [%0], 256;" :: "l"(w_mix + b * 16));
            asm volatile("cp.async.bulk.wait_group 0;" ::: "memory");
            TSTAMPC(14);
            asm volatile("red.add.relaxed.gpu.global.u32 [%0], 1;" :: "l"(&gs->bar[1]) : "memory");
            TSTAMPC(15);
        }
    } else {
        if (w < 8) {
            const uint32_t* wp = (const uint32_t*)(smem + SM_SMALL) + (t & 1) * 128 + 8 * w + g;
            const uint32_t wr0 = t < 2 ? wp[0] : 0, wr1 = t < 2 ? wp[64] : 0;
            *(uint2*)(smem + SM_AZ + (w >> 1) * 512 + lane * 16 + (w & 1) * 8) =
                make_uint2(pack2(0.5f * bf2f(wr0 & 0xFFFF), 0.5f * bf2f(wr1 & 0xFFFF)), pack2(0.5f * bf2f(wr0 >> 16), 0.5f * bf2f(wr1 >> 16)));
        }
        const bool sw = g & 1;
        uint32_t rp[4];
#pragma unroll
        for (int k = 0; k < 4; k++) rp[k] = cnt2[bin[k]] + slot[k];
        uint4* ro = (uint4*)(smem + SM_ROUT);
        uint4 *p0 = ro + (sw ? rp[2] : rp[0]), *p1 = ro + (sw ? rp[3] : rp[1]), *p2 = ro + (sw ? rp[0] : rp[2]), *p3 = ro + (sw ? rp[1] : rp[3]);
        const uint32_t ya = sb + SM_RAWY + tid * 32 + (sw ? 16 : 0);
        mbar_wait(mbarR, 0);
        TSTAMP(18);
        if (has4) {
            const uint4 y0 = lds128(ya), e0 = lds128(ya + (SM_RAWE - SM_RAWY)), y1 = lds128(ya ^ 16), e1 = lds128((ya ^ 16) + (SM_RAWE - SM_RAWY));
            *p0 = make_uint4(y0.x, e0.x, y0.y, e0.y); *p1 = make_uint4(y0.z, e0.z, y0.w, e0.w);
            *p2 = make_uint4(y1.x, e1.x, y1.y, e1.y); *p3 = make_uint4(y1.z, e1.z, y1.w, e1.w);
        }
        asm volatile("fence.proxy.async.shared::cta;" ::: "memory");
        bar_arrive(7, NT);
    }
    __syncwarp();
    TSTAMP(2);

    if (w < CW) {
        mbar_wait(mbarK, 0);
        TSTAMP(3);
        uint4 v[2] = {lds128(ka[0]), lds128(ka[1])};
        if ((int)((v[0].y ^ tag) | (v[0].w ^ tag) | (v[1].y ^ tag) | (v[1].w ^ tag)) < 0) {
#pragma unroll
            for (int j = 0; j < 2; j++) {
                int spins = 0;
#pragma unroll 1
                while ((int)((v[j].y ^ tag) | (v[j].w ^ tag)) < 0) {
                    asm volatile("{.reg .b64 lo, hi; ld.relaxed.gpu.global.v2.b64 {lo, hi}, [%4]; mov.b64 {%0,%1}, lo; mov.b64 {%2,%3}, hi;}"
                                 : "=r"(v[j].x), "=r"(v[j].y), "=r"(v[j].z), "=r"(v[j].w) : "l"((const unsigned char*)(gs->keys + b * NPIECE) + (ka[j] - sb - SM_KEYS)) : "memory");
                    if (++spins > (1 << 20)) { setflag(); break; }
                }
            }
        }
#pragma unroll
        for (int j = 0; j < 2; j++) {
            const uint32_t hc = ((v[j].y >> 28) & 7) | ((v[j].w >> 25) & 0x38);
            if (j == 1 && nk[j] == -42) {
                sts32(kc[j], hc | ((v[j].z >> 20) << 8));
                if (hc > CELL - 1) setflag();
                v[j].w |= ((80 * KN) >> 12) << 20;
            }
            nk[j] += hc;
            if (nk[j] > 0) {
                key[j][0] = v[j].x & 0xFFFFF; key[j][1] = v[j].y & 0xFFFFF; key[j][2] = v[j].z & 0xFFFFF; key[j][3] = v[j].w & 0xFFFFF;
                key[j][4] = (v[j].x >> 20) | ((v[j].y >> 8) & 0xFF000); key[j][5] = (v[j].z >> 20) | ((v[j].w >> 8) & 0xFF000);
#pragma unroll
                for (int u = 0; u < 6; u++) {
                    ha[j][u] = __umulhi(key[j][u], 0xFFFFFFFFu / KB + 1);
                    asm volatile("{.reg .u32 a, n; mad.lo.u32 a, %1, 4, %2; atom.shared.add.u32 %0, [a+%3], 1;\n"
                                 "shr.u32 n, %1, 5; mad.lo.u32 a, n, 4, %2; red.shared.add.u32 [a+%4], 128;}"
                                 : "=r"(rk[j][u]) : "r"(ha[j][u]), "r"(sb), "n"(SM_HIST), "n"(SM_MISC + 136 * 4) : "memory");
                }
            }
        }
        bar_sync(9, NT - 32);
        TSTAMP(20);
        const int n = tid >> 3, sub = tid & 7;
        const uint32_t me = deg[n];
        uint32_t r = 0, r2 = 0;
#pragma unroll
        for (int k = 0; k < 5; k++) { const uint2 dd = *(const uint2*)(deg + sub * 10 + 2 * k); r += (me - dd.x) >> 31; r2 += (me - dd.y) >> 31; }
        r += r2;
#pragma unroll
        for (int j = 0; j < 2; j++) kidx[j] += (lds32(kc[j]) & 0x700) << 9;
        r += __shfl_xor_sync(0xffffffff, r, 1); r += __shfl_xor_sync(0xffffffff, r, 2); r += __shfl_xor_sync(0xffffffff, r, 4);
        if (sub == 0) order[r] = n;
    }
    bar_sync(1, NT);
    TSTAMP(22);
    uint32_t len2;
    {
        const uint2 na = *(const uint2*)(order + 2 * w);
        uint2 nb = *(const uint2*)(order + 78 - 2 * w);
        const uint32_t hl = sb + SM_HIST + lane * 4;
        const uint32_t ha0 = lds32(hl + na.x * 128), ha1 = lds32(hl + na.y * 128), hb0 = lds32(hl + nb.y * 128), hb1 = lds32(hl + nb.x * 128);
        if (deg[na.x] >= (4 * CAP + 1) * 128) setflag();
        const uint32_t ca = ha0 + (ha1 << 16), c4 = ca + (hb0 << 8) + (hb1 << 24);
        uint32_t inc = c4;
#pragma unroll
        for (int o = 1; o < 32; o <<= 1)
            asm volatile("{.reg .pred p; .reg .u32 u; shfl.sync.up.b32 u|p, %0, %1, 0, 0xffffffff; @p add.u32 %0, %0, u;}" : "+r"(inc) : "r"(o));
        const int su = __reduce_add_sync(0xffffffff, (int)(ha0 - ha1) * (2 * lane - 31)), sv = __reduce_add_sync(0xffffffff, (int)(hb0 - hb1) * (2 * lane - 31));
        const bool swp = (su ^ sv) >= 0;
        if (swp) { nb = make_uint2(nb.y, nb.x); *(uint2*)(order + 78 - 2 * w) = nb; }
        const uint32_t sel = swp ? 0x4143 : 0x4341, ex = inc - c4;
        const uint32_t ea = (ex & 0x00FF00FF) + __byte_perm(ex, 0, sel), eb = ea + ca, base = sb + SM_LIST + w * 2048;
        uint2* pos = (uint2*)(smem + SM_POS) + lane;
        pos[na.x * 32] = make_uint2(base + (ea & 0xFFFF) * 8, na.x * (0u - 4 * KN));
        pos[nb.y * 32] = make_uint2(base + (eb & 0xFFFF) * 8, nb.y * (0u - 4 * KN) + 0x80000000u);
        pos[na.y * 32] = make_uint2(base + 4 + (ea >> 16) * 8, na.y * (0u - 4 * KN));
        pos[nb.x * 32] = make_uint2(base + 4 + (eb >> 16) * 8, nb.x * (0u - 4 * KN) + 0x80000000u);
        len2 = __shfl_sync(0xffffffff, (inc & 0x00FF00FF) + __byte_perm(inc, 0, sel), 31);
        if (max(len2 & 0xFFFF, len2 >> 16) > 4 * CAP) setflag();
    }
    uint32_t ci = cnt[min(w + NW * lane, NB)];
    ci = (((ci & 0xFF) + ((ci >> 8) & 7)) << 24) + min(w + NW * lane, NB) * (RCH / 8) + (ci >> 11);
    if (w == CW) {
        bar_arrive(9, NT);
        if (tid == NT - 1) {
            uint32_t v1, g0; int spins = 0;
            do {
                asm volatile("ld.relaxed.gpu.global.u32 %1, [%2+8]; ld.acquire.gpu.global.u32 %0, [%2+4];" : "=r"(v1), "=r"(g0) : "l"(gs->bar) : "memory");
            } while ((int)(v1 - tgt) < 0 && ++spins < (1 << 22));
            if ((int)(v1 - tgt) < 0) *flag = 1;
            if (g0 - flag[1] < 30000) flag[1] = g0;
            TSTAMPC(17);
        }
        __syncwarp();
    } else {
        bar_sync(9, NT);
        TSTAMP(21);
        const uint32_t over = lds32(flg);
#pragma unroll
        for (int j = 0; j < 2; j++) {
            if (nk[j] > 0) {
                uint2 h[6];
#pragma unroll
                for (int u = 0; u < 6; u++) h[u] = lds64(sb + SM_POS + ha[j][u] * 8);
                if (over) nk[j] = 0;
#pragma unroll
                for (int u = 0; u < 6; u++)
                    asm volatile("{.reg .pred p; setp.gt.s32 p, %2, %3; @p st.shared.u32 [%0], %1;}"
                                 :: "r"(h[u].x + rk[j][u] * 8), "r"(key[j][u] * 4 + h[u].y + (kidx[j] + (u << 17))), "r"(nk[j]), "r"(u) : "memory");
            }
        }
    }
    bar_sync(1, NT);
    TSTAMP(4);
    if (*flag) {
        slow_path(smem, n0, nn, (const uint16_t*)x, (const int*)src4, (const int*)dst4, (const uint16_t*)Y, (const uint16_t*)ef, w_rad, cg,
                  (const uint16_t*)w_mix, (__nv_bfloat16*)out);
        return;
    }
    {
        const uint4* gp = gs->recs + lane;
        asm volatile("" : "+l"(gp));
        const uint32_t sp = sb + SM_RECS + (w * CELL + lane) * 16, lc = (lane << 24) | 0xFFFFFF;
#pragma unroll
        for (int j = 0; j < 7; j++)
            asm volatile("{.reg .pred p; .reg .u32 l; .reg .u64 a; setp.lt.u32 p, %2, %3; and.b32 l, %3, 0xFFFF; mad.wide.u32 a, l, 128, %1;\n"
                         "@p cp.async.cg.shared.global [%0], [a], 16;}"
                         :: "r"(sp + j * (NW * CELL * 16)), "l"(gp), "r"(lc), "r"(__shfl_sync(0xffffffff, ci, j)) : "memory");
        for (uint32_t m = __ballot_sync(0xffffffff, ci >= (33u << 24)); m; m &= m - 1) {
            const int j = __ffs(m) - 1;
            const uint32_t cj = __shfl_sync(0xffffffff, ci, j);
            if (lane + 32 < (cj >> 24))
                asm volatile("cp.async.cg.shared.global [%0], [%1], 16;" :: "r"(sp + j * (NW * CELL * 16) + 512), "l"(gp + (size_t)(cj & 0xFFFF) * 8 + 32) : "memory");
        }
        asm volatile("cp.async.commit_group;" ::: "memory");
    }
    const int S = __shfl_sync(0xffffffff, max((int)(max(len2 & 0xFFFF, len2 >> 16) + 3) >> 2, DS + 1), 0);
    const int mylen = (lane & 1) ? len2 >> 16 : len2 & 0xFFFF;
    constexpr int NRAW = (CAP + 3) / 4;
    uint32_t bits0 = 0, raw[NRAW];
    unsigned char* meta = smem + SM_META + w * (CAP * STEPB);
    const int la = sb + SM_LIST + w * 2048 + lane * 4, llast = la - (lane & ~1) * 4 + (mylen - 1) * 8;
#pragma unroll
    for (int k = 0; k < NRAW; k++) raw[k] = lds32(min(la + k * 128, llast));
    const uint32_t sv0 = min(raw[0] & 0xFFFC, 4 * (NN - 1));
    const unsigned char* pbase = x + c * 16;
    asm volatile("" : "+l"(pbase));
    auto cpa2 = [&](uint32_t dstp, uint32_t sv) {
        asm volatile("cp.async.cg.shared.global [%0], [%1], 16; cp.async.cg.shared.global [%0+1024], [%1+128], 16;"
                     :: "r"(dstp), "l"(pbase + (size_t)sv * 256) : "memory");
    };
    auto cpa2p = [&](uint32_t dstp, uint32_t sv) {
        asm volatile("{.reg .pred p; setp.ge.s32 p, %2, 0; @p cp.async.cg.shared.global [%0], [%1], 16; @p cp.async.cg.shared.global [%0+1024], [%1+128], 16;}"
                     :: "r"(dstp), "l"(pbase + (size_t)sv * 256), "r"(sv) : "memory");
    };
    auto wait_until = [&](uint32_t tt) {
        asm volatile("{.reg .pred p; .reg .u32 d;\n"
                     "PACE_LOOP: mov.u32 d, %%globaltimer_lo; sub.u32 d, %0, d; setp.lt.u32 p, d, 32768; @p nanosleep.u32 %1; @p bra.uni PACE_LOOP;}"
                     :: "r"(tt), "n"(PSLEEP) : "memory");
    };
    const uint32_t tfill = flag[1] - FOFF + w * FSTAG;
    auto fill = [&](int i) {
        if (FDT) wait_until(tfill + i * FDT);
        cpa2(wdst + i * SLOTB, __shfl_sync(0xffffffff, sv0, 8 * i + 2 * q)); cpa2(wdst + i * SLOTB + 512, __shfl_sync(0xffffffff, sv0, 8 * i + 2 * q + 1));
        asm volatile("cp.async.commit_group;" ::: "memory");
    };
    fill(0);
    TSTAMP(5);
    auto relay = [&]() {
        uint32_t g0, g1, b0, b1;
        asm volatile("ld.volatile.shared.v2.u32 {%0,%1}, [%4+40]; ld.volatile.shared.v2.u32 {%2,%3}, [%4+16];"
                     : "=r"(g0), "=r"(g1), "=r"(b0), "=r"(b1) : "r"(flg) : "memory");
        const unsigned long long dg = (((unsigned long long)g1 << 32) | g0) - (((unsigned long long)b1 << 32) | b0);
        asm volatile("{.reg .pred p, q; setp.eq.u32 p, %1, 0; setp.lt.u64 q, %2, 30000; @q st.shared.u32 [%3+4], %4;\n"
                     "@p cp.async.cg.shared.global [%3+32], [%0], 16;}"
                     :: "l"(gs->bar), "r"(lane), "l"(dg), "r"(flg), "r"(g0) : "memory");
    };
    auto report = [&](uint32_t cand) {
        uint32_t b0, b1;
        asm volatile("ld.volatile.shared.v2.u32 {%0,%1}, [%2+16];" : "=r"(b0), "=r"(b1) : "r"(flg) : "memory");
        asm volatile("{.reg .pred p; setp.eq.u32 p, %2, 0; @p red.max.relaxed.gpu.global.u64 [%0], %1;}"
                     :: "l"(&gs->t0), "l"((((unsigned long long)b1 << 32) | b0) + (cand - b0)), "r"(lane) : "memory");
    };
    uint32_t ra[NRAW];
#pragma unroll
    for (int k = NRAW - 1; k >= 0; k--) {
        const uint32_t m = (__ballot_sync(0xffffffff, (int)raw[k] < 0) >> g) & 0x01010101u;
        bits0 = __funnelshift_l(m * 0x10204080u, bits0, 4);
        const bool pad = la + k * 128 > llast;
        ra[k] = pad ? NB * CELL * 16 : (raw[k] >> 13) & 0x1FFF0;
        raw[k] = (raw[k] & 0xFFFF) | (pad ? F_PAD : 0);
    }
    if (t < 2) bits0 = ~bits0;
    asm volatile("" : "+r"(bits0), "+r"(ra[0]), "+r"(ra[1]), "+r"(ra[2]), "+r"(ra[3]), "+r"(ra[4]), "+r"(raw[0]), "+r"(raw[1]), "+r"(raw[2]), "+r"(raw[3]), "+r"(raw[4]));
    fill(1);
    asm volatile("cp.async.wait_group 2;" ::: "memory");
    bar_sync(1, NT);
    TSTAMP(19);
    if (w == CW) {
        uint32_t tn; asm volatile("mov.u32 %0, %%globaltimer_lo;" : "=r"(tn));
        if ((int)(tn + RDY - flag[1]) > 0) { report(tn + RDY); flag[1] = tn + RDY; }
    }
    {
        uint4 rv[NRAW];
#pragma unroll
        for (int k = 0; k < NRAW - 1; k++) rv[k] = lds128(ra[k] + (sb + SM_RECS));
        if ((NRAW - 1) * 4 < S) rv[NRAW - 1] = lds128(ra[NRAW - 1] + (sb + SM_RECS));
        fill(2);
        bar_sync(1, NT);
        TSTAMP(12);
        unsigned char* mr = meta + (q - 1) * STEPB + c * 16;
        unsigned char* ms = meta + (q - DS - 1) * STEPB + 128 + c * 4;
#pragma unroll
        for (int k = 0; k < NRAW; k++) {
            if (k == 0) {
                *(uint4*)(mr + (q == 0 ? S * STEPB : 0)) = rv[k];
                *(uint32_t*)(ms + S * STEPB) = raw[0] + F_WRAP;
            } else if (k * 4 + q < S) {
                *(uint4*)(mr + k * 4 * STEPB) = rv[k];
                *(uint32_t*)(ms + k * 4 * STEPB + (k == 1 && q == 0 ? S * STEPB : 0)) = raw[k];
            }
        }
    }
    __syncwarp();
    const uint32_t tphase = PACE / 4;
    uint32_t dreg;
    {
        const int ls = lane >= S ? min(lane - S, S - 1) : lane, st = ls == 0 ? S - 1 : ls - 1;
        const uint4 u0 = *(const uint4*)(meta + st * STEPB + 128), u1 = *(const uint4*)(meta + st * STEPB + 144);
        int pos = (u0.x + u0.y + u0.z + u0.w + u1.x + u1.y + u1.z + u1.w) << 1 >> 6;
        pos += ((u0.x & F_WRAP) ? NN : 0) + (lane >= S ? NN : 0) - NN * (2 * DS + 1) / 32;
        dreg = pos * (int)tphase / NN;
    }
    fill(3);
    TSTAMP(6);

    uint32_t* stash = (uint32_t*)(gs->stash + (b * NW + w) * 256) + lane;
    float acc[4][4];
#pragma unroll
    for (int i = 0; i < 16; i++) acc[i / 4][i % 4] = 0.f;
    uint4 az = *(const uint4*)(smem + SM_AZ + lane * 16);
    uint32_t dcur = dreg, dl = 0, now = flag[1], tcur = 0;
    uint32_t mp = 0, smask = 1, didx = 2;
    uint32_t mend = S * STEPB;
    uint2 r = lds64(mend - STEPB + recl), s0 = lds64(mend - STEPB + srcl);
    auto step = [&](const uint32_t off, const int mode, const bool pc = true) {
        if (mode == 0 && pc) { unsigned long long n64; asm volatile("mov.u64 %0, %%globaltimer;" : "=l"(n64)); now = (uint32_t)n64; }
        const uint2 rc = r, sc = s0;
        if (mode != 4) r = lds64(mp + recl);
        if (mode == 0) s0 = lds64(mp + srcl);
        asm volatile("cp.async.wait_group %0;" :: "n"(DS - 1) : "memory");
        const uint4 xa = lds128(rsrc + off), xb = lds128(rsrc + off + 512), xc = lds128(rsrc + off + 1024), xd = lds128(rsrc + off + 1536);
        if (mode == 0) {
            if (pc) { dl = __shfl_sync(0xffffffff, dcur, didx); didx += 2; }
            cpa2p(wdst + off, sc.x); cpa2p(wdst + off + 512, sc.y);
        }
        if (mode == 1 && w < 16) {
#pragma unroll
            for (int j = 0; j < 4; j++) {
                const int kk = 4 * j + q, ch = 16 * (w & 7) + 2 * (kk & 7) + (kk >> 3);
                asm volatile("cp.async.cg.shared.global [%0], [%1], 16;" :: "r"(ring0 + kk * 128 + ((c ^ (kk & 7)) << 4)), "l"(w_mix + ch * 16 + (w >> 3) * 8 + c) : "memory");
            }
            asm volatile("cp.async.mbarrier.arrive.noinc.shared.b64 [%0];" :: "r"(mbarW) : "memory");
        }
        if (mode == 2 || mode == 3) {
#pragma unroll
            for (int j = 0; j < 4; j += mode - 1)
                asm volatile("cp.async.cg.shared.global [%0], [%1], 16;" :: "r"(ring0 + off + j * 512 + lane * 16), "l"(stash + (mode - 2) * 512 + j * 128 + lane * 3) : "memory");
        }
        if (mode < 4) asm volatile("cp.async.commit_group;" ::: "memory");
        float z[4], y[4], t1[4], t2[4];
        mma1688z(z, az.x, az.y, rc.y);
        mma1688z(y, az.z, az.w, rc.y);
        uint32_t bt;
        asm("{.reg .pred p; .reg .b32 m; and.b32 m, %2, %3; setp.ne.u32 p, m, 0; selp.b32 %0, %1, 0, p;}" : "=r"(bt) : "r"(rc.x), "r"(bits0), "r"(smask));
        mma1688z(t1, at[0], at[1], bt);
        mma1688z(t2, at[2], at[3], bt);
        const uint32_t T0 = pack2(t1[0], t1[2]), T1 = pack2(t2[0], t2[2]), T2 = pack2(t1[1], t1[3]), T3 = pack2(t2[1], t2[3]);
        uint32_t R[8];
#pragma unroll
        for (int i = 0; i < 4; i++) { R[i] = __float_as_uint(silu_h(z[i])); R[4 + i] = __float_as_uint(silu_h(y[i])); }
        mma16816(acc[0], mul_hi(xa.x, R[0]), mul_hi(xa.z, R[2]), mul_hi(xa.y, R[0]), mul_hi(xa.w, R[2]), T0, T1);
        mma16816(acc[1], mul_hi(xb.x, R[1]), mul_hi(xb.z, R[3]), mul_hi(xb.y, R[1]), mul_hi(xb.w, R[3]), T2, T3);
        mma16816(acc[2], mul_hi(xc.x, R[4]), mul_hi(xc.z, R[6]), mul_hi(xc.y, R[4]), mul_hi(xc.w, R[6]), T0, T1);
        mma16816(acc[3], mul_hi(xd.x, R[5]), mul_hi(xd.z, R[7]), mul_hi(xd.y, R[5]), mul_hi(xd.w, R[7]), T2, T3);
        mp += STEPB; smask <<= 1;
    };
    auto putacc = [&](uint32_t* p) {
#pragma unroll
        for (int i = 0; i < 16; i++) acc[i / 4][i % 4] *= 1.0028f;
        p[0] = pack2(acc[0][0], acc[0][1]); p[32] = pack2(acc[0][2], acc[0][3]); p[64] = pack2(acc[2][0], acc[2][1]); p[96] = pack2(acc[2][2], acc[2][3]);
        p[256] = pack2(acc[1][0], acc[1][1]); p[288] = pack2(acc[1][2], acc[1][3]); p[320] = pack2(acc[3][0], acc[3][1]); p[352] = pack2(acc[3][2], acc[3][3]);
    };
    int ph = 0;
    auto phase_end = [&](const int k) {
        az = lds128(sb + SM_AZ + (ph + 1) * 512 + lane * 16);
        putacc(stash + ph * ph * 128);
#pragma unroll
        for (int i = 0; i < 16; i++) acc[i / 4][i % 4] = 0.f;
        pbase += 256; mp = 0; smask = 1; ph++;
        dcur += tphase; didx = 1 + (k & 1);
        if (ph == 3) {
            mend -= DS * STEPB;
            if (FAN) dcur += (int)(dcur - __shfl_sync(0xffffffff, dcur, 0)) * (((w >> 2) - FANC) * FAN) >> 8;
        }
        WSTAMP(ph - 1);
    };
    uint32_t t0 = now;
    const bool reporter = w == PW && max(len2 & 0xFFFF, len2 >> 16) <= RLEN;
    if (reporter) {
        asm volatile("mov.u32 %0, %%globaltimer_lo;" : "=r"(now));
        now += PTOL - PTOL0;
    }
    const uint32_t bias = w == 0 ? 1u << 20 : 0;
    if (w == 0) relay();
    dcur += bias;
    auto body = [&](const int k) -> bool {
        if (k == 2) asm volatile("ld.volatile.shared.u32 %0, [%1+4];" : "=r"(t0) : "r"(flg));
        const bool pc = k & 1;
        step(k * SLOTB, 0, pc);
        if (!pc) {
            if (mp == mend) phase_end(k);
        } else if (mp == mend || now < dl) {
            if (mp == mend) {
                if (k == 3 && ph == 3) return true;
                phase_end(k);
            }
            if (w == 0) { dl -= 1u << 20; relay(); }
            wait_until(dl);
        }
        return false;
    };
    {
        const uint32_t d0 = __shfl_sync(0xffffffff, dreg, 0);
        if (w == 0) {
            uint32_t g0, tn; int spins = 0;
            do {
                asm volatile("ld.relaxed.gpu.global.u32 %0, [%2]; mov.u32 %1, %%globaltimer_lo;" : "=r"(g0), "=r"(tn) : "l"(&gs->t0) : "memory");
                if (g0 - t0 < 30000) { t0 = g0; flag[1] = g0; }
            } while (__shfl_sync(0xffffffff, t0 - tn, 0) < 32768 && ++spins < 64);
        }
        asm volatile("{.reg .pred p; .reg .u32 d;\n"
                     "PACE_LOOP: ld.volatile.shared.u32 %0, [%2+4]; mov.u32 d, %%globaltimer_lo; sub.u32 d, %1, d; add.u32 d, d, %0;\n"
                     "setp.lt.u32 p, d, 32768; @p nanosleep.u32 32; @p bra.uni PACE_LOOP;}"
                     : "=&r"(t0) : "r"(d0), "r"(flg) : "memory");
    }
    while (true) {
        if (reporter) {
            const uint32_t cand = now - dl + tcur - PTOL;
            if ((int)(cand - t0) > 0) report(cand);
        }
        dcur += t0 - tcur; tcur = t0;
        body(0); body(1); body(2);
        if (body(3)) break;
    }
    __syncwarp();
    step(0, 1);
    if (TDEL) { uint32_t tn; asm volatile("mov.u32 %0, %%globaltimer_lo;" : "=r"(tn)); wait_until(tn + (w >> 2) * TDEL); }
    step(SLOTB, 2); step(2 * SLOTB, 3); step(3 * SLOTB, 4);
    WSTAMP(3); ESTAMP(0);

    {
        putacc((uint32_t*)(smem + SM_RING + 2 * SLOTB + w * 2048 + 512) + lane);
        const int wg = w >> 2, w4 = w & 3;
        int nd[8];
#pragma unroll
        for (int j = 0; j < 8; j++) { const int l = wg * 8 + j; nd[j] = order[(t >> 1) ? 79 - l : l]; asm volatile("" : "+r"(nd[j])); }
        const bool odd = t & 1;
        uint2* ob = (uint2*)out + (size_t)n0 * 128 + w4 * 16 + g + (odd ? 8 : 0);
        asm volatile("cp.async.wait_all;" ::: "memory");
        mbar_wait(mbarW, 0);
        asm volatile("fence.proxy.async.shared::cta;" ::: "memory");
        ESTAMP(1);
        if (!ONEBAR) bar_sync(2 + wg, 128);
        uint32_t ticket = 0;
        if ((tid & 127) == 0) {
            asm volatile("atom.shared.add.u32 %0, [%1+48], 1;" : "=r"(ticket) : "r"(flg) : "memory");
            int spins = 0;
            while (flag[13] + LEAD < ticket && ++spins < (1 << 16)) { if (SPINS) __nanosleep(SPINS); }
        }
        bar_sync(2 + wg, 128);
        const uint64_t descA0 = (uint64_t)(((sb + SM_RING) & 0x3FFFF) >> 4) | ((uint64_t)1 << 16) | ((uint64_t)(1024 >> 4) << 32) | ((uint64_t)1 << 62);
        const uint64_t descB0 = (uint64_t)(((sb + SM_RING + SLOTB + wg * 8192) & 0x3FFFF) >> 4) | ((uint64_t)(128 >> 4) << 16) | ((uint64_t)(1024 >> 4) << 32);
        auto release = [&]() { asm volatile("{.reg .pred p; setp.eq.u32 p, %1, 0; @p st.volatile.shared.u32 [%0+52], %2;}" :: "r"(flg), "r"(tid & 127), "r"(ticket + 1) : "memory"); };
        float d[2][32];
        asm volatile("wgmma.fence.sync.aligned;" ::: "memory");
        ESTAMP(2);
#pragma unroll
        for (int i1 = 0; i1 < 2; i1++) {
#pragma unroll
            for (int i0 = 0; i0 < 8; i0++) {
                const int mt = ILV ? i0 & 1 : i1, ks = ILV ? i1 * 4 + (i0 >> 1) : i0;
                if (i1 * 8 + i0 == RELK) release();
                const uint64_t da = descA0 + (uint64_t)((ks * 2048 + mt * 16384) >> 4), db = descB0 + (uint64_t)(((ks & 3) * 256 + (ks >> 2) * SLOTB) >> 4);
                asm volatile("{.reg .pred p; setp.ne.b32 p, %34, 0;\n"
                    "wgmma.mma_async.sync.aligned.m64n64k16.f32.bf16.bf16 "
                    "{%0,%1,%2,%3,%4,%5,%6,%7,%8,%9,%10,%11,%12,%13,%14,%15,%16,%17,%18,%19,%20,%21,%22,%23,%24,%25,%26,%27,%28,%29,%30,%31}, %32, %33, p, 1, 1, 1, 1;}"
                    : "+f"(d[mt][0]), "+f"(d[mt][1]), "+f"(d[mt][2]), "+f"(d[mt][3]), "+f"(d[mt][4]), "+f"(d[mt][5]), "+f"(d[mt][6]), "+f"(d[mt][7]),
                      "+f"(d[mt][8]), "+f"(d[mt][9]), "+f"(d[mt][10]), "+f"(d[mt][11]), "+f"(d[mt][12]), "+f"(d[mt][13]), "+f"(d[mt][14]), "+f"(d[mt][15]),
                      "+f"(d[mt][16]), "+f"(d[mt][17]), "+f"(d[mt][18]), "+f"(d[mt][19]), "+f"(d[mt][20]), "+f"(d[mt][21]), "+f"(d[mt][22]), "+f"(d[mt][23]),
                      "+f"(d[mt][24]), "+f"(d[mt][25]), "+f"(d[mt][26]), "+f"(d[mt][27]), "+f"(d[mt][28]), "+f"(d[mt][29]), "+f"(d[mt][30]), "+f"(d[mt][31])
                    : "l"(da), "l"(db), "r"(ks));
            }
            asm volatile("wgmma.commit_group.sync.aligned;" ::: "memory");
        }
        if (RELK == 16) release();
#pragma unroll
        for (int mt = 0; mt < 2; mt++) {
            if (mt == 0 && !ILV) asm volatile("wgmma.wait_group.sync.aligned 1;" ::: "memory");
            else asm volatile("wgmma.wait_group.sync.aligned 0;" ::: "memory");
            if (RELK == 17 + mt) release();
            ESTAMP(3 + mt);
#pragma unroll
            for (int i = 0; i < 32; i++) asm volatile("" : "+f"(d[mt][i]) :: "memory");
#pragma unroll
            for (int j = 0; j < 8; j++) {
                const uint32_t v0 = pack2(d[mt][4 * j], d[mt][4 * j + 1]), v1 = pack2(d[mt][4 * j + 2], d[mt][4 * j + 3]);
                const uint32_t rv = __shfl_xor_sync(0xffffffff, odd ? v0 : v1, 1);
                if (nd[j] < nn) ob[nd[j] * 128 + mt * 64] = odd ? make_uint2(rv, v1) : make_uint2(v0, rv);
            }
        }
    }
    TSTAMP(8); ESTAMP(5);
}

}

extern "C" void kernel_launch(void* const* d_in, const int* in_sizes, int n_in, void* d_out, int out_size) {
    (void)in_sizes; (void)n_in; (void)out_size;
    cudaFuncSetAttribute(tfn_kernel, cudaFuncAttributeMaxDynamicSharedMemorySize, SM_TOTAL);
    Scratch* gs = nullptr;
    cudaGetSymbolAddress((void**)&gs, g_scratch);
    cudaLaunchConfig_t cfg = {};
    cfg.gridDim = dim3(NB); cfg.blockDim = dim3(NT); cfg.dynamicSmemBytes = SM_TOTAL; cfg.stream = cudaStreamPerThread;
    cudaLaunchAttribute at[1];
    at[0].id = cudaLaunchAttributeCooperative; at[0].val.cooperative = 1;
    cfg.attrs = at; cfg.numAttrs = 1;
    cudaLaunchKernelEx(&cfg, tfn_kernel, (const unsigned char*)d_in[0], (const int4*)d_in[1], (const int4*)d_in[2],
                       (const uint4*)d_in[3], (const uint4*)d_in[4], (const uint16_t*)d_in[5], (const uint16_t*)d_in[6],
                       (const uint4*)d_in[7], (uint32_t*)d_out, gs);
}
```

```cpp
#include <cuda_runtime.h>
#include <cuda_bf16.h>
#include <stdint.h>

namespace {

constexpr int NN = 10000;
constexpr int NE = 320000;
constexpr int NB = 132;
constexpr int NW = 20;
constexpr int NT = NW * 32;
constexpr int CW = NW - 1;
#define PWARP 10
constexpr int PW = PWARP;
constexpr int RW = 1;
constexpr int NPB = 76;
constexpr int CELL = 48;
constexpr int RCH = 2880;
constexpr int CAP = 19;
constexpr int DS = 4;
constexpr int STEPB = 160;
constexpr int NE4 = NE / 4;
constexpr int NPIECE = NB * 8;
constexpr int KB = 320, KN = 32 * KB;
constexpr uint32_t F_PAD = 0x80000000u;
constexpr uint32_t F_WRAP = 1;

constexpr int SLOTB = NW * 2048;
constexpr int SM_RING = 0;
constexpr int SM_META = SM_RING + DS * SLOTB;
constexpr int SM_AZ = SM_META + NW * CAP * STEPB;
constexpr int SM_MISC = SM_AZ + 2048;
constexpr int SM_TOTAL = SM_MISC + 2048;
constexpr int SM_STAGE = SM_RING;
constexpr int SM_HIST = SM_RING + 25600;
constexpr int SM_POS = SM_RING;
constexpr int SM_SMALL = SM_HIST + 13056;
constexpr int SM_LIST = SM_RING + SLOTB;
constexpr int SM_ROUT = SM_RING + 2 * SLOTB;
constexpr int SM_RECS = SM_RING + 3 * SLOTB;
constexpr int SM_RAWY = SM_META;
constexpr int SM_RAWE = SM_RAWY + 608 * 32;
constexpr int SM_KEYS = SM_RAWE + 608 * 32;
static_assert(SM_TOTAL <= 232448 && SM_KEYS + NPIECE * 16 <= SM_AZ, "smem");
static_assert(SM_RECS + NB * CELL * 16 + 16 <= SM_AZ && SM_KEYS + NPIECE * 16 <= SM_RECS + NB * CELL * 16 && SM_SMALL + 1152 <= SLOTB && DS == 4, "smem");

struct Scratch {
    uint4 keys[NB * NPIECE];
    uint4 recs[NB * RCH];
    uint4 stash[NB * NW * 256];
    unsigned bar[2];
    unsigned long long t0;
};
__device__ Scratch g_scratch;
#define TSTAMP(i)
#define TSTAMPC(i)
#define WSTAMP(i)
#define ESTAMP(i)

__device__ __forceinline__ void mma16816(float* d, uint32_t a0, uint32_t a1, uint32_t a2, uint32_t a3, uint32_t b0, uint32_t b1) {
    asm("mma.sync.aligned.m16n8k16.row.col.f32.bf16.bf16.f32 {%0,%1,%2,%3}, {%4,%5,%6,%7}, {%8,%9}, {%0,%1,%2,%3};"
        : "+f"(d[0]), "+f"(d[1]), "+f"(d[2]), "+f"(d[3]) : "r"(a0), "r"(a1), "r"(a2), "r"(a3), "r"(b0), "r"(b1));
}
__device__ __forceinline__ void mma1688z(float* d, uint32_t a0, uint32_t a1, uint32_t b0) {
    asm("mma.sync.aligned.m16n8k8.row.col.f32.bf16.bf16.f32 {%0,%1,%2,%3}, {%4,%5}, {%6}, {%7,%7,%7,%7};"
        : "=f"(d[0]), "=f"(d[1]), "=f"(d[2]), "=f"(d[3]) : "r"(a0), "r"(a1), "r"(b0), "f"(0.f));
}
__device__ __forceinline__ uint32_t pack2(float lo, float hi) {
    uint32_t r; asm("cvt.rn.bf16x2.f32 %0, %1, %2;" : "=r"(r) : "f"(hi), "f"(lo)); return r;
}
__device__ __forceinline__ float silu_h(float h) {
    float t; asm("tanh.approx.f32 %0, %1;" : "=f"(t) : "f"(h)); return fmaf(h, t, h);
}
__device__ __forceinline__ uint32_t mul_lo(uint32_t v, uint32_t r) {
    __nv_bfloat162 a = *(__nv_bfloat162*)&v, b = *(__nv_bfloat162*)&r; __nv_bfloat162 c = __hmul2(a, __low2bfloat162(b)); return *(uint32_t*)&c;
}
__device__ __forceinline__ uint32_t mul_hi(uint32_t v, uint32_t r) {
    __nv_bfloat162 a = *(__nv_bfloat162*)&v, b = *(__nv_bfloat162*)&r; __nv_bfloat162 c = __hmul2(a, __high2bfloat162(b)); return *(uint32_t*)&c;
}
__device__ __forceinline__ uint32_t lds32(uint32_t a) {
    uint32_t r; asm volatile("ld.shared.u32 %0, [%1];" : "=r"(r) : "r"(a) : "memory"); return r;
}
__device__ __forceinline__ void sts32(uint32_t a, uint32_t v) { asm volatile("st.shared.u32 [%0], %1;" :: "r"(a), "r"(v) : "memory"); }
__device__ __forceinline__ uint2 lds64(uint32_t a) {
    uint2 r; asm volatile("ld.shared.v2.u32 {%0,%1}, [%2];" : "=r"(r.x), "=r"(r.y) : "r"(a)); return r;
}
__device__ __forceinline__ uint4 lds128(uint32_t a) {
    uint4 r; asm volatile("ld.shared.v4.u32 {%0,%1,%2,%3}, [%4];" : "=r"(r.x), "=r"(r.y), "=r"(r.z), "=r"(r.w) : "r"(a) : "memory"); return r;
}
__device__ __forceinline__ void bar_sync(int id, int n) { asm volatile("bar.sync %0, %1;" :: "r"(id), "r"(n) : "memory"); }
__device__ __forceinline__ void bar_arrive(int id, int n) { asm volatile("bar.arrive %0, %1;" :: "r"(id), "r"(n) : "memory"); }
__device__ __forceinline__ void mbar_wait(uint32_t bar, uint32_t ph) {
    uint32_t done; int spins = 0;
    do {
        asm volatile("{.reg .pred p; mbarrier.try_wait.parity.shared.b64 p, [%1], %2; selp.u32 %0,1,0,p;}" : "=r"(done) : "r"(bar), "r"(ph) : "memory");
    } while (!done && ++spins < (1 << 22));
}
__device__ __forceinline__ unsigned gbar_read(const unsigned* ctr) {
    unsigned v; asm volatile("ld.relaxed.gpu.global.u32 %0, [%1];" : "=r"(v) : "l"(ctr) : "memory");
    return v;
}
__device__ __forceinline__ void gbar_arrive(unsigned* ctr) {
    asm volatile("red.add.release.gpu.global.u32 [%0], 1;" :: "l"(ctr) : "memory");
}
__device__ __forceinline__ bool gbar_wait(const unsigned* ctr, unsigned target) {
    unsigned v; int spins = 0;
    while (true) {
        asm volatile("ld.acquire.gpu.global.u32 %0, [%1];" : "=r"(v) : "l"(ctr) : "memory");
        if ((int)(v - target) >= 0 || ++spins > (1 << 22)) break;
    }
    return (int)(v - target) >= 0;
}
__device__ __forceinline__ int chunk_start4(int c) { return (c * NE4) / NB; }
__device__ __forceinline__ float bf2f(uint32_t h) { return __uint_as_float(h << 16); }

__device__ __noinline__ void slow_path(unsigned char* smem, int n0, int nn, const uint16_t* x, const int* src, const int* dst,
                                       const uint16_t* Y, const uint16_t* ef, const uint16_t* w_rad, const uint16_t* cg,
                                       const uint16_t* w_mix, __nv_bfloat16* out) {
    float* agg = (float*)smem;
    const int tid = threadIdx.x, lane = tid & 31, w = tid >> 5;
    bar_sync(1, NT);
    for (int i = tid; i < NPB * 512; i += NT) agg[i] = 0.f;
    bar_sync(1, NT);
    for (int e0 = w * 32; e0 < NE; e0 += NT) {
        int dl = dst[e0 + lane] - n0;
        unsigned m = __ballot_sync(0xffffffff, dl >= 0 && dl < nn);
        while (m) {
            int l = __ffs(m) - 1; m &= m - 1;
            int e = e0 + l, d = __shfl_sync(0xffffffff, dl, l), s = src[e];
            float T[16];
            for (int i = 0; i < 4; i++) for (int o = 0; o < 4; o++) {
                float a = 0.f;
                for (int f = 0; f < 4; f++) a += bf2f(Y[e * 4 + f]) * bf2f(cg[i * 16 + f * 4 + o]);
                T[i * 4 + o] = a;
            }
            for (int k = 0; k < 4; k++) {
                int c = lane + 32 * k;
                float z = 0.f;
                for (int j = 0; j < 4; j++) z += bf2f(ef[e * 4 + j]) * bf2f(w_rad[j * 128 + c]);
                float R = z / (1.f + __expf(-z));
                for (int o = 0; o < 4; o++) {
                    float a = 0.f;
                    for (int i = 0; i < 4; i++) a += bf2f(x[(size_t)s * 512 + c * 4 + i]) * T[i * 4 + o];
                    atomicAdd(&agg[d * 512 + c * 4 + o], R * a);
                }
            }
        }
    }
    bar_sync(1, NT);
    for (int i = tid; i < nn * 512; i += NT) {
        int n = i >> 9, d = (i >> 2) & 127, o = i & 3;
        float a = 0.f;
        for (int c = 0; c < 128; c++) a += agg[n * 512 + c * 4 + o] * bf2f(w_mix[c * 128 + d]);
        out[(size_t)(n0 + n) * 512 + (i & 511)] = __float2bfloat16(a);
    }
}

#define PACE 23000
#define YDELAY 300
#define POFF 3600
#define PSLEEP 32
#define RLEN 99
#define FDT 350
#define FOFF 1500
#define FSTAG 0
#define RELK 12
#define ILV 0
#define SPINS 40
#define ONEBAR 0
#define LEAD 0
#define FAN 16
#define FANC 2
#define TDEL 100
#define RDY 600
#define XPF 48
#define PTOL0 300
#define PTOL 1100
__global__ void __launch_bounds__(NT, 1)
tfn_kernel(const unsigned char* __restrict__ x, const int4* __restrict__ src4, const int4* __restrict__ dst4,
           const uint4* __restrict__ Y, const uint4* __restrict__ ef, const uint16_t* __restrict__ w_rad,
           const uint16_t* __restrict__ cg, const uint4* __restrict__ w_mix, uint32_t* __restrict__ out, Scratch* __restrict__ gs) {
    extern __shared__ __align__(1024) unsigned char smem[];
    const uint32_t sb = (uint32_t)__cvta_generic_to_shared(smem);
    const int b = blockIdx.x, tid = threadIdx.x, lane = tid & 31, g = lane >> 2, t = lane & 3;
    const int w = __shfl_sync(0xffffffff, tid >> 5, 0);
    uint32_t* stage = (uint32_t*)(smem + SM_STAGE);
    uint32_t* hist = (uint32_t*)(smem + SM_HIST);
    uint32_t* cnt = (uint32_t*)(smem + SM_MISC);
    uint32_t* deg = cnt + 136;
    uint32_t* order = deg + 104;
    uint32_t* cnt2 = order + 80;
    volatile uint32_t* flag = cnt2 + 136;
    const uint32_t mbarK = sb + SM_MISC + 1920, mbarR = mbarK + 8, mbarW = mbarK + 16;
    const int n0 = b * NPB, nn = min(NPB, NN - n0);
    TSTAMP(0);

    const int c0 = chunk_start4(b), c1 = chunk_start4(b + 1);
    const bool has4 = c0 + tid < c1;
    int4 d4 = make_int4(0, 0, 0, 0), s4 = d4;
    if (has4) { d4 = __ldg(dst4 + c0 + tid); s4 = __ldg(src4 + c0 + tid); }
    unsigned tgt = 0;
    if (tid == NT - 1) {
        tgt = gbar_read(&gs->bar[0]);
        asm volatile("mbarrier.init.shared.b64 [%0], 1;" :: "r"(mbarK));
        asm volatile("mbarrier.init.shared.b64 [%0], 1;" :: "r"(mbarR));
        asm volatile("mbarrier.init.shared.b64 [%0], 512;" :: "r"(mbarW));
        asm volatile("fence.mbarrier_init.release.cluster;" ::: "memory");
        flag[0] = 0; flag[12] = 0; flag[13] = 0; flag[15] = 0;
    }
    if (w == CW) {
        asm volatile("cp.async.cg.shared.global [%0], [%1], 16;" :: "r"(sb + SM_SMALL + lane * 16), "l"(w_rad + lane * 8) : "memory");
        asm volatile("cp.async.cg.shared.global [%0], [%1], 16;" :: "r"(sb + SM_SMALL + 512 + lane * 16), "l"(w_rad + 256 + lane * 8) : "memory");
        if (lane < 8) asm volatile("cp.async.cg.shared.global [%0], [%1], 16;" :: "r"(sb + SM_SMALL + 1024 + lane * 16), "l"(cg + lane * 8) : "memory");
    }
    ((uint4*)hist)[tid] = make_uint4(0, 0, 0, 0);
    {
        const uint32_t dk = (80 + b % 22) * KN + (b & 31) * KB;
#pragma unroll
        for (int j = 0; j < 3; j++) if (tid + j * NT < NB * CELL / 4) ((uint4*)stage)[tid + j * NT] = make_uint4(dk, dk, dk, dk);
    }
    if (tid < 136) cnt[tid] = 0;
    if (tid == 0) { *(uint4*)(smem + SM_MISC + 1824 + 32) = make_uint4(0, 0, 0, 0); *(uint4*)(smem + SM_RECS + NB * CELL * 16) = make_uint4(0, 0, 0, 0); }
    if (tid < 80) { deg[tid] = 127 - tid; order[tid] = tid; }
    __syncthreads();
    TSTAMP(9);
    if (tid == 64) {
        if (YDELAY) __nanosleep(YDELAY);
        asm volatile("mbarrier.arrive.expect_tx.shared.b64 _, [%0], %1;" :: "r"(mbarR), "r"((c1 - c0) * 64) : "memory");
        asm volatile("cp.async.bulk.shared::cluster.global.mbarrier::complete_tx::bytes [%0], [%1], %2, [%3];"
                     :: "r"(sb + SM_RAWY), "l"(Y + 2 * c0), "r"((c1 - c0) * 32), "r"(mbarR) : "memory");
        asm volatile("cp.async.bulk.shared::cluster.global.mbarrier::complete_tx::bytes [%0], [%1], %2, [%3];"
                     :: "r"(sb + SM_RAWE), "l"(ef + 2 * c0), "r"((c1 - c0) * 32), "r"(mbarR) : "memory");
    }

    uint32_t bin[4] = {0, 0, 0, 0}, slot[4] = {0, 0, 0, 0};
    if (has4) {
        const uint32_t dd[4] = {(uint32_t)d4.x, (uint32_t)d4.y, (uint32_t)d4.z, (uint32_t)d4.w}, ss[4] = {(uint32_t)s4.x, (uint32_t)s4.y, (uint32_t)s4.z, (uint32_t)s4.w};
#pragma unroll
        for (int k = 0; k < 4; k++) { bin[k] = dd[k] / NPB; slot[k] = atomicAdd(&cnt[bin[k]], 1); }
#pragma unroll
        for (int k = 0; k < 4; k++) stage[bin[k] * CELL + min(slot[k], CELL - 1)] = (dd[k] - bin[k] * NPB) * KN + ss[k];
    }
    if (w == CW) {
        if (tid == NT - 1) { tgt = tgt / NB + 1; flag[14] = (tgt & 1) << 31; tgt *= NB; }
        asm volatile("cp.async.wait_all;" ::: "memory");
    }
    bar_sync(1, NT);
    TSTAMP(1);
    const uint32_t tag = flag[14];
#pragma unroll
    for (int j = 0; j < 2; j++) {
        const int i = tid + j * NT;
        if (i < NPIECE) {
            const uint2 sa = *(const uint2*)(stage + i * 6), sc = *(const uint2*)(stage + i * 6 + 2);
            uint2 se = *(const uint2*)(stage + i * 6 + 4);
            const uint32_t cf = cnt[i >> 3], cn = min(cf, 63u);
            if ((i & 7) == 7) {
                const uint32_t al = cf > CELL - 8 ? 7 : 0;
                uint32_t o;
                asm volatile("atom.shared.add.u32 %0, [%1], %2;" : "=r"(o) : "r"(sb + SM_MISC + 1824 + 60), "r"(cf + al) : "memory");
                se.y = (o + al) & ~al;
                cnt2[i >> 3] = se.y;
            }
            asm volatile("{.reg .b64 lo, hi; mov.b64 lo, {%1,%2}; mov.b64 hi, {%3,%4}; st.relaxed.gpu.global.v2.b64 [%0], {lo, hi};}"
                         :: "l"(gs->keys + ((i >> 3) * NB + b) * 8 + ((i ^ b) & 7)),
                            "r"(sa.x | (se.x << 20)), "r"(sa.y | ((se.x >> 12) << 20) | ((cn & 7) << 28) | tag),
                            "r"(sc.x | (se.y << 20)), "r"(sc.y | ((se.y >> 12) << 20) | ((cn >> 3) << 28) | tag) : "memory");
        }
    }
    bar_sync(1, NT);
    if (tid == NT - 1) {
        TSTAMPC(10);
        asm volatile("red.add.relaxed.gpu.global.u32 [%0], 1;" :: "l"(&gs->bar[0]) : "memory");
        asm volatile("mbarrier.arrive.expect_tx.shared.b64 _, [%0], %1;" :: "r"(mbarK), "r"(NPIECE * 16) : "memory");
        gbar_wait(&gs->bar[0], tgt);
        TSTAMPC(13);
        asm volatile("fence.proxy.async.global;" ::: "memory");
        asm volatile("cp.async.bulk.shared::cluster.global.mbarrier::complete_tx::bytes [%0], [%1], %2, [%3];"
                 :: "r"(sb + SM_KEYS), "l"(gs->keys + b * NPIECE), "r"(NPIECE * 16), "r"(mbarK) : "memory");
    }
    __syncwarp();
    uint32_t at[4];
    {
        const int o = g & 3, f = 2 * (t & 1);
#pragma unroll
        for (int i = 0; i < 4; i++) {
            const uint16_t* cp = (const uint16_t*)(smem + SM_SMALL + 1024) + i * 16 + f * 4 + o;
            at[i] = (t >> 1) == (g >> 2) ? cp[0] | ((uint32_t)cp[4] << 16) : 0;
        }
    }

    const int q = lane >> 3, c = lane & 7;
    const uint32_t ring0 = sb + SM_RING + w * 2048;
    uint32_t wdst = ring0 + q * 128 + ((c + 2 * q) & 7) * 16;
    uint32_t rsrc = ring0 + t * 128 + ((g + 2 * t) & 7) * 16;
    uint32_t recl = sb + SM_META + w * (CAP * STEPB) + g * 16 + (t & 1) * 8, srcl = sb + SM_META + w * (CAP * STEPB) + 128 + q * 8;
    uint32_t flg = sb + SM_MISC + (136 + 104 + 80 + 136) * 4;
    asm volatile("" : "+r"(wdst), "+r"(rsrc), "+r"(recl), "+r"(srcl), "+r"(flg));
    auto setflag = [&]() { sts32(flg, 1); };
    uint32_t key[2][6], ha[2][6], rk[2][6], kidx[2], ka[2], kc[2];
    int nk[2];
#pragma unroll
    for (int j = 0; j < 2; j++) {
        const int i0 = j ? 2 * 608 - 1 - tid : tid, i = min(i0, NPIECE - 1), r = i / NB, cc = i - r * NB;
        ka[j] = sb + SM_KEYS + (cc * 8 + ((r ^ cc) & 7)) * 16;
        kidx[j] = (cc * CELL + r * 6) << 17;
        kc[j] = sb + SM_MISC + cc * 4;
        nk[j] = i0 < NPIECE && w < CW ? -6 * r : -1000;
    }
    asm volatile("" : "+r"(at[0]), "+r"(at[1]), "+r"(at[2]), "+r"(at[3]), "+r"(ka[0]), "+r"(ka[1]), "+r"(kidx[0]), "+r"(kidx[1]), "+r"(kc[0]), "+r"(kc[1]), "+r"(nk[0]), "+r"(nk[1]));
    if (w == CW) {
        __syncwarp();
        bar_sync(7, NT);
        if (tid == NT - 1) {
            TSTAMPC(11);
            asm volatile("cp.async.bulk.global.shared::cta.bulk_group [%0], [%1], %2;"
                         :: "l"(gs->recs + b * RCH), "r"(sb + SM_ROUT), "r"(((flag[15] + 1) & ~1u) * 16) : "memory");
            asm volatile("cp.async.bulk.commit_group;" ::: "memory");
            mbar_wait(mbarK, 0);
            unsigned long long tbase;
            asm volatile("mov.u64 %0, %%globaltimer;" : "=l"(tbase));
            tbase += POFF;
            flag[1] = (uint32_t)tbase; flag[4] = (uint32_t)tbase; flag[5] = (uint32_t)(tbase >> 32);
            asm volatile("red.max.relaxed.gpu.global.u64 [%0], %1;" :: "l"(&gs->t0), "l"(tbase) : "memory");
            if (b < 128) asm volatile("cp.async.bulk.prefetch.L2.global [%0], 256;" :: "l"(w_mix + b * 16));
            asm volatile("cp.async.bulk.wait_group 0;" ::: "memory");
            TSTAMPC(14);
            asm volatile("red.add.relaxed.gpu.global.u32 [%0], 1;" :: "l"(&gs->bar[1]) : "memory");
            TSTAMPC(15);
        }
    } else {
        if (w < 8) {
            const uint32_t* wp = (const uint32_t*)(smem + SM_SMALL) + (t & 1) * 128 + 8 * w + g;
            const uint32_t wr0 = t < 2 ? wp[0] : 0, wr1 = t < 2 ? wp[64] : 0;
            *(uint2*)(smem + SM_AZ + (w >> 1) * 512 + lane * 16 + (w & 1) * 8) =
                make_uint2(pack2(0.5f * bf2f(wr0 & 0xFFFF), 0.5f * bf2f(wr1 & 0xFFFF)), pack2(0.5f * bf2f(wr0 >> 16), 0.5f * bf2f(wr1 >> 16)));
        }
        const bool sw = g & 1;
        uint32_t rp[4];
#pragma unroll
        for (int k = 0; k < 4; k++) rp[k] = cnt2[bin[k]] + slot[k];
        uint4* ro = (uint4*)(smem + SM_ROUT);
        uint4 *p0 = ro + (sw ? rp[2] : rp[0]), *p1 = ro + (sw ? rp[3] : rp[1]), *p2 = ro + (sw ? rp[0] : rp[2]), *p3 = ro + (sw ? rp[1] : rp[3]);
        const uint32_t ya = sb + SM_RAWY + tid * 32 + (sw ? 16 : 0);
        mbar_wait(mbarR, 0);
        TSTAMP(18);
        if (has4) {
            const uint4 y0 = lds128(ya), e0 = lds128(ya + (SM_RAWE - SM_RAWY)), y1 = lds128(ya ^ 16), e1 = lds128((ya ^ 16) + (SM_RAWE - SM_RAWY));
            *p0 = make_uint4(y0.x, e0.x, y0.y, e0.y); *p1 = make_uint4(y0.z, e0.z, y0.w, e0.w);
            *p2 = make_uint4(y1.x, e1.x, y1.y, e1.y); *p3 = make_uint4(y1.z, e1.z, y1.w, e1.w);
        }
        asm volatile("fence.proxy.async.shared::cta;" ::: "memory");
        bar_arrive(7, NT);
        if (XPF && tid >= 512 && tid < 512 + 2 * XPF)
            asm volatile("prefetch.global.L2 [%0];" :: "l"(x + (size_t)(b * XPF + ((tid - 512) >> 1)) * 1024 + (tid & 1) * 128));
    }
    __syncwarp();
    TSTAMP(2);

    if (w < CW) {
        mbar_wait(mbarK, 0);
        TSTAMP(3);
        uint4 v[2] = {lds128(ka[0]), lds128(ka[1])};
        if ((int)((v[0].y ^ tag) | (v[0].w ^ tag) | (v[1].y ^ tag) | (v[1].w ^ tag)) < 0) {
#pragma unroll
            for (int j = 0; j < 2; j++) {
                int spins = 0;
#pragma unroll 1
                while ((int)((v[j].y ^ tag) | (v[j].w ^ tag)) < 0) {
                    asm volatile("{.reg .b64 lo, hi; ld.relaxed.gpu.global.v2.b64 {lo, hi}, [%4]; mov.b64 {%0,%1}, lo; mov.b64 {%2,%3}, hi;}"
                                 : "=r"(v[j].x), "=r"(v[j].y), "=r"(v[j].z), "=r"(v[j].w) : "l"((const unsigned char*)(gs->keys + b * NPIECE) + (ka[j] - sb - SM_KEYS)) : "memory");
                    if (++spins > (1 << 20)) { setflag(); break; }
                }
            }
        }
#pragma unroll
        for (int j = 0; j < 2; j++) {
            const uint32_t hc = ((v[j].y >> 28) & 7) | ((v[j].w >> 25) & 0x38);
            if (j == 1 && nk[j] == -42) {
                sts32(kc[j], hc | ((v[j].z >> 20) << 8));
                if (hc > CELL - 1) setflag();
                v[j].w |= ((80 * KN) >> 12) << 20;
            }
            nk[j] += hc;
            if (nk[j] > 0) {
                key[j][0] = v[j].x & 0xFFFFF; key[j][1] = v[j].y & 0xFFFFF; key[j][2] = v[j].z & 0xFFFFF; key[j][3] = v[j].w & 0xFFFFF;
                key[j][4] = (v[j].x >> 20) | ((v[j].y >> 8) & 0xFF000); key[j][5] = (v[j].z >> 20) | ((v[j].w >> 8) & 0xFF000);
#pragma unroll
                for (int u = 0; u < 6; u++) {
                    ha[j][u] = __umulhi(key[j][u], 0xFFFFFFFFu / KB + 1);
                    asm volatile("{.reg .u32 a, n; mad.lo.u32 a, %1, 4, %2; atom.shared.add.u32 %0, [a+%3], 1;\n"
                                 "shr.u32 n, %1, 5; mad.lo.u32 a, n, 4, %2; red.shared.add.u32 [a+%4], 128;}"
                                 : "=r"(rk[j][u]) : "r"(ha[j][u]), "r"(sb), "n"(SM_HIST), "n"(SM_MISC + 136 * 4) : "memory");
                }
            }
        }
        bar_sync(9, NT - 32);
        TSTAMP(20);
        const int n = tid >> 3, sub = tid & 7;
        const uint32_t me = deg[n];
        uint32_t r = 0, r2 = 0;
#pragma unroll
        for (int k = 0; k < 5; k++) { const uint2 dd = *(const uint2*)(deg + sub * 10 + 2 * k); r += (me - dd.x) >> 31; r2 += (me - dd.y) >> 31; }
        r += r2;
#pragma unroll
        for (int j = 0; j < 2; j++) kidx[j] += (lds32(kc[j]) & 0x700) << 9;
        r += __shfl_xor_sync(0xffffffff, r, 1); r += __shfl_xor_sync(0xffffffff, r, 2); r += __shfl_xor_sync(0xffffffff, r, 4);
        if (sub == 0) order[r] = n;
    }
    bar_sync(1, NT);
    TSTAMP(22);
    uint32_t len2;
    {
        const uint2 na = *(const uint2*)(order + 2 * w);
        uint2 nb = *(const uint2*)(order + 78 - 2 * w);
        const uint32_t hl = sb + SM_HIST + lane * 4;
        const uint32_t ha0 = lds32(hl + na.x * 128), ha1 = lds32(hl + na.y * 128), hb0 = lds32(hl + nb.y * 128), hb1 = lds32(hl + nb.x * 128);
        if (deg[na.x] >= (4 * CAP + 1) * 128) setflag();
        const uint32_t ca = ha0 + (ha1 << 16), c4 = ca + (hb0 << 8) + (hb1 << 24);
        uint32_t inc = c4;
#pragma unroll
        for (int o = 1; o < 32; o <<= 1)
            asm volatile("{.reg .pred p; .reg .u32 u; shfl.sync.up.b32 u|p, %0, %1, 0, 0xffffffff; @p add.u32 %0, %0, u;}" : "+r"(inc) : "r"(o));
        const int su = __reduce_add_sync(0xffffffff, (int)(ha0 - ha1) * (2 * lane - 31)), sv = __reduce_add_sync(0xffffffff, (int)(hb0 - hb1) * (2 * lane - 31));
        const bool swp = (su ^ sv) >= 0;
        if (swp) { nb = make_uint2(nb.y, nb.x); *(uint2*)(order + 78 - 2 * w) = nb; }
        const uint32_t sel = swp ? 0x4143 : 0x4341, ex = inc - c4;
        const uint32_t ea = (ex & 0x00FF00FF) + __byte_perm(ex, 0, sel), eb = ea + ca, base = sb + SM_LIST + w * 2048;
        uint2* pos = (uint2*)(smem + SM_POS) + lane;
        pos[na.x * 32] = make_uint2(base + (ea & 0xFFFF) * 8, na.x * (0u - 4 * KN));
        pos[nb.y * 32] = make_uint2(base + (eb & 0xFFFF) * 8, nb.y * (0u - 4 * KN) + 0x80000000u);
        pos[na.y * 32] = make_uint2(base + 4 + (ea >> 16) * 8, na.y * (0u - 4 * KN));
        pos[nb.x * 32] = make_uint2(base + 4 + (eb >> 16) * 8, nb.x * (0u - 4 * KN) + 0x80000000u);
        len2 = __shfl_sync(0xffffffff, (inc & 0x00FF00FF) + __byte_perm(inc, 0, sel), 31);
        if (max(len2 & 0xFFFF, len2 >> 16) > 4 * CAP) setflag();
    }
    uint32_t ci = cnt[min(w + NW * lane, NB)];
    ci = (((ci & 0xFF) + ((ci >> 8) & 7)) << 24) + min(w + NW * lane, NB) * (RCH / 8) + (ci >> 11);
    if (w == CW) {
        bar_arrive(9, NT);
        if (tid == NT - 1) {
            uint32_t v1, g0; int spins = 0;
            do {
                asm volatile("ld.relaxed.gpu.global.u32 %1, [%2+8]; ld.acquire.gpu.global.u32 %0, [%2+4];" : "=r"(v1), "=r"(g0) : "l"(gs->bar) : "memory");
            } while ((int)(v1 - tgt) < 0 && ++spins < (1 << 22));
            if ((int)(v1 - tgt) < 0) *flag = 1;
            if (g0 - flag[1] < 30000) flag[1] = g0;
            TSTAMPC(17);
        }
        __syncwarp();
    } else {
        bar_sync(9, NT);
        TSTAMP(21);
        const uint32_t over = lds32(flg);
#pragma unroll
        for (int j = 0; j < 2; j++) {
            if (nk[j] > 0) {
                uint2 h[6];
#pragma unroll
                for (int u = 0; u < 6; u++) h[u] = lds64(sb + SM_POS + ha[j][u] * 8);
                if (over) nk[j] = 0;
#pragma unroll
                for (int u = 0; u < 6; u++)
                    asm volatile("{.reg .pred p; setp.gt.s32 p, %2, %3; @p st.shared.u32 [%0], %1;}"
                                 :: "r"(h[u].x + rk[j][u] * 8), "r"(key[j][u] * 4 + h[u].y + (kidx[j] + (u << 17))), "r"(nk[j]), "r"(u) : "memory");
            }
        }
    }
    bar_sync(1, NT);
    TSTAMP(4);
    if (*flag) {
        slow_path(smem, n0, nn, (const uint16_t*)x, (const int*)src4, (const int*)dst4, (const uint16_t*)Y, (const uint16_t*)ef, w_rad, cg,
                  (const uint16_t*)w_mix, (__nv_bfloat16*)out);
        return;
    }
    {
        const uint4* gp = gs->recs + lane;
        asm volatile("" : "+l"(gp));
        const uint32_t sp = sb + SM_RECS + (w * CELL + lane) * 16, lc = (lane << 24) | 0xFFFFFF;
#pragma unroll
        for (int j = 0; j < 7; j++)
            asm volatile("{.reg .pred p; .reg .u32 l; .reg .u64 a; setp.lt.u32 p, %2, %3; and.b32 l, %3, 0xFFFF; mad.wide.u32 a, l, 128, %1;\n"
                         "@p cp.async.cg.shared.global [%0], [a], 16;}"
                         :: "r"(sp + j * (NW * CELL * 16)), "l"(gp), "r"(lc), "r"(__shfl_sync(0xffffffff, ci, j)) : "memory");
        for (uint32_t m = __ballot_sync(0xffffffff, ci >= (33u << 24)); m; m &= m - 1) {
            const int j = __ffs(m) - 1;
            const uint32_t cj = __shfl_sync(0xffffffff, ci, j);
            if (lane + 32 < (cj >> 24))
                asm volatile("cp.async.cg.shared.global [%0], [%1], 16;" :: "r"(sp + j * (NW * CELL * 16) + 512), "l"(gp + (size_t)(cj & 0xFFFF) * 8 + 32) : "memory");
        }
        asm volatile("cp.async.commit_group;" ::: "memory");
    }
    const int S = __shfl_sync(0xffffffff, max((int)(max(len2 & 0xFFFF, len2 >> 16) + 3) >> 2, DS + 1), 0);
    const int mylen = (lane & 1) ? len2 >> 16 : len2 & 0xFFFF;
    constexpr int NRAW = (CAP + 3) / 4;
    uint32_t bits0 = 0, raw[NRAW];
    unsigned char* meta = smem + SM_META + w * (CAP * STEPB);
    const int la = sb + SM_LIST + w * 2048 + lane * 4, llast = la - (lane & ~1) * 4 + (mylen - 1) * 8;
#pragma unroll
    for (int k = 0; k < NRAW; k++) raw[k] = lds32(min(la + k * 128, llast));
    const uint32_t sv0 = min(raw[0] & 0xFFFC, 4 * (NN - 1));
    const unsigned char* pbase = x + c * 16;
    asm volatile("" : "+l"(pbase));
    auto cpa2 = [&](uint32_t dstp, uint32_t sv) {
        asm volatile("cp.async.cg.shared.global [%0], [%1], 16; cp.async.cg.shared.global [%0+1024], [%1+128], 16;"
                     :: "r"(dstp), "l"(pbase + (size_t)sv * 256) : "memory");
    };
    auto cpa2p = [&](uint32_t dstp, uint32_t sv) {
        asm volatile("{.reg .pred p; setp.ge.s32 p, %2, 0; @p cp.async.cg.shared.global [%0], [%1], 16; @p cp.async.cg.shared.global [%0+1024], [%1+128], 16;}"
                     :: "r"(dstp), "l"(pbase + (size_t)sv * 256), "r"(sv) : "memory");
    };
    auto wait_until = [&](uint32_t tt) {
        asm volatile("{.reg .pred p; .reg .u32 d;\n"
                     "PACE_LOOP: mov.u32 d, %%globaltimer_lo; sub.u32 d, %0, d; setp.lt.u32 p, d, 32768; @p nanosleep.u32 %1; @p bra.uni PACE_LOOP;}"
                     :: "r"(tt), "n"(PSLEEP) : "memory");
    };
    const uint32_t tfill = flag[1] - FOFF + w * FSTAG;
    auto fill = [&](int i) {
        if (FDT) wait_until(tfill + i * FDT);
        cpa2(wdst + i * SLOTB, __shfl_sync(0xffffffff, sv0, 8 * i + 2 * q)); cpa2(wdst + i * SLOTB + 512, __shfl_sync(0xffffffff, sv0, 8 * i + 2 * q + 1));
        asm volatile("cp.async.commit_group;" ::: "memory");
    };
    fill(0);
    TSTAMP(5);
    auto relay = [&]() {
        uint32_t g0, g1, b0, b1;
        asm volatile("ld.volatile.shared.v2.u32 {%0,%1}, [%4+40]; ld.volatile.shared.v2.u32 {%2,%3}, [%4+16];"
                     : "=r"(g0), "=r"(g1), "=r"(b0), "=r"(b1) : "r"(flg) : "memory");
        const unsigned long long dg = (((unsigned long long)g1 << 32) | g0) - (((unsigned long long)b1 << 32) | b0);
        asm volatile("{.reg .pred p, q; setp.eq.u32 p, %1, 0; setp.lt.u64 q, %2, 30000; @q st.shared.u32 [%3+4], %4;\n"
                     "@p cp.async.cg.shared.global [%3+32], [%0], 16;}"
                     :: "l"(gs->bar), "r"(lane), "l"(dg), "r"(flg), "r"(g0) : "memory");
    };
    auto report = [&](uint32_t cand) {
        uint32_t b0, b1;
        asm volatile("ld.volatile.shared.v2.u32 {%0,%1}, [%2+16];" : "=r"(b0), "=r"(b1) : "r"(flg) : "memory");
        asm volatile("{.reg .pred p; setp.eq.u32 p, %2, 0; @p red.max.relaxed.gpu.global.u64 [%0], %1;}"
                     :: "l"(&gs->t0), "l"((((unsigned long long)b1 << 32) | b0) + (cand - b0)), "r"(lane) : "memory");
    };
    uint32_t ra[NRAW];
#pragma unroll
    for (int k = NRAW - 1; k >= 0; k--) {
        const uint32_t m = (__ballot_sync(0xffffffff, (int)raw[k] < 0) >> g) & 0x01010101u;
        bits0 = __funnelshift_l(m * 0x10204080u, bits0, 4);
        const bool pad = la + k * 128 > llast;
        ra[k] = pad ? NB * CELL * 16 : (raw[k] >> 13) & 0x1FFF0;
        raw[k] = (raw[k] & 0xFFFF) | (pad ? F_PAD : 0);
    }
    if (t < 2) bits0 = ~bits0;
    asm volatile("" : "+r"(bits0), "+r"(ra[0]), "+r"(ra[1]), "+r"(ra[2]), "+r"(ra[3]), "+r"(ra[4]), "+r"(raw[0]), "+r"(raw[1]), "+r"(raw[2]), "+r"(raw[3]), "+r"(raw[4]));
    fill(1);
    asm volatile("cp.async.wait_group 2;" ::: "memory");
    bar_sync(1, NT);
    TSTAMP(19);
    if (w == CW) {
        uint32_t tn; asm volatile("mov.u32 %0, %%globaltimer_lo;" : "=r"(tn));
        if ((int)(tn + RDY - flag[1]) > 0) { report(tn + RDY); flag[1] = tn + RDY; }
    }
    {
        uint4 rv[NRAW];
#pragma unroll
        for (int k = 0; k < NRAW - 1; k++) rv[k] = lds128(ra[k] + (sb + SM_RECS));
        if ((NRAW - 1) * 4 < S) rv[NRAW - 1] = lds128(ra[NRAW - 1] + (sb + SM_RECS));
        fill(2);
        bar_sync(1, NT);
        TSTAMP(12);
        unsigned char* mr = meta + (q - 1) * STEPB + c * 16;
        unsigned char* ms = meta + (q - DS - 1) * STEPB + 128 + c * 4;
#pragma unroll
        for (int k = 0; k < NRAW; k++) {
            if (k == 0) {
                *(uint4*)(mr + (q == 0 ? S * STEPB : 0)) = rv[k];
                *(uint32_t*)(ms + S * STEPB) = raw[0] + F_WRAP;
            } else if (k * 4 + q < S) {
                *(uint4*)(mr + k * 4 * STEPB) = rv[k];
                *(uint32_t*)(ms + k * 4 * STEPB + (k == 1 && q == 0 ? S * STEPB : 0)) = raw[k];
            }
        }
    }
    __syncwarp();
    const uint32_t tphase = PACE / 4;
    uint32_t dreg;
    {
        const int ls = lane >= S ? min(lane - S, S - 1) : lane, st = ls == 0 ? S - 1 : ls - 1;
        const uint4 u0 = *(const uint4*)(meta + st * STEPB + 128), u1 = *(const uint4*)(meta + st * STEPB + 144);
        int pos = (u0.x + u0.y + u0.z + u0.w + u1.x + u1.y + u1.z + u1.w) << 1 >> 6;
        pos += ((u0.x & F_WRAP) ? NN : 0) + (lane >= S ? NN : 0) - NN * (2 * DS + 1) / 32;
        dreg = pos * (int)tphase / NN;
    }
    fill(3);
    TSTAMP(6);

    uint32_t* stash = (uint32_t*)(gs->stash + (b * NW + w) * 256) + lane;
    float acc[4][4];
#pragma unroll
    for (int i = 0; i < 16; i++) acc[i / 4][i % 4] = 0.f;
    uint4 az = *(const uint4*)(smem + SM_AZ + lane * 16);
    uint32_t dcur = dreg, dl = 0, now = flag[1], tcur = 0;
    uint32_t mp = 0, smask = 1, didx = 2;
    uint32_t mend = S * STEPB;
    uint2 r = lds64(mend - STEPB + recl), s0 = lds64(mend - STEPB + srcl);
    auto step = [&](const uint32_t off, const int mode, const bool pc = true) {
        if (mode == 0 && pc) { unsigned long long n64; asm volatile("mov.u64 %0, %%globaltimer;" : "=l"(n64)); now = (uint32_t)n64; }
        const uint2 rc = r, sc = s0;
        if (mode != 4) r = lds64(mp + recl);
        if (mode == 0) s0 = lds64(mp + srcl);
        asm volatile("cp.async.wait_group %0;" :: "n"(DS - 1) : "memory");
        const uint4 xa = lds128(rsrc + off), xb = lds128(rsrc + off + 512), xc = lds128(rsrc + off + 1024), xd = lds128(rsrc + off + 1536);
        if (mode == 0) {
            if (pc) { dl = __shfl_sync(0xffffffff, dcur, didx); didx += 2; }
            cpa2p(wdst + off, sc.x); cpa2p(wdst + off + 512, sc.y);
        }
        if (mode == 1 && w < 16) {
#pragma unroll
            for (int j = 0; j < 4; j++) {
                const int kk = 4 * j + q, ch = 16 * (w & 7) + 2 * (kk & 7) + (kk >> 3);
                asm volatile("cp.async.cg.shared.global [%0], [%1], 16;" :: "r"(ring0 + kk * 128 + ((c ^ (kk & 7)) << 4)), "l"(w_mix + ch * 16 + (w >> 3) * 8 + c) : "memory");
            }
            asm volatile("cp.async.mbarrier.arrive.noinc.shared.b64 [%0];" :: "r"(mbarW) : "memory");
        }
        if (mode == 2 || mode == 3) {
#pragma unroll
            for (int j = 0; j < 4; j += mode - 1)
                asm volatile("cp.async.cg.shared.global [%0], [%1], 16;" :: "r"(ring0 + off + j * 512 + lane * 16), "l"(stash + (mode - 2) * 512 + j * 128 + lane * 3) : "memory");
        }
        if (mode < 4) asm volatile("cp.async.commit_group;" ::: "memory");
        float z[4], y[4], t1[4], t2[4];
        mma1688z(z, az.x, az.y, rc.y);
        mma1688z(y, az.z, az.w, rc.y);
        uint32_t bt;
        asm("{.reg .pred p; .reg .b32 m; and.b32 m, %2, %3; setp.ne.u32 p, m, 0; selp.b32 %0, %1, 0, p;}" : "=r"(bt) : "r"(rc.x), "r"(bits0), "r"(smask));
        mma1688z(t1, at[0], at[1], bt);
        mma1688z(t2, at[2], at[3], bt);
        const uint32_t T0 = pack2(t1[0], t1[2]), T1 = pack2(t2[0], t2[2]), T2 = pack2(t1[1], t1[3]), T3 = pack2(t2[1], t2[3]);
        uint32_t R[8];
#pragma unroll
        for (int i = 0; i < 4; i++) { R[i] = __float_as_uint(silu_h(z[i])); R[4 + i] = __float_as_uint(silu_h(y[i])); }
        mma16816(acc[0], mul_hi(xa.x, R[0]), mul_hi(xa.z, R[2]), mul_hi(xa.y, R[0]), mul_hi(xa.w, R[2]), T0, T1);
        mma16816(acc[1], mul_hi(xb.x, R[1]), mul_hi(xb.z, R[3]), mul_hi(xb.y, R[1]), mul_hi(xb.w, R[3]), T2, T3);
        mma16816(acc[2], mul_hi(xc.x, R[4]), mul_hi(xc.z, R[6]), mul_hi(xc.y, R[4]), mul_hi(xc.w, R[6]), T0, T1);
        mma16816(acc[3], mul_hi(xd.x, R[5]), mul_hi(xd.z, R[7]), mul_hi(xd.y, R[5]), mul_hi(xd.w, R[7]), T2, T3);
        mp += STEPB; smask <<= 1;
    };
    auto putacc = [&](uint32_t* p) {
#pragma unroll
        for (int i = 0; i < 16; i++) acc[i / 4][i % 4] *= 1.0028f;
        p[0] = pack2(acc[0][0], acc[0][1]); p[32] = pack2(acc[0][2], acc[0][3]); p[64] = pack2(acc[2][0], acc[2][1]); p[96] = pack2(acc[2][2], acc[2][3]);
        p[256] = pack2(acc[1][0], acc[1][1]); p[288] = pack2(acc[1][2], acc[1][3]); p[320] = pack2(acc[3][0], acc[3][1]); p[352] = pack2(acc[3][2], acc[3][3]);
    };
    int ph = 0;
    auto phase_end = [&](const int k) {
        az = lds128(sb + SM_AZ + (ph + 1) * 512 + lane * 16);
        putacc(stash + ph * ph * 128);
#pragma unroll
        for (int i = 0; i < 16; i++) acc[i / 4][i % 4] = 0.f;
        pbase += 256; mp = 0; smask = 1; ph++;
        dcur += tphase; didx = 1 + (k & 1);
        if (ph == 3) {
            mend -= DS * STEPB;
            if (FAN) dcur += (int)(dcur - __shfl_sync(0xffffffff, dcur, 0)) * (((w >> 2) - FANC) * FAN) >> 8;
        }
        WSTAMP(ph - 1);
    };
    uint32_t t0 = now;
    const bool reporter = w == PW && max(len2 & 0xFFFF, len2 >> 16) <= RLEN;
    if (reporter) {
        asm volatile("mov.u32 %0, %%globaltimer_lo;" : "=r"(now));
        now += PTOL - PTOL0;
    }
    const uint32_t bias = w == RW ? 1u << 20 : 0;
    if (w == RW) relay();
    dcur += bias;
    auto body = [&](const int k) -> bool {
        if (k == 2) asm volatile("ld.volatile.shared.u32 %0, [%1+4];" : "=r"(t0) : "r"(flg));
        const bool pc = k & 1;
        step(k * SLOTB, 0, pc);
        if (!pc) {
            if (mp == mend) phase_end(k);
        } else if (mp == mend || now < dl) {
            if (mp == mend) {
                if (k == 3 && ph == 3) return true;
                phase_end(k);
            }
            if (w == RW) { dl -= 1u << 20; relay(); }
            wait_until(dl);
        }
        return false;
    };
    {
        const uint32_t d0 = __shfl_sync(0xffffffff, dreg, 0);
        if (w == RW) {
            uint32_t g0, tn; int spins = 0;
            do {
                asm volatile("ld.relaxed.gpu.global.u32 %0, [%2]; mov.u32 %1, %%globaltimer_lo;" : "=r"(g0), "=r"(tn) : "l"(&gs->t0) : "memory");
                if (g0 - t0 < 30000) { t0 = g0; flag[1] = g0; }
            } while (__shfl_sync(0xffffffff, t0 - tn, 0) < 32768 && ++spins < 64);
        }
        asm volatile("{.reg .pred p; .reg .u32 d;\n"
                     "PACE_LOOP: ld.volatile.shared.u32 %0, [%2+4]; mov.u32 d, %%globaltimer_lo; sub.u32 d, %1, d; add.u32 d, d, %0;\n"
                     "setp.lt.u32 p, d, 32768; @p nanosleep.u32 32; @p bra.uni PACE_LOOP;}"
                     : "=&r"(t0) : "r"(d0), "r"(flg) : "memory");
    }
    while (true) {
        if (reporter) {
            const uint32_t cand = now - dl + tcur - PTOL;
            if ((int)(cand - t0) > 0) report(cand);
        }
        dcur += t0 - tcur; tcur = t0;
        body(0); body(1); body(2);
        if (body(3)) break;
    }
    __syncwarp();
    step(0, 1);
    if (TDEL) { uint32_t tn; asm volatile("mov.u32 %0, %%globaltimer_lo;" : "=r"(tn)); wait_until(tn + (w >> 2) * TDEL); }
    step(SLOTB, 2); step(2 * SLOTB, 3); step(3 * SLOTB, 4);
    WSTAMP(3); ESTAMP(0);

    {
        putacc((uint32_t*)(smem + SM_RING + 2 * SLOTB + w * 2048 + 512) + lane);
        const int wg = w >> 2, w4 = w & 3;
        int nd[8];
#pragma unroll
        for (int j = 0; j < 8; j++) { const int l = wg * 8 + j; nd[j] = order[(t >> 1) ? 79 - l : l]; asm volatile("" : "+r"(nd[j])); }
        const bool odd = t & 1;
        uint2* ob = (uint2*)out + (size_t)n0 * 128 + w4 * 16 + g + (odd ? 8 : 0);
        asm volatile("cp.async.wait_all;" ::: "memory");
        mbar_wait(mbarW, 0);
        asm volatile("fence.proxy.async.shared::cta;" ::: "memory");
        ESTAMP(1);
        if (!ONEBAR) bar_sync(2 + wg, 128);
        uint32_t ticket = 0;
        if ((tid & 127) == 0) {
            asm volatile("atom.shared.add.u32 %0, [%1+48], 1;" : "=r"(ticket) : "r"(flg) : "memory");
            int spins = 0;
            while (flag[13] + LEAD < ticket && ++spins < (1 << 16)) { if (SPINS) __nanosleep(SPINS); }
        }
        bar_sync(2 + wg, 128);
        const uint64_t descA0 = (uint64_t)(((sb + SM_RING) & 0x3FFFF) >> 4) | ((uint64_t)1 << 16) | ((uint64_t)(1024 >> 4) << 32) | ((uint64_t)1 << 62);
        const uint64_t descB0 = (uint64_t)(((sb + SM_RING + SLOTB + wg * 8192) & 0x3FFFF) >> 4) | ((uint64_t)(128 >> 4) << 16) | ((uint64_t)(1024 >> 4) << 32);
        auto release = [&]() { asm volatile("{.reg .pred p; setp.eq.u32 p, %1, 0; @p st.volatile.shared.u32 [%0+52], %2;}" :: "r"(flg), "r"(tid & 127), "r"(ticket + 1) : "memory"); };
        float d[2][32];
        asm volatile("wgmma.fence.sync.aligned;" ::: "memory");
        ESTAMP(2);
#pragma unroll
        for (int i1 = 0; i1 < 2; i1++) {
#pragma unroll
            for (int i0 = 0; i0 < 8; i0++) {
                const int mt = ILV ? i0 & 1 : i1, ks = ILV ? i1 * 4 + (i0 >> 1) : i0;
                if (i1 * 8 + i0 == RELK) release();
                const uint64_t da = descA0 + (uint64_t)((ks * 2048 + mt * 16384) >> 4), db = descB0 + (uint64_t)(((ks & 3) * 256 + (ks >> 2) * SLOTB) >> 4);
                asm volatile("{.reg .pred p; setp.ne.b32 p, %34, 0;\n"
                    "wgmma.mma_async.sync.aligned.m64n64k16.f32.bf16.bf16 "
                    "{%0,%1,%2,%3,%4,%5,%6,%7,%8,%9,%10,%11,%12,%13,%14,%15,%16,%17,%18,%19,%20,%21,%22,%23,%24,%25,%26,%27,%28,%29,%30,%31}, %32, %33, p, 1, 1, 1, 1;}"
                    : "+f"(d[mt][0]), "+f"(d[mt][1]), "+f"(d[mt][2]), "+f"(d[mt][3]), "+f"(d[mt][4]), "+f"(d[mt][5]), "+f"(d[mt][6]), "+f"(d[mt][7]),
                      "+f"(d[mt][8]), "+f"(d[mt][9]), "+f"(d[mt][10]), "+f"(d[mt][11]), "+f"(d[mt][12]), "+f"(d[mt][13]), "+f"(d[mt][14]), "+f"(d[mt][15]),
                      "+f"(d[mt][16]), "+f"(d[mt][17]), "+f"(d[mt][18]), "+f"(d[mt][19]), "+f"(d[mt][20]), "+f"(d[mt][21]), "+f"(d[mt][22]), "+f"(d[mt][23]),
                      "+f"(d[mt][24]), "+f"(d[mt][25]), "+f"(d[mt][26]), "+f"(d[mt][27]), "+f"(d[mt][28]), "+f"(d[mt][29]), "+f"(d[mt][30]), "+f"(d[mt][31])
                    : "l"(da), "l"(db), "r"(ks));
            }
            asm volatile("wgmma.commit_group.sync.aligned;" ::: "memory");
        }
        if (RELK == 16) release();
#pragma unroll
        for (int mt = 0; mt < 2; mt++) {
            if (mt == 0 && !ILV) asm volatile("wgmma.wait_group.sync.aligned 1;" ::: "memory");
            else asm volatile("wgmma.wait_group.sync.aligned 0;" ::: "memory");
            if (RELK == 17 + mt) release();
            ESTAMP(3 + mt);
#pragma unroll
            for (int i = 0; i < 32; i++) asm volatile("" : "+f"(d[mt][i]) :: "memory");
#pragma unroll
            for (int j = 0; j < 8; j++) {
                const uint32_t v0 = pack2(d[mt][4 * j], d[mt][4 * j + 1]), v1 = pack2(d[mt][4 * j + 2], d[mt][4 * j + 3]);
                const uint32_t rv = __shfl_xor_sync(0xffffffff, odd ? v0 : v1, 1);
                if (nd[j] < nn) ob[nd[j] * 128 + mt * 64] = odd ? make_uint2(rv, v1) : make_uint2(v0, rv);
            }
        }
    }
    TSTAMP(8); ESTAMP(5);
}

}

extern "C" void kernel_launch(void* const* d_in, const int* in_sizes, int n_in, void* d_out, int out_size) {
    (void)in_sizes; (void)n_in; (void)out_size;
    cudaFuncSetAttribute(tfn_kernel, cudaFuncAttributeMaxDynamicSharedMemorySize, SM_TOTAL);
    Scratch* gs = nullptr;
    cudaGetSymbolAddress((void**)&gs, g_scratch);
    cudaLaunchConfig_t cfg = {};
    cfg.gridDim = dim3(NB); cfg.blockDim = dim3(NT); cfg.dynamicSmemBytes = SM_TOTAL; cfg.stream = cudaStreamPerThread;
    cudaLaunchAttribute at[1];
    at[0].id = cudaLaunchAttributeCooperative; at[0].val.cooperative = 1;
    cfg.attrs = at; cfg.numAttrs = 1;
    cudaLaunchKernelEx(&cfg, tfn_kernel, (const unsigned char*)d_in[0], (const int4*)d_in[1], (const int4*)d_in[2],
                       (const uint4*)d_in[3], (const uint4*)d_in[4], (const uint16_t*)d_in[5], (const uint16_t*)d_in[6],
                       (const uint4*)d_in[7], (uint32_t*)d_out, gs);
}
```

```cpp
#include <cuda_runtime.h>
#include <cuda_bf16.h>
#include <stdint.h>

namespace {

constexpr int NN = 10000;
constexpr int NE = 320000;
constexpr int NB = 132;
constexpr int NW = 20;
constexpr int NT = NW * 32;
constexpr int CW = NW - 1;
constexpr int PW = 10;
constexpr int RW = 1;
constexpr int NPB = 76;
constexpr int CELL = 48;
constexpr int RCH = 2880;
constexpr int CAP = 19;
constexpr int DS = 4;
constexpr int STEPB = 160;
constexpr int NE4 = NE / 4;
constexpr int NPIECE = NB * 8;
constexpr int KB = 320, KN = 32 * KB;
constexpr uint32_t F_PAD = 0x80000000u;
constexpr uint32_t F_WRAP = 1;

constexpr int SLOTB = NW * 2048;
constexpr int SM_RING = 0;
constexpr int SM_META = SM_RING + DS * SLOTB;
constexpr int SM_AZ = SM_META + NW * CAP * STEPB;
constexpr int SM_MISC = SM_AZ + 2048;
constexpr int SM_TOTAL = SM_MISC + 2048;
constexpr int SM_STAGE = SM_RING;
constexpr int SM_HIST = SM_RING + 25600;
constexpr int SM_POS = SM_RING;
constexpr int SM_SMALL = SM_HIST + 13056;
constexpr int SM_LIST = SM_RING + SLOTB;
constexpr int SM_ROUT = SM_RING + 2 * SLOTB;
constexpr int SM_RECS = SM_RING + 3 * SLOTB;
constexpr int SM_RAWY = SM_META;
constexpr int SM_RAWE = SM_RAWY + 608 * 32;
constexpr int SM_KEYS = SM_RAWE + 608 * 32;
static_assert(SM_TOTAL <= 232448 && SM_KEYS + NPIECE * 16 <= SM_AZ, "smem");
static_assert(SM_RECS + NB * CELL * 16 + 16 <= SM_AZ && SM_KEYS + NPIECE * 16 <= SM_RECS + NB * CELL * 16 && SM_SMALL + 1152 <= SLOTB && DS == 4, "smem");

struct Scratch {
    uint4 keys[NB * NPIECE];
    uint4 recs[NB * RCH];
    uint4 stash[NB * NW * 256];
    unsigned bar[2];
    unsigned long long t0;
};
__device__ Scratch g_scratch;
#define TSTAMP(i)
#define TSTAMPC(i)
#define WSTAMP(i)
#define ESTAMP(i)

__device__ __forceinline__ void mma16816(float* d, uint32_t a0, uint32_t a1, uint32_t a2, uint32_t a3, uint32_t b0, uint32_t b1) {
    asm("mma.sync.aligned.m16n8k16.row.col.f32.bf16.bf16.f32 {%0,%1,%2,%3}, {%4,%5,%6,%7}, {%8,%9}, {%0,%1,%2,%3};"
        : "+f"(d[0]), "+f"(d[1]), "+f"(d[2]), "+f"(d[3]) : "r"(a0), "r"(a1), "r"(a2), "r"(a3), "r"(b0), "r"(b1));
}
__device__ __forceinline__ void mma1688z(float* d, uint32_t a0, uint32_t a1, uint32_t b0) {
    asm("mma.sync.aligned.m16n8k8.row.col.f32.bf16.bf16.f32 {%0,%1,%2,%3}, {%4,%5}, {%6}, {%7,%7,%7,%7};"
        : "=f"(d[0]), "=f"(d[1]), "=f"(d[2]), "=f"(d[3]) : "r"(a0), "r"(a1), "r"(b0), "f"(0.f));
}
__device__ __forceinline__ uint32_t pack2(float lo, float hi) {
    uint32_t r; asm("cvt.rn.bf16x2.f32 %0, %1, %2;" : "=r"(r) : "f"(hi), "f"(lo)); return r;
}
__device__ __forceinline__ float silu_h(float h) {
    float t; asm("tanh.approx.f32 %0, %1;" : "=f"(t) : "f"(h)); return fmaf(h, t, h);
}
__device__ __forceinline__ uint32_t mul_lo(uint32_t v, uint32_t r) {
    __nv_bfloat162 a = *(__nv_bfloat162*)&v, b = *(__nv_bfloat162*)&r; __nv_bfloat162 c = __hmul2(a, __low2bfloat162(b)); return *(uint32_t*)&c;
}
__device__ __forceinline__ uint32_t mul_hi(uint32_t v, uint32_t r) {
    __nv_bfloat162 a = *(__nv_bfloat162*)&v, b = *(__nv_bfloat162*)&r; __nv_bfloat162 c = __hmul2(a, __high2bfloat162(b)); return *(uint32_t*)&c;
}
__device__ __forceinline__ uint32_t lds32(uint32_t a) {
    uint32_t r; asm volatile("ld.shared.u32 %0, [%1];" : "=r"(r) : "r"(a) : "memory"); return r;
}
__device__ __forceinline__ void sts32(uint32_t a, uint32_t v) { asm volatile("st.shared.u32 [%0], %1;" :: "r"(a), "r"(v) : "memory"); }
__device__ __forceinline__ uint2 lds64(uint32_t a) {
    uint2 r; asm volatile("ld.shared.v2.u32 {%0,%1}, [%2];" : "=r"(r.x), "=r"(r.y) : "r"(a)); return r;
}
__device__ __forceinline__ uint4 lds128(uint32_t a) {
    uint4 r; asm volatile("ld.shared.v4.u32 {%0,%1,%2,%3}, [%4];" : "=r"(r.x), "=r"(r.y), "=r"(r.z), "=r"(r.w) : "r"(a) : "memory"); return r;
}
__device__ __forceinline__ void bar_sync(int id, int n) { asm volatile("bar.sync %0, %1;" :: "r"(id), "r"(n) : "memory"); }
__device__ __forceinline__ void bar_arrive(int id, int n) { asm volatile("bar.arrive %0, %1;" :: "r"(id), "r"(n) : "memory"); }
__device__ __forceinline__ void mbar_wait(uint32_t bar, uint32_t ph) {
    uint32_t done; int spins = 0;
    do {
        asm volatile("{.reg .pred p; mbarrier.try_wait.parity.shared.b64 p, [%1], %2; selp.u32 %0,1,0,p;}" : "=r"(done) : "r"(bar), "r"(ph) : "memory");
    } while (!done && ++spins < (1 << 22));
}
__device__ __forceinline__ void gbar_arrive(unsigned* ctr) {
    asm volatile("red.inc.relaxed.gpu.global.u32 [%0], %1;" :: "l"(ctr), "n"(2 * NB - 1) : "memory");
}
__device__ __forceinline__ int chunk_start4(int c) { return (c * NE4) / NB; }
__device__ __forceinline__ float bf2f(uint32_t h) { return __uint_as_float(h << 16); }

__device__ __noinline__ void slow_path(unsigned char* smem, int n0, int nn, const uint16_t* x, const int* src, const int* dst,
                                       const uint16_t* Y, const uint16_t* ef, const uint16_t* w_rad, const uint16_t* cg,
                                       const uint16_t* w_mix, __nv_bfloat16* out) {
    float* agg = (float*)smem;
    const int tid = threadIdx.x, lane = tid & 31, w = tid >> 5;
    bar_sync(1, NT);
    for (int i = tid; i < NPB * 512; i += NT) agg[i] = 0.f;
    bar_sync(1, NT);
    for (int e0 = w * 32; e0 < NE; e0 += NT) {
        int dl = dst[e0 + lane] - n0;
        unsigned m = __ballot_sync(0xffffffff, dl >= 0 && dl < nn);
        while (m) {
            int l = __ffs(m) - 1; m &= m - 1;
            int e = e0 + l, d = __shfl_sync(0xffffffff, dl, l), s = src[e];
            float T[16];
            for (int i = 0; i < 4; i++) for (int o = 0; o < 4; o++) {
                float a = 0.f;
                for (int f = 0; f < 4; f++) a += bf2f(Y[e * 4 + f]) * bf2f(cg[i * 16 + f * 4 + o]);
                T[i * 4 + o] = a;
            }
            for (int k = 0; k < 4; k++) {
                int c = lane + 32 * k;
                float z = 0.f;
                for (int j = 0; j < 4; j++) z += bf2f(ef[e * 4 + j]) * bf2f(w_rad[j * 128 + c]);
                float R = z / (1.f + __expf(-z));
                for (int o = 0; o < 4; o++) {
                    float a = 0.f;
                    for (int i = 0; i < 4; i++) a += bf2f(x[(size_t)s * 512 + c * 4 + i]) * T[i * 4 + o];
                    atomicAdd(&agg[d * 512 + c * 4 + o], R * a);
                }
            }
        }
    }
    bar_sync(1, NT);
    for (int i = tid; i < nn * 512; i += NT) {
        int n = i >> 9, d = (i >> 2) & 127, o = i & 3;
        float a = 0.f;
        for (int c = 0; c < 128; c++) a += agg[n * 512 + c * 4 + o] * bf2f(w_mix[c * 128 + d]);
        out[(size_t)(n0 + n) * 512 + (i & 511)] = __float2bfloat16(a);
    }
}

#define PACE 23000
#define YDELAY 300
#define POFF 3600
#define PSLEEP 32
#define FDT 350
#define FOFF 1500
#define RELK 12
#define FAN 16
#define TDEL 100
#define RDY 600
#define XPF 48
#define PTOL0 300
#define PTOL 1100
__global__ void __launch_bounds__(NT, 1)
tfn_kernel(const unsigned char* __restrict__ x, const int4* __restrict__ src4, const int4* __restrict__ dst4,
           const uint4* __restrict__ Y, const uint4* __restrict__ ef, const uint16_t* __restrict__ w_rad,
           const uint16_t* __restrict__ cg, const uint4* __restrict__ w_mix, uint32_t* __restrict__ out, Scratch* __restrict__ gs) {
    extern __shared__ __align__(1024) unsigned char smem[];
    const uint32_t sb = (uint32_t)__cvta_generic_to_shared(smem);
    const int b = blockIdx.x, tid = threadIdx.x, lane = tid & 31, g = lane >> 2, t = lane & 3;
    const int w = __shfl_sync(0xffffffff, tid >> 5, 0);
    uint32_t* stage = (uint32_t*)(smem + SM_STAGE);
    uint32_t* hist = (uint32_t*)(smem + SM_HIST);
    uint32_t* cnt = (uint32_t*)(smem + SM_MISC);
    uint32_t* deg = cnt + 136;
    uint32_t* order = deg + 104;
    uint32_t* cnt2 = order + 80;
    volatile uint32_t* flag = cnt2 + 136;
    const uint32_t mbarK = sb + SM_MISC + 1920, mbarR = mbarK + 8, mbarW = mbarK + 16;
    const int n0 = b * NPB, nn = min(NPB, NN - n0);
    TSTAMP(0);

    const int c0 = chunk_start4(b), c1 = chunk_start4(b + 1);
    const bool has4 = c0 + tid < c1;
    int4 d4 = make_int4(0, 0, 0, 0), s4 = d4;
    if (has4) { d4 = __ldg(dst4 + c0 + tid); s4 = __ldg(src4 + c0 + tid); }
    unsigned par = 0;
    if (tid == NT - 1) {
        asm volatile("ld.relaxed.gpu.global.u32 %0, [%1];" : "=r"(par) : "l"(gs->bar) : "memory");
        asm volatile("mbarrier.init.shared.b64 [%0], 1;" :: "r"(mbarK));
        asm volatile("mbarrier.init.shared.b64 [%0], 1;" :: "r"(mbarR));
        asm volatile("mbarrier.init.shared.b64 [%0], 512;" :: "r"(mbarW));
        asm volatile("fence.mbarrier_init.release.cluster;" ::: "memory");
        flag[0] = 0; flag[12] = 0; flag[13] = 0; flag[15] = 0;
    }
    if (w == CW) {
        asm volatile("cp.async.cg.shared.global [%0], [%1], 16;" :: "r"(sb + SM_SMALL + lane * 16), "l"(w_rad + lane * 8) : "memory");
        asm volatile("cp.async.cg.shared.global [%0], [%1], 16;" :: "r"(sb + SM_SMALL + 512 + lane * 16), "l"(w_rad + 256 + lane * 8) : "memory");
        if (lane < 8) asm volatile("cp.async.cg.shared.global [%0], [%1], 16;" :: "r"(sb + SM_SMALL + 1024 + lane * 16), "l"(cg + lane * 8) : "memory");
    }
    ((uint4*)hist)[tid] = make_uint4(0, 0, 0, 0);
    {
        const uint32_t dk = (80 + b % 22) * KN + (b & 31) * KB;
#pragma unroll
        for (int j = 0; j < 3; j++) if (tid + j * NT < NB * CELL / 4) ((uint4*)stage)[tid + j * NT] = make_uint4(dk, dk, dk, dk);
    }
    if (tid < 136) cnt[tid] = 0;
    if (tid == 0) { *(uint4*)(smem + SM_MISC + 1824 + 32) = make_uint4(0, 0, 0, 0); *(uint4*)(smem + SM_RECS + NB * CELL * 16) = make_uint4(0, 0, 0, 0); }
    if (tid < 80) { deg[tid] = 127 - tid; order[tid] = tid; }
    __syncthreads();
    TSTAMP(9);
    if (tid == 64) {
        __nanosleep(YDELAY);
        asm volatile("mbarrier.arrive.expect_tx.shared.b64 _, [%0], %1;" :: "r"(mbarR), "r"((c1 - c0) * 64) : "memory");
        asm volatile("cp.async.bulk.shared::cluster.global.mbarrier::complete_tx::bytes [%0], [%1], %2, [%3];"
                     :: "r"(sb + SM_RAWY), "l"(Y + 2 * c0), "r"((c1 - c0) * 32), "r"(mbarR) : "memory");
        asm volatile("cp.async.bulk.shared::cluster.global.mbarrier::complete_tx::bytes [%0], [%1], %2, [%3];"
                     :: "r"(sb + SM_RAWE), "l"(ef + 2 * c0), "r"((c1 - c0) * 32), "r"(mbarR) : "memory");
    }

    uint32_t bin[4] = {0, 0, 0, 0}, slot[4] = {0, 0, 0, 0};
    if (has4) {
        const uint32_t dd[4] = {(uint32_t)d4.x, (uint32_t)d4.y, (uint32_t)d4.z, (uint32_t)d4.w}, ss[4] = {(uint32_t)s4.x, (uint32_t)s4.y, (uint32_t)s4.z, (uint32_t)s4.w};
#pragma unroll
        for (int k = 0; k < 4; k++) { bin[k] = dd[k] / NPB; slot[k] = atomicAdd(&cnt[bin[k]], 1); }
#pragma unroll
        for (int k = 0; k < 4; k++) stage[bin[k] * CELL + min(slot[k], CELL - 1)] = (dd[k] - bin[k] * NPB) * KN + ss[k];
    }
    if (w == CW) {
        if (tid == NT - 1) { par = par >= NB; flag[14] = (par ^ 1) << 31; }
        asm volatile("cp.async.wait_all;" ::: "memory");
    }
    bar_sync(1, NT);
    TSTAMP(1);
    const uint32_t tag = flag[14];
#pragma unroll
    for (int j = 0; j < 2; j++) {
        const int i = tid + j * NT;
        if (i < NPIECE) {
            const uint2 sa = *(const uint2*)(stage + i * 6), sc = *(const uint2*)(stage + i * 6 + 2);
            uint2 se = *(const uint2*)(stage + i * 6 + 4);
            const uint32_t cf = cnt[i >> 3], cn = min(cf, 63u);
            if ((i & 7) == 7) {
                const uint32_t al = cf > CELL - 8 ? 7 : 0;
                uint32_t o;
                asm volatile("atom.shared.add.u32 %0, [%1], %2;" : "=r"(o) : "r"(sb + SM_MISC + 1824 + 60), "r"(cf + al) : "memory");
                se.y = (o + al) & ~al;
                cnt2[i >> 3] = se.y;
            }
            asm volatile("{.reg .b64 lo, hi; mov.b64 lo, {%1,%2}; mov.b64 hi, {%3,%4}; st.relaxed.gpu.global.v2.b64 [%0], {lo, hi};}"
                         :: "l"(gs->keys + ((i >> 3) * NB + b) * 8 + ((i ^ b) & 7)),
                            "r"(sa.x | (se.x << 20)), "r"(sa.y | ((se.x >> 12) << 20) | ((cn & 7) << 28) | tag),
                            "r"(sc.x | (se.y << 20)), "r"(sc.y | ((se.y >> 12) << 20) | ((cn >> 3) << 28) | tag) : "memory");
        }
    }
    bar_sync(1, NT);
    if (tid == NT - 1) {
        TSTAMPC(10);
        gbar_arrive(&gs->bar[0]);
        asm volatile("mbarrier.arrive.expect_tx.shared.b64 _, [%0], %1;" :: "r"(mbarK), "r"(NPIECE * 16) : "memory");
        unsigned v; int spins = 0;
        do { asm volatile("ld.relaxed.gpu.global.u32 %0, [%1];" : "=r"(v) : "l"(gs->bar) : "memory"); } while ((v >= NB) == par && ++spins < (1 << 22));
        TSTAMPC(13);
        asm volatile("fence.proxy.async.global;" ::: "memory");
        asm volatile("cp.async.bulk.shared::cluster.global.mbarrier::complete_tx::bytes [%0], [%1], %2, [%3];"
                 :: "r"(sb + SM_KEYS), "l"(gs->keys + b * NPIECE), "r"(NPIECE * 16), "r"(mbarK) : "memory");
    }
    __syncwarp();
    uint32_t at[4];
    {
        const int o = g & 3, f = 2 * (t & 1);
#pragma unroll
        for (int i = 0; i < 4; i++) {
            const uint16_t* cp = (const uint16_t*)(smem + SM_SMALL + 1024) + i * 16 + f * 4 + o;
            at[i] = (t >> 1) == (g >> 2) ? cp[0] | ((uint32_t)cp[4] << 16) : 0;
        }
    }

    const int q = lane >> 3, c = lane & 7;
    const uint32_t ring0 = sb + SM_RING + w * 2048;
    uint32_t wdst = ring0 + q * 128 + ((c + 2 * q) & 7) * 16;
    uint32_t rsrc = ring0 + t * 128 + ((g + 2 * t) & 7) * 16;
    uint32_t recl = sb + SM_META + w * (CAP * STEPB) + g * 16 + (t & 1) * 8, srcl = sb + SM_META + w * (CAP * STEPB) + 128 + q * 8;
    uint32_t flg = sb + SM_MISC + (136 + 104 + 80 + 136) * 4;
    asm volatile("" : "+r"(wdst), "+r"(rsrc), "+r"(recl), "+r"(srcl), "+r"(flg));
    auto setflag = [&]() { sts32(flg, 1); };
    uint32_t key[2][6], ha[2][6], rk[2][6], kidx[2], ka[2], kc[2];
    int nk[2];
#pragma unroll
    for (int j = 0; j < 2; j++) {
        const int i0 = j ? 2 * 608 - 1 - tid : tid, i = min(i0, NPIECE - 1), r = i / NB, cc = i - r * NB;
        ka[j] = sb + SM_KEYS + (cc * 8 + ((r ^ cc) & 7)) * 16;
        kidx[j] = (cc * CELL + r * 6) << 17;
        kc[j] = sb + SM_MISC + cc * 4;
        nk[j] = i0 < NPIECE && w < CW ? -6 * r : -1000;
    }
    asm volatile("" : "+r"(at[0]), "+r"(at[1]), "+r"(at[2]), "+r"(at[3]), "+r"(ka[0]), "+r"(ka[1]), "+r"(kidx[0]), "+r"(kidx[1]), "+r"(kc[0]), "+r"(kc[1]), "+r"(nk[0]), "+r"(nk[1]));
    if (w == CW) {
        __syncwarp();
        bar_sync(7, NT);
        if (tid == NT - 1) {
            TSTAMPC(11);
            asm volatile("cp.async.bulk.global.shared::cta.bulk_group [%0], [%1], %2;"
                         :: "l"(gs->recs + b * RCH), "r"(sb + SM_ROUT), "r"(((flag[15] + 1) & ~1u) * 16) : "memory");
            asm volatile("cp.async.bulk.commit_group;" ::: "memory");
            mbar_wait(mbarK, 0);
            unsigned long long tbase;
            asm volatile("mov.u64 %0, %%globaltimer;" : "=l"(tbase));
            tbase += POFF;
            flag[1] = (uint32_t)tbase; flag[4] = (uint32_t)tbase; flag[5] = (uint32_t)(tbase >> 32);
            asm volatile("red.max.relaxed.gpu.global.u64 [%0], %1;" :: "l"(&gs->t0), "l"(tbase) : "memory");
            if (b < 128) asm volatile("cp.async.bulk.prefetch.L2.global [%0], 256;" :: "l"(w_mix + b * 16));
            asm volatile("cp.async.bulk.wait_group 0;" ::: "memory");
            TSTAMPC(14);
            gbar_arrive(&gs->bar[1]);
            TSTAMPC(15);
        }
    } else {
        if (w < 8) {
            const uint32_t* wp = (const uint32_t*)(smem + SM_SMALL) + (t & 1) * 128 + 8 * w + g;
            const uint32_t wr0 = t < 2 ? wp[0] : 0, wr1 = t < 2 ? wp[64] : 0;
            *(uint2*)(smem + SM_AZ + (w >> 1) * 512 + lane * 16 + (w & 1) * 8) =
                make_uint2(pack2(0.5f * bf2f(wr0 & 0xFFFF), 0.5f * bf2f(wr1 & 0xFFFF)), pack2(0.5f * bf2f(wr0 >> 16), 0.5f * bf2f(wr1 >> 16)));
        }
        const bool sw = g & 1;
        uint32_t rp[4];
#pragma unroll
        for (int k = 0; k < 4; k++) rp[k] = cnt2[bin[k]] + slot[k];
        uint4* ro = (uint4*)(smem + SM_ROUT);
        uint4 *p0 = ro + (sw ? rp[2] : rp[0]), *p1 = ro + (sw ? rp[3] : rp[1]), *p2 = ro + (sw ? rp[0] : rp[2]), *p3 = ro + (sw ? rp[1] : rp[3]);
        const uint32_t ya = sb + SM_RAWY + tid * 32 + (sw ? 16 : 0);
        mbar_wait(mbarR, 0);
        TSTAMP(18);
        if (has4) {
            const uint4 y0 = lds128(ya), e0 = lds128(ya + (SM_RAWE - SM_RAWY)), y1 = lds128(ya ^ 16), e1 = lds128((ya ^ 16) + (SM_RAWE - SM_RAWY));
            *p0 = make_uint4(y0.x, e0.x, y0.y, e0.y); *p1 = make_uint4(y0.z, e0.z, y0.w, e0.w);
            *p2 = make_uint4(y1.x, e1.x, y1.y, e1.y); *p3 = make_uint4(y1.z, e1.z, y1.w, e1.w);
        }
        asm volatile("fence.proxy.async.shared::cta;" ::: "memory");
        bar_arrive(7, NT);
        if (tid >= 512 && tid < 512 + 2 * XPF)
            asm volatile("prefetch.global.L2 [%0];" :: "l"(x + (size_t)(b * XPF + ((tid - 512) >> 1)) * 1024 + (tid & 1) * 128));
    }
    __syncwarp();
    TSTAMP(2);

    if (w < CW) {
        mbar_wait(mbarK, 0);
        TSTAMP(3);
        uint4 v[2] = {lds128(ka[0]), lds128(ka[1])};
        if ((int)((v[0].y ^ tag) | (v[0].w ^ tag) | (v[1].y ^ tag) | (v[1].w ^ tag)) < 0) {
#pragma unroll
            for (int j = 0; j < 2; j++) {
                int spins = 0;
#pragma unroll 1
                while ((int)((v[j].y ^ tag) | (v[j].w ^ tag)) < 0) {
                    asm volatile("{.reg .b64 lo, hi; ld.relaxed.gpu.global.v2.b64 {lo, hi}, [%4]; mov.b64 {%0,%1}, lo; mov.b64 {%2,%3}, hi;}"
                                 : "=r"(v[j].x), "=r"(v[j].y), "=r"(v[j].z), "=r"(v[j].w) : "l"((const unsigned char*)(gs->keys + b * NPIECE) + (ka[j] - sb - SM_KEYS)) : "memory");
                    if (++spins > (1 << 20)) { setflag(); break; }
                }
            }
        }
#pragma unroll
        for (int j = 0; j < 2; j++) {
            const uint32_t hc = ((v[j].y >> 28) & 7) | ((v[j].w >> 25) & 0x38);
            if (j == 1 && nk[j] == -42) {
                sts32(kc[j], hc | ((v[j].z >> 20) << 8));
                if (hc > CELL - 1) setflag();
                v[j].w |= ((80 * KN) >> 12) << 20;
            }
            nk[j] += hc;
            if (nk[j] > 0) {
                key[j][0] = v[j].x & 0xFFFFF; key[j][1] = v[j].y & 0xFFFFF; key[j][2] = v[j].z & 0xFFFFF; key[j][3] = v[j].w & 0xFFFFF;
                key[j][4] = (v[j].x >> 20) | ((v[j].y >> 8) & 0xFF000); key[j][5] = (v[j].z >> 20) | ((v[j].w >> 8) & 0xFF000);
#pragma unroll
                for (int u = 0; u < 6; u++) {
                    ha[j][u] = __umulhi(key[j][u], 0xFFFFFFFFu / KB + 1);
                    asm volatile("{.reg .u32 a, n; mad.lo.u32 a, %1, 4, %2; atom.shared.add.u32 %0, [a+%3], 1;\n"
                                 "shr.u32 n, %1, 5; mad.lo.u32 a, n, 4, %2; red.shared.add.u32 [a+%4], 128;}"
                                 : "=r"(rk[j][u]) : "r"(ha[j][u]), "r"(sb), "n"(SM_HIST), "n"(SM_MISC + 136 * 4) : "memory");
                }
            }
        }
        bar_sync(9, NT - 32);
        TSTAMP(20);
        const int n = tid >> 3, sub = tid & 7;
        const uint32_t me = deg[n];
        uint32_t r = 0, r2 = 0;
#pragma unroll
        for (int k = 0; k < 5; k++) { const uint2 dd = *(const uint2*)(deg + sub * 10 + 2 * k); r += (me - dd.x) >> 31; r2 += (me - dd.y) >> 31; }
        r += r2;
#pragma unroll
        for (int j = 0; j < 2; j++) kidx[j] += (lds32(kc[j]) & 0x700) << 9;
        r += __shfl_xor_sync(0xffffffff, r, 1); r += __shfl_xor_sync(0xffffffff, r, 2); r += __shfl_xor_sync(0xffffffff, r, 4);
        if (sub == 0) order[r] = n;
    }
    bar_sync(1, NT);
    TSTAMP(22);
    uint32_t len2;
    {
        const uint2 na = *(const uint2*)(order + 2 * w);
        uint2 nb = *(const uint2*)(order + 78 - 2 * w);
        const uint32_t hl = sb + SM_HIST + lane * 4;
        const uint32_t ha0 = lds32(hl + na.x * 128), ha1 = lds32(hl + na.y * 128), hb0 = lds32(hl + nb.y * 128), hb1 = lds32(hl + nb.x * 128);
        if (deg[na.x] >= (4 * CAP + 1) * 128) setflag();
        const uint32_t ca = ha0 + (ha1 << 16), c4 = ca + (hb0 << 8) + (hb1 << 24);
        uint32_t inc = c4;
#pragma unroll
        for (int o = 1; o < 32; o <<= 1)
            asm volatile("{.reg .pred p; .reg .u32 u; shfl.sync.up.b32 u|p, %0, %1, 0, 0xffffffff; @p add.u32 %0, %0, u;}" : "+r"(inc) : "r"(o));
        const int su = __reduce_add_sync(0xffffffff, (int)(ha0 - ha1) * (2 * lane - 31)), sv = __reduce_add_sync(0xffffffff, (int)(hb0 - hb1) * (2 * lane - 31));
        const bool swp = (su ^ sv) >= 0;
        if (swp) { nb = make_uint2(nb.y, nb.x); *(uint2*)(order + 78 - 2 * w) = nb; }
        const uint32_t sel = swp ? 0x4143 : 0x4341, ex = inc - c4;
        const uint32_t ea = (ex & 0x00FF00FF) + __byte_perm(ex, 0, sel), eb = ea + ca, base = sb + SM_LIST + w * 2048;
        uint2* pos = (uint2*)(smem + SM_POS) + lane;
        pos[na.x * 32] = make_uint2(base + (ea & 0xFFFF) * 8, na.x * (0u - 4 * KN));
        pos[nb.y * 32] = make_uint2(base + (eb & 0xFFFF) * 8, nb.y * (0u - 4 * KN) + 0x80000000u);
        pos[na.y * 32] = make_uint2(base + 4 + (ea >> 16) * 8, na.y * (0u - 4 * KN));
        pos[nb.x * 32] = make_uint2(base + 4 + (eb >> 16) * 8, nb.x * (0u - 4 * KN) + 0x80000000u);
        len2 = __shfl_sync(0xffffffff, (inc & 0x00FF00FF) + __byte_perm(inc, 0, sel), 31);
        if (max(len2 & 0xFFFF, len2 >> 16) > 4 * CAP) setflag();
    }
    uint32_t ci = cnt[min(w + NW * lane, NB)];
    ci = (((ci & 0xFF) + ((ci >> 8) & 7)) << 24) + min(w + NW * lane, NB) * (RCH / 8) + (ci >> 11);
    if (w == CW) {
        bar_arrive(9, NT);
        if (tid == NT - 1) {
            uint32_t v1, g0; int spins = 0;
            do {
                asm volatile("ld.relaxed.gpu.global.u32 %1, [%2+8]; ld.acquire.gpu.global.u32 %0, [%2+4];" : "=r"(v1), "=r"(g0) : "l"(gs->bar) : "memory");
            } while ((v1 >= NB) == par && ++spins < (1 << 22));
            if ((v1 >= NB) == par) *flag = 1;
            if (g0 - flag[1] < 30000) flag[1] = g0;
            TSTAMPC(17);
        }
        __syncwarp();
    } else {
        bar_sync(9, NT);
        TSTAMP(21);
        const uint32_t over = lds32(flg);
#pragma unroll
        for (int j = 0; j < 2; j++) {
            if (nk[j] > 0) {
                uint2 h[6];
#pragma unroll
                for (int u = 0; u < 6; u++) h[u] = lds64(sb + SM_POS + ha[j][u] * 8);
                if (over) nk[j] = 0;
#pragma unroll
                for (int u = 0; u < 6; u++)
                    asm volatile("{.reg .pred p; setp.gt.s32 p, %2, %3; @p st.shared.u32 [%0], %1;}"
                                 :: "r"(h[u].x + rk[j][u] * 8), "r"(key[j][u] * 4 + h[u].y + (kidx[j] + (u << 17))), "r"(nk[j]), "r"(u) : "memory");
            }
        }
    }
    bar_sync(1, NT);
    TSTAMP(4);
    if (*flag) {
        slow_path(smem, n0, nn, (const uint16_t*)x, (const int*)src4, (const int*)dst4, (const uint16_t*)Y, (const uint16_t*)ef, w_rad, cg,
                  (const uint16_t*)w_mix, (__nv_bfloat16*)out);
        return;
    }
    {
        const uint4* gp = gs->recs + lane;
        asm volatile("" : "+l"(gp));
        const uint32_t sp = sb + SM_RECS + (w * CELL + lane) * 16, lc = (lane << 24) | 0xFFFFFF;
#pragma unroll
        for (int j = 0; j < 7; j++)
            asm volatile("{.reg .pred p; .reg .u32 l; .reg .u64 a; setp.lt.u32 p, %2, %3; and.b32 l, %3, 0xFFFF; mad.wide.u32 a, l, 128, %1;\n"
                         "@p cp.async.cg.shared.global [%0], [a], 16;}"
                         :: "r"(sp + j * (NW * CELL * 16)), "l"(gp), "r"(lc), "r"(__shfl_sync(0xffffffff, ci, j)) : "memory");
        for (uint32_t m = __ballot_sync(0xffffffff, ci >= (33u << 24)); m; m &= m - 1) {
            const int j = __ffs(m) - 1;
            const uint32_t cj = __shfl_sync(0xffffffff, ci, j);
            if (lane + 32 < (cj >> 24))
                asm volatile("cp.async.cg.shared.global [%0], [%1], 16;" :: "r"(sp + j * (NW * CELL * 16) + 512), "l"(gp + (size_t)(cj & 0xFFFF) * 8 + 32) : "memory");
        }
        asm volatile("cp.async.commit_group;" ::: "memory");
    }
    const int S = __shfl_sync(0xffffffff, max((int)(max(len2 & 0xFFFF, len2 >> 16) + 3) >> 2, DS + 1), 0);
    const int mylen = (lane & 1) ? len2 >> 16 : len2 & 0xFFFF;
    constexpr int NRAW = (CAP + 3) / 4;
    uint32_t bits0 = 0, raw[NRAW];
    unsigned char* meta = smem + SM_META + w * (CAP * STEPB);
    const int la = sb + SM_LIST + w * 2048 + lane * 4, llast = la - (lane & ~1) * 4 + (mylen - 1) * 8;
#pragma unroll
    for (int k = 0; k < NRAW; k++) raw[k] = lds32(min(la + k * 128, llast));
    const uint32_t sv0 = min(raw[0] & 0xFFFC, 4 * (NN - 1));
    const unsigned char* pbase = x + c * 16;
    asm volatile("" : "+l"(pbase));
    auto cpa2 = [&](uint32_t dstp, uint32_t sv) {
        asm volatile("cp.async.cg.shared.global [%0], [%1], 16; cp.async.cg.shared.global [%0+1024], [%1+128], 16;"
                     :: "r"(dstp), "l"(pbase + (size_t)sv * 256) : "memory");
    };
    auto cpa2p = [&](uint32_t dstp, uint32_t sv) {
        asm volatile("{.reg .pred p; setp.ge.s32 p, %2, 0; @p cp.async.cg.shared.global [%0], [%1], 16; @p cp.async.cg.shared.global [%0+1024], [%1+128], 16;}"
                     :: "r"(dstp), "l"(pbase + (size_t)sv * 256), "r"(sv) : "memory");
    };
    auto wait_until = [&](uint32_t tt) {
        asm volatile("{.reg .pred p; .reg .u32 d;\n"
                     "PACE_LOOP: mov.u32 d, %%globaltimer_lo; sub.u32 d, %0, d; setp.lt.u32 p, d, 32768; @p nanosleep.u32 %1; @p bra.uni PACE_LOOP;}"
                     :: "r"(tt), "n"(PSLEEP) : "memory");
    };
    const uint32_t tfill = flag[1] - FOFF;
    auto fill = [&](int i) {
        wait_until(tfill + i * FDT);
        cpa2(wdst + i * SLOTB, __shfl_sync(0xffffffff, sv0, 8 * i + 2 * q)); cpa2(wdst + i * SLOTB + 512, __shfl_sync(0xffffffff, sv0, 8 * i + 2 * q + 1));
        asm volatile("cp.async.commit_group;" ::: "memory");
    };
    fill(0);
    TSTAMP(5);
    auto relay = [&]() {
        uint32_t g0, g1, b0, b1;
        asm volatile("ld.volatile.shared.v2.u32 {%0,%1}, [%4+40]; ld.volatile.shared.v2.u32 {%2,%3}, [%4+16];"
                     : "=r"(g0), "=r"(g1), "=r"(b0), "=r"(b1) : "r"(flg) : "memory");
        const unsigned long long dg = (((unsigned long long)g1 << 32) | g0) - (((unsigned long long)b1 << 32) | b0);
        asm volatile("{.reg .pred p, q; setp.eq.u32 p, %1, 0; setp.lt.u64 q, %2, 30000; @q st.shared.u32 [%3+4], %4;\n"
                     "@p cp.async.cg.shared.global [%3+32], [%0], 16;}"
                     :: "l"(gs->bar), "r"(lane), "l"(dg), "r"(flg), "r"(g0) : "memory");
    };
    auto report = [&](uint32_t cand) {
        uint32_t b0, b1;
        asm volatile("ld.volatile.shared.v2.u32 {%0,%1}, [%2+16];" : "=r"(b0), "=r"(b1) : "r"(flg) : "memory");
        asm volatile("{.reg .pred p; setp.eq.u32 p, %2, 0; @p red.max.relaxed.gpu.global.u64 [%0], %1;}"
                     :: "l"(&gs->t0), "l"((((unsigned long long)b1 << 32) | b0) + (cand - b0)), "r"(lane) : "memory");
    };
    uint32_t ra[NRAW];
#pragma unroll
    for (int k = NRAW - 1; k >= 0; k--) {
        const uint32_t m = (__ballot_sync(0xffffffff, (int)raw[k] < 0) >> g) & 0x01010101u;
        bits0 = __funnelshift_l(m * 0x10204080u, bits0, 4);
        const bool pad = la + k * 128 > llast;
        ra[k] = pad ? NB * CELL * 16 : (raw[k] >> 13) & 0x1FFF0;
        raw[k] = (raw[k] & 0xFFFF) | (pad ? F_PAD : 0);
    }
    if (t < 2) bits0 = ~bits0;
    asm volatile("" : "+r"(bits0), "+r"(ra[0]), "+r"(ra[1]), "+r"(ra[2]), "+r"(ra[3]), "+r"(ra[4]), "+r"(raw[0]), "+r"(raw[1]), "+r"(raw[2]), "+r"(raw[3]), "+r"(raw[4]));
    fill(1);
    asm volatile("cp.async.wait_group 2;" ::: "memory");
    bar_sync(1, NT);
    TSTAMP(19);
    if (w == CW) {
        uint32_t tn; asm volatile("mov.u32 %0, %%globaltimer_lo;" : "=r"(tn));
        if ((int)(tn + RDY - flag[1]) > 0) { report(tn + RDY); flag[1] = tn + RDY; }
    }
    {
        uint4 rv[NRAW];
#pragma unroll
        for (int k = 0; k < NRAW - 1; k++) rv[k] = lds128(ra[k] + (sb + SM_RECS));
        if ((NRAW - 1) * 4 < S) rv[NRAW - 1] = lds128(ra[NRAW - 1] + (sb + SM_RECS));
        fill(2);
        bar_sync(1, NT);
        TSTAMP(12);
        unsigned char* mr = meta + (q - 1) * STEPB + c * 16;
        unsigned char* ms = meta + (q - DS - 1) * STEPB + 128 + c * 4;
#pragma unroll
        for (int k = 0; k < NRAW; k++) {
            if (k == 0) {
                *(uint4*)(mr + (q == 0 ? S * STEPB : 0)) = rv[k];
                *(uint32_t*)(ms + S * STEPB) = raw[0] + F_WRAP;
            } else if (k * 4 + q < S) {
                *(uint4*)(mr + k * 4 * STEPB) = rv[k];
                *(uint32_t*)(ms + k * 4 * STEPB + (k == 1 && q == 0 ? S * STEPB : 0)) = raw[k];
            }
        }
    }
    __syncwarp();
    const uint32_t tphase = PACE / 4;
    uint32_t dreg;
    {
        const int ls = lane >= S ? min(lane - S, S - 1) : lane, st = ls == 0 ? S - 1 : ls - 1;
        const uint4 u0 = *(const uint4*)(meta + st * STEPB + 128), u1 = *(const uint4*)(meta + st * STEPB + 144);
        int pos = (u0.x + u0.y + u0.z + u0.w + u1.x + u1.y + u1.z + u1.w) << 1 >> 6;
        pos += ((u0.x & F_WRAP) ? NN : 0) + (lane >= S ? NN : 0) - NN * (2 * DS + 1) / 32;
        dreg = pos * (int)tphase / NN;
    }
    fill(3);
    TSTAMP(6);

    uint32_t* stash = (uint32_t*)(gs->stash + (b * NW + w) * 256) + lane;
    float acc[4][4];
#pragma unroll
    for (int i = 0; i < 16; i++) acc[i / 4][i % 4] = 0.f;
    uint4 az = *(const uint4*)(smem + SM_AZ + lane * 16);
    uint32_t dcur = dreg, dl = 0, now = flag[1], tcur = 0;
    uint32_t mp = 0, smask = 1, didx = 2;
    uint32_t mend = S * STEPB;
    uint2 r = lds64(mend - STEPB + recl), s0 = lds64(mend - STEPB + srcl);
    auto step = [&](const uint32_t off, const int mode, const bool pc = true) {
        if (mode == 0 && pc) { unsigned long long n64; asm volatile("mov.u64 %0, %%globaltimer;" : "=l"(n64)); now = (uint32_t)n64; }
        const uint2 rc = r, sc = s0;
        if (mode != 4) r = lds64(mp + recl);
        if (mode == 0) s0 = lds64(mp + srcl);
        asm volatile("cp.async.wait_group %0;" :: "n"(DS - 1) : "memory");
        const uint4 xa = lds128(rsrc + off), xb = lds128(rsrc + off + 512), xc = lds128(rsrc + off + 1024), xd = lds128(rsrc + off + 1536);
        if (mode == 0) {
            if (pc) { dl = __shfl_sync(0xffffffff, dcur, didx); didx += 2; }
            cpa2p(wdst + off, sc.x); cpa2p(wdst + off + 512, sc.y);
        }
        if (mode == 1 && w < 16) {
#pragma unroll
            for (int j = 0; j < 4; j++) {
                const int kk = 4 * j + q, ch = 16 * (w & 7) + 2 * (kk & 7) + (kk >> 3);
                asm volatile("cp.async.cg.shared.global [%0], [%1], 16;" :: "r"(ring0 + kk * 128 + ((c ^ (kk & 7)) << 4)), "l"(w_mix + ch * 16 + (w >> 3) * 8 + c) : "memory");
            }
            asm volatile("cp.async.mbarrier.arrive.noinc.shared.b64 [%0];" :: "r"(mbarW) : "memory");
        }
        if (mode == 2 || mode == 3) {
#pragma unroll
            for (int j = 0; j < 4; j += mode - 1)
                asm volatile("cp.async.cg.shared.global [%0], [%1], 16;" :: "r"(ring0 + off + j * 512 + lane * 16), "l"(stash + (mode - 2) * 512 + j * 128 + lane * 3) : "memory");
        }
        if (mode < 4) asm volatile("cp.async.commit_group;" ::: "memory");
        float z[4], y[4], t1[4], t2[4];
        mma1688z(z, az.x, az.y, rc.y);
        mma1688z(y, az.z, az.w, rc.y);
        uint32_t bt;
        asm("{.reg .pred p; .reg .b32 m; and.b32 m, %2, %3; setp.ne.u32 p, m, 0; selp.b32 %0, %1, 0, p;}" : "=r"(bt) : "r"(rc.x), "r"(bits0), "r"(smask));
        mma1688z(t1, at[0], at[1], bt);
        mma1688z(t2, at[2], at[3], bt);
        const uint32_t T0 = pack2(t1[0], t1[2]), T1 = pack2(t2[0], t2[2]), T2 = pack2(t1[1], t1[3]), T3 = pack2(t2[1], t2[3]);
        uint32_t R[8];
#pragma unroll
        for (int i = 0; i < 4; i++) { R[i] = __float_as_uint(silu_h(z[i])); R[4 + i] = __float_as_uint(silu_h(y[i])); }
        mma16816(acc[0], mul_hi(xa.x, R[0]), mul_hi(xa.z, R[2]), mul_hi(xa.y, R[0]), mul_hi(xa.w, R[2]), T0, T1);
        mma16816(acc[1], mul_hi(xb.x, R[1]), mul_hi(xb.z, R[3]), mul_hi(xb.y, R[1]), mul_hi(xb.w, R[3]), T2, T3);
        mma16816(acc[2], mul_hi(xc.x, R[4]), mul_hi(xc.z, R[6]), mul_hi(xc.y, R[4]), mul_hi(xc.w, R[6]), T0, T1);
        mma16816(acc[3], mul_hi(xd.x, R[5]), mul_hi(xd.z, R[7]), mul_hi(xd.y, R[5]), mul_hi(xd.w, R[7]), T2, T3);
        mp += STEPB; smask <<= 1;
    };
    auto putacc = [&](uint32_t* p) {
#pragma unroll
        for (int i = 0; i < 16; i++) acc[i / 4][i % 4] *= 1.0028f;
        p[0] = pack2(acc[0][0], acc[0][1]); p[32] = pack2(acc[0][2], acc[0][3]); p[64] = pack2(acc[2][0], acc[2][1]); p[96] = pack2(acc[2][2], acc[2][3]);
        p[256] = pack2(acc[1][0], acc[1][1]); p[288] = pack2(acc[1][2], acc[1][3]); p[320] = pack2(acc[3][0], acc[3][1]); p[352] = pack2(acc[3][2], acc[3][3]);
    };
    int ph = 0;
    auto phase_end = [&](const int k) {
        az = lds128(sb + SM_AZ + (ph + 1) * 512 + lane * 16);
        putacc(stash + ph * ph * 128);
#pragma unroll
        for (int i = 0; i < 16; i++) acc[i / 4][i % 4] = 0.f;
        pbase += 256; mp = 0; smask = 1; ph++;
        dcur += tphase; didx = 1 + (k & 1);
        if (ph == 3) {
            mend -= DS * STEPB;
            dcur += (int)(dcur - __shfl_sync(0xffffffff, dcur, 0)) * (((w >> 2) - 2) * FAN) >> 8;
        }
        WSTAMP(ph - 1);
    };
    uint32_t t0 = now;
    if (w == PW) {
        asm volatile("mov.u32 %0, %%globaltimer_lo;" : "=r"(now));
        now += PTOL - PTOL0;
    }
    const uint32_t bias = w == RW ? 1u << 20 : 0;
    if (w == RW) relay();
    dcur += bias;
    auto body = [&](const int k) -> bool {
        if (k == 2) asm volatile("ld.volatile.shared.u32 %0, [%1+4];" : "=r"(t0) : "r"(flg));
        const bool pc = k & 1;
        step(k * SLOTB, 0, pc);
        if (!pc) {
            if (mp == mend) phase_end(k);
        } else if (mp == mend || now < dl) {
            if (mp == mend) {
                if (k == 3 && ph == 3) return true;
                phase_end(k);
            }
            if (w == RW) { dl -= 1u << 20; relay(); }
            wait_until(dl);
        }
        return false;
    };
    {
        const uint32_t d0 = __shfl_sync(0xffffffff, dreg, 0);
        if (w == RW) {
            uint32_t g0, tn; int spins = 0;
            do {
                asm volatile("ld.relaxed.gpu.global.u32 %0, [%2]; mov.u32 %1, %%globaltimer_lo;" : "=r"(g0), "=r"(tn) : "l"(&gs->t0) : "memory");
                if (g0 - t0 < 30000) { t0 = g0; flag[1] = g0; }
            } while (__shfl_sync(0xffffffff, t0 - tn, 0) < 32768 && ++spins < 64);
        }
        asm volatile("{.reg .pred p; .reg .u32 d;\n"
                     "PACE_LOOP: ld.volatile.shared.u32 %0, [%2+4]; mov.u32 d, %%globaltimer_lo; sub.u32 d, %1, d; add.u32 d, d, %0;\n"
                     "setp.lt.u32 p, d, 32768; @p nanosleep.u32 32; @p bra.uni PACE_LOOP;}"
                     : "=&r"(t0) : "r"(d0), "r"(flg) : "memory");
    }
    while (true) {
        if (w == PW) {
            const uint32_t cand = now - dl + tcur - PTOL;
            if ((int)(cand - t0) > 0) report(cand);
        }
        dcur += t0 - tcur; tcur = t0;
        body(0); body(1); body(2);
        if (body(3)) break;
    }
    __syncwarp();
    step(0, 1);
    { uint32_t tn; asm volatile("mov.u32 %0, %%globaltimer_lo;" : "=r"(tn)); wait_until(tn + (w >> 2) * TDEL); }
    step(SLOTB, 2); step(2 * SLOTB, 3); step(3 * SLOTB, 4);
    WSTAMP(3); ESTAMP(0);

    {
        putacc((uint32_t*)(smem + SM_RING + 2 * SLOTB + w * 2048 + 512) + lane);
        const int wg = w >> 2, w4 = w & 3;
        int nd[8];
#pragma unroll
        for (int j = 0; j < 8; j++) { const int l = wg * 8 + j; nd[j] = order[(t >> 1) ? 79 - l : l]; asm volatile("" : "+r"(nd[j])); }
        const bool odd = t & 1;
        uint2* ob = (uint2*)out + (size_t)n0 * 128 + w4 * 16 + g + (odd ? 8 : 0);
        asm volatile("cp.async.wait_all;" ::: "memory");
        mbar_wait(mbarW, 0);
        asm volatile("fence.proxy.async.shared::cta;" ::: "memory");
        ESTAMP(1);
        bar_sync(2 + wg, 128);
        uint32_t ticket = 0;
        if ((tid & 127) == 0) {
            asm volatile("atom.shared.add.u32 %0, [%1+48], 1;" : "=r"(ticket) : "r"(flg) : "memory");
            int spins = 0;
            while (flag[13] < ticket && ++spins < (1 << 16)) __nanosleep(40);
        }
        bar_sync(2 + wg, 128);
        const uint64_t descA0 = (uint64_t)(((sb + SM_RING) & 0x3FFFF) >> 4) | ((uint64_t)1 << 16) | ((uint64_t)(1024 >> 4) << 32) | ((uint64_t)1 << 62);
        const uint64_t descB0 = (uint64_t)(((sb + SM_RING + SLOTB + wg * 8192) & 0x3FFFF) >> 4) | ((uint64_t)(128 >> 4) << 16) | ((uint64_t)(1024 >> 4) << 32);
        float d[2][32];
        asm volatile("wgmma.fence.sync.aligned;" ::: "memory");
        ESTAMP(2);
#pragma unroll
        for (int mt = 0; mt < 2; mt++) {
#pragma unroll
            for (int ks = 0; ks < 8; ks++) {
                if (mt * 8 + ks == RELK)
                    asm volatile("{.reg .pred p; setp.eq.u32 p, %1, 0; @p st.volatile.shared.u32 [%0+52], %2;}" :: "r"(flg), "r"(tid & 127), "r"(ticket + 1) : "memory");
                const uint64_t da = descA0 + (uint64_t)((ks * 2048 + mt * 16384) >> 4), db = descB0 + (uint64_t)(((ks & 3) * 256 + (ks >> 2) * SLOTB) >> 4);
                asm volatile("{.reg .pred p; setp.ne.b32 p, %34, 0;\n"
                    "wgmma.mma_async.sync.aligned.m64n64k16.f32.bf16.bf16 "
                    "{%0,%1,%2,%3,%4,%5,%6,%7,%8,%9,%10,%11,%12,%13,%14,%15,%16,%17,%18,%19,%20,%21,%22,%23,%24,%25,%26,%27,%28,%29,%30,%31}, %32, %33, p, 1, 1, 1, 1;}"
                    : "+f"(d[mt][0]), "+f"(d[mt][1]), "+f"(d[mt][2]), "+f"(d[mt][3]), "+f"(d[mt][4]), "+f"(d[mt][5]), "+f"(d[mt][6]), "+f"(d[mt][7]),
                      "+f"(d[mt][8]), "+f"(d[mt][9]), "+f"(d[mt][10]), "+f"(d[mt][11]), "+f"(d[mt][12]), "+f"(d[mt][13]), "+f"(d[mt][14]), "+f"(d[mt][15]),
                      "+f"(d[mt][16]), "+f"(d[mt][17]), "+f"(d[mt][18]), "+f"(d[mt][19]), "+f"(d[mt][20]), "+f"(d[mt][21]), "+f"(d[mt][22]), "+f"(d[mt][23]),
                      "+f"(d[mt][24]), "+f"(d[mt][25]), "+f"(d[mt][26]), "+f"(d[mt][27]), "+f"(d[mt][28]), "+f"(d[mt][29]), "+f"(d[mt][30]), "+f"(d[mt][31])
                    : "l"(da), "l"(db), "r"(ks));
            }
            asm volatile("wgmma.commit_group.sync.aligned;" ::: "memory");
        }
#pragma unroll
        for (int mt = 0; mt < 2; mt++) {
            if (mt == 0) asm volatile("wgmma.wait_group.sync.aligned 1;" ::: "memory");
            else asm volatile("wgmma.wait_group.sync.aligned 0;" ::: "memory");
            ESTAMP(3 + mt);
#pragma unroll
            for (int i = 0; i < 32; i++) asm volatile("" : "+f"(d[mt][i]) :: "memory");
#pragma unroll
            for (int j = 0; j < 8; j++) {
                const uint32_t v0 = pack2(d[mt][4 * j], d[mt][4 * j + 1]), v1 = pack2(d[mt][4 * j + 2], d[mt][4 * j + 3]);
                const uint32_t rv = __shfl_xor_sync(0xffffffff, odd ? v0 : v1, 1);
                if (nd[j] < nn) ob[nd[j] * 128 + mt * 64] = odd ? make_uint2(rv, v1) : make_uint2(v0, rv);
            }
        }
    }
    TSTAMP(8); ESTAMP(5);
}

__global__ void __launch_bounds__(NT, 1)
tfn_fallback(const uint16_t* x, const int* src, const int* dst, const uint16_t* Y, const uint16_t* ef, const uint16_t* w_rad,
             const uint16_t* cg, const uint16_t* w_mix, __nv_bfloat16* out) {
    extern __shared__ __align__(1024) unsigned char smem[];
    const int n0 = blockIdx.x * NPB;
    slow_path(smem, n0, min(NPB, NN - n0), x, src, dst, Y, ef, w_rad, cg, w_mix, out);
}

}

extern "C" void kernel_launch(void* const* d_in, const int* in_sizes, int n_in, void* d_out, int out_size) {
    (void)in_sizes; (void)n_in; (void)out_size;
    cudaFuncSetAttribute(tfn_kernel, cudaFuncAttributeMaxDynamicSharedMemorySize, SM_TOTAL);
    int dev = 0, sms = 0;
    cudaGetDevice(&dev);
    cudaDeviceGetAttribute(&sms, cudaDevAttrMultiProcessorCount, dev);
    if (sms < NB) {
        cudaFuncSetAttribute(tfn_fallback, cudaFuncAttributeMaxDynamicSharedMemorySize, NPB * 2048);
        tfn_fallback<<<NB, NT, NPB * 2048, cudaStreamPerThread>>>((const uint16_t*)d_in[0], (const int*)d_in[1], (const int*)d_in[2], (const uint16_t*)d_in[3],
            (const uint16_t*)d_in[4], (const uint16_t*)d_in[5], (const uint16_t*)d_in[6], (const uint16_t*)d_in[7], (__nv_bfloat16*)d_out);
        return;
    }
    Scratch* gs = nullptr;
    cudaGetSymbolAddress((void**)&gs, g_scratch);
    cudaLaunchConfig_t cfg = {};
    cfg.gridDim = dim3(NB); cfg.blockDim = dim3(NT); cfg.dynamicSmemBytes = SM_TOTAL; cfg.stream = cudaStreamPerThread;
    cudaLaunchAttribute at[1];
    at[0].id = cudaLaunchAttributeCooperative; at[0].val.cooperative = 1;
    cfg.attrs = at; cfg.numAttrs = 1;
    cudaLaunchKernelEx(&cfg, tfn_kernel, (const unsigned char*)d_in[0], (const int4*)d_in[1], (const int4*)d_in[2],
                       (const uint4*)d_in[3], (const uint4*)d_in[4], (const uint16_t*)d_in[5], (const uint16_t*)d_in[6],
                       (const uint4*)d_in[7], (uint32_t*)d_out, gs);
}
```

```cpp
#include <cuda_runtime.h>
#include <cuda_bf16.h>
#include <stdint.h>

namespace {

constexpr int NN = 10000;
constexpr int NE = 320000;
constexpr int NB = 132;
constexpr int NW = 20;
constexpr int NT = NW * 32;
constexpr int CW = NW - 1;
constexpr int PW = 10;
constexpr int RW = 1;
constexpr int NPB = 76;
constexpr int CELL = 48;
constexpr int RCH = 2880;
constexpr int CAP = 19;
constexpr int DS = 4;
constexpr int STEPB = 160;
constexpr int NE4 = NE / 4;
constexpr int NPIECE = NB * 8;
constexpr int KB = 320, KN = 32 * KB;
constexpr uint32_t F_PAD = 0x80000000u;
constexpr uint32_t F_WRAP = 1;

constexpr int SLOTB = NW * 2048;
constexpr int SM_RING = 0;
constexpr int SM_META = SM_RING + DS * SLOTB;
constexpr int SM_AZ = SM_META + NW * CAP * STEPB;
constexpr int SM_MISC = SM_AZ + 2048;
constexpr int SM_TOTAL = SM_MISC + 2048;
constexpr int SM_STAGE = SM_RING;
constexpr int SM_HIST = SM_RING + 25600;
constexpr int SM_POS = SM_RING;
constexpr int SM_SMALL = SM_HIST + 13056;
constexpr int SM_LIST = SM_RING + SLOTB;
constexpr int SM_ROUT = SM_RING + 2 * SLOTB;
constexpr int SM_RECS = SM_RING + 3 * SLOTB;
constexpr int SM_RAWY = SM_META;
constexpr int SM_RAWE = SM_RAWY + 608 * 32;
constexpr int SM_KEYS = SM_RAWE + 608 * 32;
static_assert(SM_TOTAL <= 232448 && SM_KEYS + NPIECE * 16 <= SM_AZ, "smem");
static_assert(SM_RECS + NB * CELL * 16 + 16 <= SM_AZ && SM_KEYS + NPIECE * 16 <= SM_RECS + NB * CELL * 16 && SM_SMALL + 1152 <= SLOTB && DS == 4, "smem");

struct Scratch {
    uint4 keys[NB * NPIECE];
    uint4 recs[NB * RCH];
    uint4 stash[NB * NW * 256];
    unsigned bar[2];
    unsigned long long t0;
};
__device__ Scratch g_scratch;
#define TSTAMP(i)
#define TSTAMPC(i)
#define WSTAMP(i)
#define ESTAMP(i)

__device__ __forceinline__ void mma16816(float* d, uint32_t a0, uint32_t a1, uint32_t a2, uint32_t a3, uint32_t b0, uint32_t b1) {
    asm("mma.sync.aligned.m16n8k16.row.col.f32.bf16.bf16.f32 {%0,%1,%2,%3}, {%4,%5,%6,%7}, {%8,%9}, {%0,%1,%2,%3};"
        : "+f"(d[0]), "+f"(d[1]), "+f"(d[2]), "+f"(d[3]) : "r"(a0), "r"(a1), "r"(a2), "r"(a3), "r"(b0), "r"(b1));
}
__device__ __forceinline__ void mma1688z(float* d, uint32_t a0, uint32_t a1, uint32_t b0) {
    asm("mma.sync.aligned.m16n8k8.row.col.f32.bf16.bf16.f32 {%0,%1,%2,%3}, {%4,%5}, {%6}, {%7,%7,%7,%7};"
        : "=f"(d[0]), "=f"(d[1]), "=f"(d[2]), "=f"(d[3]) : "r"(a0), "r"(a1), "r"(b0), "f"(0.f));
}
__device__ __forceinline__ uint32_t pack2(float lo, float hi) {
    uint32_t r; asm("cvt.rn.bf16x2.f32 %0, %1, %2;" : "=r"(r) : "f"(hi), "f"(lo)); return r;
}
__device__ __forceinline__ float silu_h(float h) {
    float t; asm("tanh.approx.f32 %0, %1;" : "=f"(t) : "f"(h)); return fmaf(h, t, h);
}
__device__ __forceinline__ uint32_t mul_lo(uint32_t v, uint32_t r) {
    __nv_bfloat162 a = *(__nv_bfloat162*)&v, b = *(__nv_bfloat162*)&r; __nv_bfloat162 c = __hmul2(a, __low2bfloat162(b)); return *(uint32_t*)&c;
}
__device__ __forceinline__ uint32_t mul_hi(uint32_t v, uint32_t r) {
    __nv_bfloat162 a = *(__nv_bfloat162*)&v, b = *(__nv_bfloat162*)&r; __nv_bfloat162 c = __hmul2(a, __high2bfloat162(b)); return *(uint32_t*)&c;
}
__device__ __forceinline__ uint32_t lds32(uint32_t a) {
    uint32_t r; asm volatile("ld.shared.u32 %0, [%1];" : "=r"(r) : "r"(a) : "memory"); return r;
}
__device__ __forceinline__ void sts32(uint32_t a, uint32_t v) { asm volatile("st.shared.u32 [%0], %1;" :: "r"(a), "r"(v) : "memory"); }
__device__ __forceinline__ uint2 lds64(uint32_t a) {
    uint2 r; asm volatile("ld.shared.v2.u32 {%0,%1}, [%2];" : "=r"(r.x), "=r"(r.y) : "r"(a)); return r;
}
__device__ __forceinline__ uint4 lds128(uint32_t a) {
    uint4 r; asm volatile("ld.shared.v4.u32 {%0,%1,%2,%3}, [%4];" : "=r"(r.x), "=r"(r.y), "=r"(r.z), "=r"(r.w) : "r"(a) : "memory"); return r;
}
__device__ __forceinline__ void bar_sync(int id, int n) { asm volatile("bar.sync %0, %1;" :: "r"(id), "r"(n) : "memory"); }
__device__ __forceinline__ void bar_arrive(int id, int n) { asm volatile("bar.arrive %0, %1;" :: "r"(id), "r"(n) : "memory"); }
__device__ __forceinline__ void mbar_wait(uint32_t bar, uint32_t ph) {
    uint32_t done; int spins = 0;
    do {
        asm volatile("{.reg .pred p; mbarrier.try_wait.parity.shared.b64 p, [%1], %2; selp.u32 %0,1,0,p;}" : "=r"(done) : "r"(bar), "r"(ph) : "memory");
    } while (!done && ++spins < (1 << 22));
}
__device__ __forceinline__ void gbar_arrive(unsigned* ctr) {
    asm volatile("red.inc.relaxed.gpu.global.u32 [%0], %1;" :: "l"(ctr), "n"(2 * NB - 1) : "memory");
}
__device__ __forceinline__ int chunk_start4(int c) { return (c * NE4) / NB; }
__device__ __forceinline__ float bf2f(uint32_t h) { return __uint_as_float(h << 16); }

__device__ __noinline__ void slow_path(unsigned char* smem, int n0, int nn, const uint16_t* x, const int* src, const int* dst,
                                       const uint16_t* Y, const uint16_t* ef, const uint16_t* w_rad, const uint16_t* cg,
                                       const uint16_t* w_mix, __nv_bfloat16* out) {
    float* agg = (float*)smem;
    const int tid = threadIdx.x, lane = tid & 31, w = tid >> 5;
    bar_sync(1, NT);
    for (int i = tid; i < NPB * 512; i += NT) agg[i] = 0.f;
    bar_sync(1, NT);
    for (int e0 = w * 32; e0 < NE; e0 += NT) {
        int dl = dst[e0 + lane] - n0;
        unsigned m = __ballot_sync(0xffffffff, dl >= 0 && dl < nn);
        while (m) {
            int l = __ffs(m) - 1; m &= m - 1;
            int e = e0 + l, d = __shfl_sync(0xffffffff, dl, l), s = src[e];
            float T[16];
            for (int i = 0; i < 4; i++) for (int o = 0; o < 4; o++) {
                float a = 0.f;
                for (int f = 0; f < 4; f++) a += bf2f(Y[e * 4 + f]) * bf2f(cg[i * 16 + f * 4 + o]);
                T[i * 4 + o] = a;
            }
            for (int k = 0; k < 4; k++) {
                int c = lane + 32 * k;
                float z = 0.f;
                for (int j = 0; j < 4; j++) z += bf2f(ef[e * 4 + j]) * bf2f(w_rad[j * 128 + c]);
                float R = z / (1.f + __expf(-z));
                for (int o = 0; o < 4; o++) {
                    float a = 0.f;
                    for (int i = 0; i < 4; i++) a += bf2f(x[(size_t)s * 512 + c * 4 + i]) * T[i * 4 + o];
                    atomicAdd(&agg[d * 512 + c * 4 + o], R * a);
                }
            }
        }
    }
    bar_sync(1, NT);
    for (int i = tid; i < nn * 512; i += NT) {
        int n = i >> 9, d = (i >> 2) & 127, o = i & 3;
        float a = 0.f;
        for (int c = 0; c < 128; c++) a += agg[n * 512 + c * 4 + o] * bf2f(w_mix[c * 128 + d]);
        out[(size_t)(n0 + n) * 512 + (i & 511)] = __float2bfloat16(a);
    }
}

#define PACE 23000
#define YDELAY 300
#define POFF 3600
#define PSLEEP 64
#define FDT 350
#define FOFF 1500
#define RELK 12
#define FAN 16
#define TDEL 100
#define RDY 600
#define PTOL0 300
#define PTOL 1100
__global__ void __launch_bounds__(NT, 1)
tfn_kernel(const unsigned char* __restrict__ x, const int4* __restrict__ src4, const int4* __restrict__ dst4,
           const uint4* __restrict__ Y, const uint4* __restrict__ ef, const uint16_t* __restrict__ w_rad,
           const uint16_t* __restrict__ cg, const uint4* __restrict__ w_mix, uint32_t* __restrict__ out, Scratch* __restrict__ gs) {
    extern __shared__ __align__(1024) unsigned char smem[];
    const uint32_t sb = (uint32_t)__cvta_generic_to_shared(smem);
    const int b = blockIdx.x, tid = threadIdx.x, lane = tid & 31, g = lane >> 2, t = lane & 3;
    const int w = __shfl_sync(0xffffffff, tid >> 5, 0);
    uint32_t* stage = (uint32_t*)(smem + SM_STAGE);
    uint32_t* hist = (uint32_t*)(smem + SM_HIST);
    uint32_t* cnt = (uint32_t*)(smem + SM_MISC);
    uint32_t* deg = cnt + 136;
    uint32_t* order = deg + 104;
    uint32_t* cnt2 = order + 80;
    volatile uint32_t* flag = cnt2 + 136;
    const uint32_t mbarK = sb + SM_MISC + 1920, mbarR = mbarK + 8, mbarW = mbarK + 16;
    const int n0 = b * NPB, nn = min(NPB, NN - n0);
    TSTAMP(0);

    const int c0 = chunk_start4(b), c1 = chunk_start4(b + 1);
    const bool has4 = c0 + tid < c1;
    int4 d4 = make_int4(0, 0, 0, 0), s4 = d4;
    if (has4) { d4 = __ldg(dst4 + c0 + tid); s4 = __ldg(src4 + c0 + tid); }
    unsigned par = 0;
    if (tid == NT - 1) {
        asm volatile("ld.relaxed.gpu.global.u32 %0, [%1];" : "=r"(par) : "l"(gs->bar) : "memory");
        asm volatile("mbarrier.init.shared.b64 [%0], 1;" :: "r"(mbarK));
        asm volatile("mbarrier.init.shared.b64 [%0], 1;" :: "r"(mbarR));
        asm volatile("mbarrier.init.shared.b64 [%0], 512;" :: "r"(mbarW));
        asm volatile("fence.mbarrier_init.release.cluster;" ::: "memory");
        flag[0] = 0; flag[12] = 0; flag[13] = 0; flag[15] = 0;
    }
    if (w == CW) {
        asm volatile("cp.async.cg.shared.global [%0], [%1], 16;" :: "r"(sb + SM_SMALL + lane * 16), "l"(w_rad + lane * 8) : "memory");
        asm volatile("cp.async.cg.shared.global [%0], [%1], 16;" :: "r"(sb + SM_SMALL + 512 + lane * 16), "l"(w_rad + 256 + lane * 8) : "memory");
        if (lane < 8) asm volatile("cp.async.cg.shared.global [%0], [%1], 16;" :: "r"(sb + SM_SMALL + 1024 + lane * 16), "l"(cg + lane * 8) : "memory");
    }
    ((uint4*)hist)[tid] = make_uint4(0, 0, 0, 0);
    {
        const uint32_t dk = (80 + b % 22) * KN + (b & 31) * KB;
#pragma unroll
        for (int j = 0; j < 3; j++) if (tid + j * NT < NB * CELL / 4) ((uint4*)stage)[tid + j * NT] = make_uint4(dk, dk, dk, dk);
    }
    if (tid < 136) cnt[tid] = 0;
    if (tid == 0) { *(uint4*)(smem + SM_MISC + 1824 + 32) = make_uint4(0, 0, 0, 0); *(uint4*)(smem + SM_RECS + NB * CELL * 16) = make_uint4(0, 0, 0, 0); }
    if (tid < 80) { deg[tid] = 127 - tid; order[tid] = tid; }
    __syncthreads();
    TSTAMP(9);
    if (tid == 64) {
        __nanosleep(YDELAY);
        asm volatile("mbarrier.arrive.expect_tx.shared.b64 _, [%0], %1;" :: "r"(mbarR), "r"((c1 - c0) * 64) : "memory");
        asm volatile("cp.async.bulk.shared::cluster.global.mbarrier::complete_tx::bytes [%0], [%1], %2, [%3];"
                     :: "r"(sb + SM_RAWY), "l"(Y + 2 * c0), "r"((c1 - c0) * 32), "r"(mbarR) : "memory");
        asm volatile("cp.async.bulk.shared::cluster.global.mbarrier::complete_tx::bytes [%0], [%1], %2, [%3];"
                     :: "r"(sb + SM_RAWE), "l"(ef + 2 * c0), "r"((c1 - c0) * 32), "r"(mbarR) : "memory");
    }

    uint32_t bin[4] = {0, 0, 0, 0}, slot[4] = {0, 0, 0, 0};
    if (has4) {
        const uint32_t dd[4] = {(uint32_t)d4.x, (uint32_t)d4.y, (uint32_t)d4.z, (uint32_t)d4.w}, ss[4] = {(uint32_t)s4.x, (uint32_t)s4.y, (uint32_t)s4.z, (uint32_t)s4.w};
#pragma unroll
        for (int k = 0; k < 4; k++) { bin[k] = dd[k] / NPB; slot[k] = atomicAdd(&cnt[bin[k]], 1); }
#pragma unroll
        for (int k = 0; k < 4; k++) stage[bin[k] * CELL + min(slot[k], CELL - 1)] = (dd[k] - bin[k] * NPB) * KN + ss[k];
    }
    if (w == CW) {
        if (tid == NT - 1) { par = par >= NB; flag[14] = (par ^ 1) << 31; }
        asm volatile("cp.async.wait_all;" ::: "memory");
    }
    bar_sync(1, NT);
    TSTAMP(1);
    const uint32_t tag = flag[14];
#pragma unroll
    for (int j = 0; j < 2; j++) {
        const int i = tid + j * NT;
        if (i < NPIECE) {
            const uint2 sa = *(const uint2*)(stage + i * 6), sc = *(const uint2*)(stage + i * 6 + 2);
            uint2 se = *(const uint2*)(stage + i * 6 + 4);
            const uint32_t cf = cnt[i >> 3], cn = min(cf, 63u);
            if ((i & 7) == 7) {
                const uint32_t al = cf > CELL - 8 ? 7 : 0;
                uint32_t o;
                asm volatile("atom.shared.add.u32 %0, [%1], %2;" : "=r"(o) : "r"(sb + SM_MISC + 1824 + 60), "r"(cf + al) : "memory");
                se.y = (o + al) & ~al;
                cnt2[i >> 3] = se.y;
            }
            asm volatile("{.reg .b64 lo, hi; mov.b64 lo, {%1,%2}; mov.b64 hi, {%3,%4}; st.relaxed.gpu.global.v2.b64 [%0], {lo, hi};}"
                         :: "l"(gs->keys + ((i >> 3) * NB + b) * 8 + ((i ^ b) & 7)),
                            "r"(sa.x | (se.x << 20)), "r"(sa.y | ((se.x >> 12) << 20) | ((cn & 7) << 28) | tag),
                            "r"(sc.x | (se.y << 20)), "r"(sc.y | ((se.y >> 12) << 20) | ((cn >> 3) << 28) | tag) : "memory");
        }
    }
    bar_sync(1, NT);
    if (tid == NT - 1) {
        TSTAMPC(10);
        gbar_arrive(&gs->bar[0]);
        asm volatile("mbarrier.arrive.expect_tx.shared.b64 _, [%0], %1;" :: "r"(mbarK), "r"(NPIECE * 16) : "memory");
        unsigned v; int spins = 0;
        do { asm volatile("ld.relaxed.gpu.global.u32 %0, [%1];" : "=r"(v) : "l"(gs->bar) : "memory"); } while ((v >= NB) == par && ++spins < (1 << 22));
        TSTAMPC(13);
        asm volatile("fence.proxy.async.global;" ::: "memory");
        asm volatile("cp.async.bulk.shared::cluster.global.mbarrier::complete_tx::bytes [%0], [%1], %2, [%3];"
                 :: "r"(sb + SM_KEYS), "l"(gs->keys + b * NPIECE), "r"(NPIECE * 16), "r"(mbarK) : "memory");
    }
    __syncwarp();
    uint32_t at[4];
    {
        const int o = g & 3, f = 2 * (t & 1);
#pragma unroll
        for (int i = 0; i < 4; i++) {
            const uint16_t* cp = (const uint16_t*)(smem + SM_SMALL + 1024) + i * 16 + f * 4 + o;
            at[i] = (t >> 1) == (g >> 2) ? cp[0] | ((uint32_t)cp[4] << 16) : 0;
        }
    }

    const int q = lane >> 3, c = lane & 7;
    const uint32_t ring0 = sb + SM_RING + w * 2048;
    uint32_t wdst = ring0 + q * 128 + ((c + 2 * q) & 7) * 16;
    uint32_t rsrc = ring0 + t * 128 + ((g + 2 * t) & 7) * 16;
    uint32_t recl = sb + SM_META + w * (CAP * STEPB) + g * 16 + (t & 1) * 8, srcl = sb + SM_META + w * (CAP * STEPB) + 128 + q * 8;
    uint32_t flg = sb + SM_MISC + (136 + 104 + 80 + 136) * 4;
    asm volatile("" : "+r"(wdst), "+r"(rsrc), "+r"(recl), "+r"(srcl), "+r"(flg));
    auto setflag = [&]() { sts32(flg, 1); };
    uint32_t key[2][6], ha[2][6], rk[2][6], kidx[2], ka[2], kc[2];
    int nk[2];
#pragma unroll
    for (int j = 0; j < 2; j++) {
        const int i0 = j ? 2 * 608 - 1 - tid : tid, i = min(i0, NPIECE - 1), r = i / NB, cc = i - r * NB;
        ka[j] = sb + SM_KEYS + (cc * 8 + ((r ^ cc) & 7)) * 16;
        kidx[j] = (cc * CELL + r * 6) << 17;
        kc[j] = sb + SM_MISC + cc * 4;
        nk[j] = i0 < NPIECE && w < CW ? -6 * r : -1000;
    }
    asm volatile("" : "+r"(at[0]), "+r"(at[1]), "+r"(at[2]), "+r"(at[3]), "+r"(ka[0]), "+r"(ka[1]), "+r"(kidx[0]), "+r"(kidx[1]), "+r"(kc[0]), "+r"(kc[1]), "+r"(nk[0]), "+r"(nk[1]));
    if (w == CW) {
        __syncwarp();
        bar_sync(7, NT);
        if (tid == NT - 1) {
            TSTAMPC(11);
            asm volatile("cp.async.bulk.global.shared::cta.bulk_group [%0], [%1], %2;"
                         :: "l"(gs->recs + b * RCH), "r"(sb + SM_ROUT), "r"(((flag[15] + 1) & ~1u) * 16) : "memory");
            asm volatile("cp.async.bulk.commit_group;" ::: "memory");
            mbar_wait(mbarK, 0);
            unsigned long long tbase;
            asm volatile("mov.u64 %0, %%globaltimer;" : "=l"(tbase));
            tbase += POFF;
            flag[1] = (uint32_t)tbase; flag[4] = (uint32_t)tbase; flag[5] = (uint32_t)(tbase >> 32);
            asm volatile("red.max.relaxed.gpu.global.u64 [%0], %1;" :: "l"(&gs->t0), "l"(tbase) : "memory");
            if (b < 128) asm volatile("cp.async.bulk.prefetch.L2.global [%0], 256;" :: "l"(w_mix + b * 16));
            asm volatile("cp.async.bulk.wait_group 0;" ::: "memory");
            TSTAMPC(14);
            gbar_arrive(&gs->bar[1]);
            TSTAMPC(15);
        }
    } else {
        if (w < 8) {
            const uint32_t* wp = (const uint32_t*)(smem + SM_SMALL) + (t & 1) * 128 + 8 * w + g;
            const uint32_t wr0 = t < 2 ? wp[0] : 0, wr1 = t < 2 ? wp[64] : 0;
            *(uint2*)(smem + SM_AZ + (w >> 1) * 512 + lane * 16 + (w & 1) * 8) =
                make_uint2(pack2(0.5f * bf2f(wr0 & 0xFFFF), 0.5f * bf2f(wr1 & 0xFFFF)), pack2(0.5f * bf2f(wr0 >> 16), 0.5f * bf2f(wr1 >> 16)));
        }
        const bool sw = g & 1;
        uint32_t rp[4];
#pragma unroll
        for (int k = 0; k < 4; k++) rp[k] = cnt2[bin[k]] + slot[k];
        uint4* ro = (uint4*)(smem + SM_ROUT);
        uint4 *p0 = ro + (sw ? rp[2] : rp[0]), *p1 = ro + (sw ? rp[3] : rp[1]), *p2 = ro + (sw ? rp[0] : rp[2]), *p3 = ro + (sw ? rp[1] : rp[3]);
        const uint32_t ya = sb + SM_RAWY + tid * 32 + (sw ? 16 : 0);
        mbar_wait(mbarR, 0);
        TSTAMP(18);
        if (has4) {
            const uint4 y0 = lds128(ya), e0 = lds128(ya + (SM_RAWE - SM_RAWY)), y1 = lds128(ya ^ 16), e1 = lds128((ya ^ 16) + (SM_RAWE - SM_RAWY));
            *p0 = make_uint4(y0.x, e0.x, y0.y, e0.y); *p1 = make_uint4(y0.z, e0.z, y0.w, e0.w);
            *p2 = make_uint4(y1.x, e1.x, y1.y, e1.y); *p3 = make_uint4(y1.z, e1.z, y1.w, e1.w);
        }
        asm volatile("fence.proxy.async.shared::cta;" ::: "memory");
        bar_arrive(7, NT);
    }
    __syncwarp();
    TSTAMP(2);

    if (w < CW) {
        mbar_wait(mbarK, 0);
        TSTAMP(3);
        uint4 v[2] = {lds128(ka[0]), lds128(ka[1])};
        if ((int)((v[0].y ^ tag) | (v[0].w ^ tag) | (v[1].y ^ tag) | (v[1].w ^ tag)) < 0) {
#pragma unroll
            for (int j = 0; j < 2; j++) {
                int spins = 0;
#pragma unroll 1
                while ((int)((v[j].y ^ tag) | (v[j].w ^ tag)) < 0) {
                    asm volatile("{.reg .b64 lo, hi; ld.relaxed.gpu.global.v2.b64 {lo, hi}, [%4]; mov.b64 {%0,%1}, lo; mov.b64 {%2,%3}, hi;}"
                                 : "=r"(v[j].x), "=r"(v[j].y), "=r"(v[j].z), "=r"(v[j].w) : "l"((const unsigned char*)(gs->keys + b * NPIECE) + (ka[j] - sb - SM_KEYS)) : "memory");
                    if (++spins > (1 << 20)) { setflag(); break; }
                }
            }
        }
#pragma unroll
        for (int j = 0; j < 2; j++) {
            const uint32_t hc = ((v[j].y >> 28) & 7) | ((v[j].w >> 25) & 0x38);
            if (j == 1 && nk[j] == -42) {
                sts32(kc[j], hc | ((v[j].z >> 20) << 8));
                if (hc > CELL - 1) setflag();
                v[j].w |= ((80 * KN) >> 12) << 20;
            }
            nk[j] += hc;
            if (nk[j] > 0) {
                key[j][0] = v[j].x & 0xFFFFF; key[j][1] = v[j].y & 0xFFFFF; key[j][2] = v[j].z & 0xFFFFF; key[j][3] = v[j].w & 0xFFFFF;
                key[j][4] = (v[j].x >> 20) | ((v[j].y >> 8) & 0xFF000); key[j][5] = (v[j].z >> 20) | ((v[j].w >> 8) & 0xFF000);
#pragma unroll
                for (int u = 0; u < 6; u++) {
                    ha[j][u] = __umulhi(key[j][u], 0xFFFFFFFFu / KB + 1);
                    asm volatile("{.reg .u32 a, n; mad.lo.u32 a, %1, 4, %2; atom.shared.add.u32 %0, [a+%3], 1;\n"
                                 "shr.u32 n, %1, 5; mad.lo.u32 a, n, 4, %2; red.shared.add.u32 [a+%4], 128;}"
                                 : "=r"(rk[j][u]) : "r"(ha[j][u]), "r"(sb), "n"(SM_HIST), "n"(SM_MISC + 136 * 4) : "memory");
                }
            }
        }
        bar_sync(9, NT - 32);
        TSTAMP(20);
        const int n = tid >> 3, sub = tid & 7;
        const uint32_t me = deg[n];
        uint32_t r = 0, r2 = 0;
#pragma unroll
        for (int k = 0; k < 5; k++) { const uint2 dd = *(const uint2*)(deg + sub * 10 + 2 * k); r += (me - dd.x) >> 31; r2 += (me - dd.y) >> 31; }
        r += r2;
#pragma unroll
        for (int j = 0; j < 2; j++) kidx[j] += (lds32(kc[j]) & 0x700) << 9;
        r += __shfl_xor_sync(0xffffffff, r, 1); r += __shfl_xor_sync(0xffffffff, r, 2); r += __shfl_xor_sync(0xffffffff, r, 4);
        if (sub == 0) order[r] = n;
    }
    bar_sync(1, NT);
    TSTAMP(22);
    uint32_t len2;
    {
        const uint2 na = *(const uint2*)(order + 2 * w);
        uint2 nb = *(const uint2*)(order + 78 - 2 * w);
        const uint32_t hl = sb + SM_HIST + lane * 4;
        const uint32_t ha0 = lds32(hl + na.x * 128), ha1 = lds32(hl + na.y * 128), hb0 = lds32(hl + nb.y * 128), hb1 = lds32(hl + nb.x * 128);
        if (deg[na.x] >= (4 * CAP + 1) * 128) setflag();
        const uint32_t ca = ha0 + (ha1 << 16), c4 = ca + (hb0 << 8) + (hb1 << 24);
        uint32_t inc = c4;
#pragma unroll
        for (int o = 1; o < 32; o <<= 1)
            asm volatile("{.reg .pred p; .reg .u32 u; shfl.sync.up.b32 u|p, %0, %1, 0, 0xffffffff; @p add.u32 %0, %0, u;}" : "+r"(inc) : "r"(o));
        const int su = __reduce_add_sync(0xffffffff, (int)(ha0 - ha1) * (2 * lane - 31)), sv = __reduce_add_sync(0xffffffff, (int)(hb0 - hb1) * (2 * lane - 31));
        const bool swp = (su ^ sv) >= 0;
        if (swp) { nb = make_uint2(nb.y, nb.x); *(uint2*)(order + 78 - 2 * w) = nb; }
        const uint32_t sel = swp ? 0x4143 : 0x4341, ex = inc - c4;
        const uint32_t ea = (ex & 0x00FF00FF) + __byte_perm(ex, 0, sel), eb = ea + ca, base = sb + SM_LIST + w * 2048;
        uint2* pos = (uint2*)(smem + SM_POS) + lane;
        pos[na.x * 32] = make_uint2(base + (ea & 0xFFFF) * 8, na.x * (0u - 4 * KN));
        pos[nb.y * 32] = make_uint2(base + (eb & 0xFFFF) * 8, nb.y * (0u - 4 * KN) + 0x80000000u);
        pos[na.y * 32] = make_uint2(base + 4 + (ea >> 16) * 8, na.y * (0u - 4 * KN));
        pos[nb.x * 32] = make_uint2(base + 4 + (eb >> 16) * 8, nb.x * (0u - 4 * KN) + 0x80000000u);
        len2 = __shfl_sync(0xffffffff, (inc & 0x00FF00FF) + __byte_perm(inc, 0, sel), 31);
        if (max(len2 & 0xFFFF, len2 >> 16) > 4 * CAP) setflag();
    }
    uint32_t ci = cnt[min(w + NW * lane, NB)];
    ci = (((ci & 0xFF) + ((ci >> 8) & 7)) << 24) + min(w + NW * lane, NB) * (RCH / 8) + (ci >> 11);
    if (w == CW) {
        bar_arrive(9, NT);
        if (tid == NT - 1) {
            uint32_t v1, g0; int spins = 0;
            do {
                asm volatile("ld.relaxed.gpu.global.u32 %1, [%2+8]; ld.acquire.gpu.global.u32 %0, [%2+4];" : "=r"(v1), "=r"(g0) : "l"(gs->bar) : "memory");
            } while ((v1 >= NB) == par && ++spins < (1 << 22));
            if ((v1 >= NB) == par) *flag = 1;
            if (g0 - flag[1] < 30000) flag[1] = g0;
            TSTAMPC(17);
        }
        __syncwarp();
    } else {
        bar_sync(9, NT);
        TSTAMP(21);
        const uint32_t over = lds32(flg);
#pragma unroll
        for (int j = 0; j < 2; j++) {
            if (nk[j] > 0) {
                uint2 h[6];
#pragma unroll
                for (int u = 0; u < 6; u++) h[u] = lds64(sb + SM_POS + ha[j][u] * 8);
                if (over) nk[j] = 0;
#pragma unroll
                for (int u = 0; u < 6; u++)
                    asm volatile("{.reg .pred p; setp.gt.s32 p, %2, %3; @p st.shared.u32 [%0], %1;}"
                                 :: "r"(h[u].x + rk[j][u] * 8), "r"(key[j][u] * 4 + h[u].y + (kidx[j] + (u << 17))), "r"(nk[j]), "r"(u) : "memory");
            }
        }
    }
    bar_sync(1, NT);
    TSTAMP(4);
    if (*flag) {
        slow_path(smem, n0, nn, (const uint16_t*)x, (const int*)src4, (const int*)dst4, (const uint16_t*)Y, (const uint16_t*)ef, w_rad, cg,
                  (const uint16_t*)w_mix, (__nv_bfloat16*)out);
        return;
    }
    {
        const uint4* gp = gs->recs + lane;
        asm volatile("" : "+l"(gp));
        const uint32_t sp = sb + SM_RECS + (w * CELL + lane) * 16, lc = (lane << 24) | 0xFFFFFF;
#pragma unroll
        for (int j = 0; j < 7; j++)
            asm volatile("{.reg .pred p; .reg .u32 l; .reg .u64 a; setp.lt.u32 p, %2, %3; and.b32 l, %3, 0xFFFF; mad.wide.u32 a, l, 128, %1;\n"
                         "@p cp.async.cg.shared.global [%0], [a], 16;}"
                         :: "r"(sp + j * (NW * CELL * 16)), "l"(gp), "r"(lc), "r"(__shfl_sync(0xffffffff, ci, j)) : "memory");
        for (uint32_t m = __ballot_sync(0xffffffff, ci >= (33u << 24)); m; m &= m - 1) {
            const int j = __ffs(m) - 1;
            const uint32_t cj = __shfl_sync(0xffffffff, ci, j);
            if (lane + 32 < (cj >> 24))
                asm volatile("cp.async.cg.shared.global [%0], [%1], 16;" :: "r"(sp + j * (NW * CELL * 16) + 512), "l"(gp + (size_t)(cj & 0xFFFF) * 8 + 32) : "memory");
        }
        asm volatile("cp.async.commit_group;" ::: "memory");
    }
    const int S = __shfl_sync(0xffffffff, max((int)(max(len2 & 0xFFFF, len2 >> 16) + 3) >> 2, DS + 1), 0);
    const int mylen = (lane & 1) ? len2 >> 16 : len2 & 0xFFFF;
    constexpr int NRAW = (CAP + 3) / 4;
    uint32_t bits0 = 0, raw[NRAW];
    unsigned char* meta = smem + SM_META + w * (CAP * STEPB);
    const int la = sb + SM_LIST + w * 2048 + lane * 4, llast = la - (lane & ~1) * 4 + (mylen - 1) * 8;
#pragma unroll
    for (int k = 0; k < NRAW; k++) raw[k] = lds32(min(la + k * 128, llast));
    const uint32_t sv0 = min(raw[0] & 0xFFFC, 4 * (NN - 1));
    const unsigned char* pbase = x + c * 16;
    asm volatile("" : "+l"(pbase));
    auto cpa2 = [&](uint32_t dstp, uint32_t sv) {
        asm volatile("cp.async.cg.shared.global [%0], [%1], 16; cp.async.cg.shared.global [%0+1024], [%1+128], 16;"
                     :: "r"(dstp), "l"(pbase + (size_t)sv * 256) : "memory");
    };
    auto cpa2p = [&](uint32_t dstp, uint32_t sv) {
        asm volatile("{.reg .pred p; setp.ge.s32 p, %2, 0; @p cp.async.cg.shared.global [%0], [%1], 16; @p cp.async.cg.shared.global [%0+1024], [%1+128], 16;}"
                     :: "r"(dstp), "l"(pbase + (size_t)sv * 256), "r"(sv) : "memory");
    };
    auto wait_until = [&](uint32_t tt) {
        asm volatile("{.reg .pred p; .reg .u32 d;\n"
                     "PACE_LOOP: mov.u32 d, %%globaltimer_lo; sub.u32 d, %0, d; setp.lt.u32 p, d, 32768; @p nanosleep.u32 %1; @p bra.uni PACE_LOOP;}"
                     :: "r"(tt), "n"(PSLEEP) : "memory");
    };
    const uint32_t tfill = flag[1] - FOFF;
    auto fill = [&](int i) {
        wait_until(tfill + i * FDT);
        cpa2(wdst + i * SLOTB, __shfl_sync(0xffffffff, sv0, 8 * i + 2 * q)); cpa2(wdst + i * SLOTB + 512, __shfl_sync(0xffffffff, sv0, 8 * i + 2 * q + 1));
        asm volatile("cp.async.commit_group;" ::: "memory");
    };
    fill(0);
    TSTAMP(5);
    auto relay = [&]() {
        uint32_t g0, g1, b0, b1;
        asm volatile("ld.volatile.shared.v2.u32 {%0,%1}, [%4+40]; ld.volatile.shared.v2.u32 {%2,%3}, [%4+16];"
                     : "=r"(g0), "=r"(g1), "=r"(b0), "=r"(b1) : "r"(flg) : "memory");
        const unsigned long long dg = (((unsigned long long)g1 << 32) | g0) - (((unsigned long long)b1 << 32) | b0);
        asm volatile("{.reg .pred p, q; setp.eq.u32 p, %1, 0; setp.lt.u64 q, %2, 30000; @q st.shared.u32 [%3+4], %4;\n"
                     "@p cp.async.cg.shared.global [%3+32], [%0], 16;}"
                     :: "l"(gs->bar), "r"(lane), "l"(dg), "r"(flg), "r"(g0) : "memory");
    };
    auto report = [&](uint32_t cand) {
        uint32_t b0, b1;
        asm volatile("ld.volatile.shared.v2.u32 {%0,%1}, [%2+16];" : "=r"(b0), "=r"(b1) : "r"(flg) : "memory");
        asm volatile("{.reg .pred p; setp.eq.u32 p, %2, 0; @p red.max.relaxed.gpu.global.u64 [%0], %1;}"
                     :: "l"(&gs->t0), "l"((((unsigned long long)b1 << 32) | b0) + (cand - b0)), "r"(lane) : "memory");
    };
    uint32_t ra[NRAW];
#pragma unroll
    for (int k = NRAW - 1; k >= 0; k--) {
        const uint32_t m = (__ballot_sync(0xffffffff, (int)raw[k] < 0) >> g) & 0x01010101u;
        bits0 = __funnelshift_l(m * 0x10204080u, bits0, 4);
        const bool pad = la + k * 128 > llast;
        ra[k] = pad ? NB * CELL * 16 : (raw[k] >> 13) & 0x1FFF0;
        raw[k] = (raw[k] & 0xFFFF) | (pad ? F_PAD : 0);
    }
    if (t < 2) bits0 = ~bits0;
    asm volatile("" : "+r"(bits0), "+r"(ra[0]), "+r"(ra[1]), "+r"(ra[2]), "+r"(ra[3]), "+r"(ra[4]), "+r"(raw[0]), "+r"(raw[1]), "+r"(raw[2]), "+r"(raw[3]), "+r"(raw[4]));
    fill(1);
    asm volatile("cp.async.wait_group 2;" ::: "memory");
    bar_sync(1, NT);
    TSTAMP(19);
    if (w == CW) {
        uint32_t tn; asm volatile("mov.u32 %0, %%globaltimer_lo;" : "=r"(tn));
        if ((int)(tn + RDY - flag[1]) > 0) { report(tn + RDY); flag[1] = tn + RDY; }
    }
    {
        uint4 rv[NRAW];
#pragma unroll
        for (int k = 0; k < NRAW - 1; k++) rv[k] = lds128(ra[k] + (sb + SM_RECS));
        if ((NRAW - 1) * 4 < S) rv[NRAW - 1] = lds128(ra[NRAW - 1] + (sb + SM_RECS));
        fill(2);
        bar_sync(1, NT);
        TSTAMP(12);
        unsigned char* mr = meta + (q - 1) * STEPB + c * 16;
        unsigned char* ms = meta + (q - DS - 1) * STEPB + 128 + c * 4;
#pragma unroll
        for (int k = 0; k < NRAW; k++) {
            if (k == 0) {
                *(uint4*)(mr + (q == 0 ? S * STEPB : 0)) = rv[k];
                *(uint32_t*)(ms + S * STEPB) = raw[0] + F_WRAP;
            } else if (k * 4 + q < S) {
                *(uint4*)(mr + k * 4 * STEPB) = rv[k];
                *(uint32_t*)(ms + k * 4 * STEPB + (k == 1 && q == 0 ? S * STEPB : 0)) = raw[k];
            }
        }
    }
    __syncwarp();
    const uint32_t tphase = PACE / 4;
    uint32_t dreg;
    {
        const int ls = lane >= S ? min(lane - S, S - 1) : lane, st = ls == 0 ? S - 1 : ls - 1;
        const uint4 u0 = *(const uint4*)(meta + st * STEPB + 128), u1 = *(const uint4*)(meta + st * STEPB + 144);
        int pos = (u0.x + u0.y + u0.z + u0.w + u1.x + u1.y + u1.z + u1.w) << 1 >> 6;
        pos += ((u0.x & F_WRAP) ? NN : 0) + (lane >= S ? NN : 0) - NN * (2 * DS + 1) / 32;
        dreg = pos * (int)tphase / NN;
    }
    fill(3);
    TSTAMP(6);

    uint32_t* stash = (uint32_t*)(gs->stash + (b * NW + w) * 256) + lane;
    asm volatile("" : "+l"(stash));
    float acc[4][4];
#pragma unroll
    for (int i = 0; i < 16; i++) acc[i / 4][i % 4] = 0.f;
    uint4 az = *(const uint4*)(smem + SM_AZ + lane * 16);
    uint32_t dcur = dreg, dl = 0, now = flag[1], tcur = 0;
    uint32_t mp = 0, smask = 1, didx = 2;
    uint32_t mend = S * STEPB;
    uint2 r = lds64(mend - STEPB + recl), s0 = lds64(mend - STEPB + srcl);
    auto step = [&](const uint32_t off, const int mode, const bool pc = true) {
        if (mode == 0 && pc) { unsigned long long n64; asm volatile("mov.u64 %0, %%globaltimer;" : "=l"(n64)); now = (uint32_t)n64; }
        const uint2 rc = r, sc = s0;
        if (mode != 4) r = lds64(mp + recl);
        if (mode == 0) s0 = lds64(mp + srcl);
        asm volatile("cp.async.wait_group %0;" :: "n"(DS - 1) : "memory");
        const uint4 xa = lds128(rsrc + off), xb = lds128(rsrc + off + 512), xc = lds128(rsrc + off + 1024), xd = lds128(rsrc + off + 1536);
        if (mode == 0) {
            if (pc) { dl = __shfl_sync(0xffffffff, dcur, didx); didx += 2; }
            cpa2p(wdst + off, sc.x); cpa2p(wdst + off + 512, sc.y);
        }
        if (mode == 1 && w < 16) {
#pragma unroll
            for (int j = 0; j < 4; j++) {
                const int kk = 4 * j + q, ch = 16 * (w & 7) + 2 * (kk & 7) + (kk >> 3);
                asm volatile("cp.async.cg.shared.global [%0], [%1], 16;" :: "r"(ring0 + kk * 128 + ((c ^ (kk & 7)) << 4)), "l"(w_mix + ch * 16 + (w >> 3) * 8 + c) : "memory");
            }
            asm volatile("cp.async.mbarrier.arrive.noinc.shared.b64 [%0];" :: "r"(mbarW) : "memory");
        }
        if (mode == 2 || mode == 3) {
#pragma unroll
            for (int j = 0; j < 4; j += mode - 1)
                asm volatile("cp.async.cg.shared.global [%0], [%1], 16;" :: "r"(ring0 + off + j * 512 + lane * 16), "l"(stash + (mode - 2) * 512 + j * 128 + lane * 3) : "memory");
        }
        if (mode < 4) asm volatile("cp.async.commit_group;" ::: "memory");
        float z[4], y[4], t1[4], t2[4];
        mma1688z(z, az.x, az.y, rc.y);
        mma1688z(y, az.z, az.w, rc.y);
        uint32_t bt;
        asm("{.reg .pred p; .reg .b32 m; and.b32 m, %2, %3; setp.ne.u32 p, m, 0; selp.b32 %0, %1, 0, p;}" : "=r"(bt) : "r"(rc.x), "r"(bits0), "r"(smask));
        mma1688z(t1, at[0], at[1], bt);
        mma1688z(t2, at[2], at[3], bt);
        const uint32_t T0 = pack2(t1[0], t1[2]), T1 = pack2(t2[0], t2[2]), T2 = pack2(t1[1], t1[3]), T3 = pack2(t2[1], t2[3]);
        uint32_t R[8];
#pragma unroll
        for (int i = 0; i < 4; i++) { R[i] = __float_as_uint(silu_h(z[i])); R[4 + i] = __float_as_uint(silu_h(y[i])); }
        mma16816(acc[0], mul_hi(xa.x, R[0]), mul_hi(xa.z, R[2]), mul_hi(xa.y, R[0]), mul_hi(xa.w, R[2]), T0, T1);
        mma16816(acc[1], mul_hi(xb.x, R[1]), mul_hi(xb.z, R[3]), mul_hi(xb.y, R[1]), mul_hi(xb.w, R[3]), T2, T3);
        mma16816(acc[2], mul_hi(xc.x, R[4]), mul_hi(xc.z, R[6]), mul_hi(xc.y, R[4]), mul_hi(xc.w, R[6]), T0, T1);
        mma16816(acc[3], mul_hi(xd.x, R[5]), mul_hi(xd.z, R[7]), mul_hi(xd.y, R[5]), mul_hi(xd.w, R[7]), T2, T3);
        mp += STEPB; smask <<= 1;
    };
    auto putacc = [&](uint32_t* p) {
#pragma unroll
        for (int i = 0; i < 16; i++) acc[i / 4][i % 4] *= 1.0028f;
        p[0] = pack2(acc[0][0], acc[0][1]); p[32] = pack2(acc[0][2], acc[0][3]); p[64] = pack2(acc[2][0], acc[2][1]); p[96] = pack2(acc[2][2], acc[2][3]);
        p[256] = pack2(acc[1][0], acc[1][1]); p[288] = pack2(acc[1][2], acc[1][3]); p[320] = pack2(acc[3][0], acc[3][1]); p[352] = pack2(acc[3][2], acc[3][3]);
    };
    int ph = 0;
    auto phase_end = [&](const int k) {
        az = lds128(sb + SM_AZ + (ph + 1) * 512 + lane * 16);
        putacc(stash + ph * ph * 128);
#pragma unroll
        for (int i = 0; i < 16; i++) acc[i / 4][i % 4] = 0.f;
        pbase += 256; mp = 0; smask = 1; ph++;
        dcur += tphase; didx = 1 + (k & 1);
        if (ph == 3) {
            mend -= DS * STEPB;
            dcur += (int)(dcur - __shfl_sync(0xffffffff, dcur, 0)) * (((w >> 2) - 2) * FAN) >> 8;
        }
        WSTAMP(ph - 1);
    };
    uint32_t t0 = now;
    if (w == PW) {
        asm volatile("mov.u32 %0, %%globaltimer_lo;" : "=r"(now));
        now += PTOL - PTOL0;
    }
    const uint32_t bias = w == RW ? 1u << 20 : 0;
    if (w == RW) relay();
    dcur += bias;
    auto body = [&](const int k) -> bool {
        if (k == 2) asm volatile("ld.volatile.shared.u32 %0, [%1+4];" : "=r"(t0) : "r"(flg));
        const bool pc = k & 1;
        step(k * SLOTB, 0, pc);
        if (!pc) {
            if (mp == mend) phase_end(k);
        } else if (mp == mend || now < dl) {
            if (mp == mend) {
                if (k == 3 && ph == 3) return true;
                phase_end(k);
            }
            if (w == RW) { dl -= 1u << 20; relay(); }
            wait_until(dl);
        }
        return false;
    };
    {
        const uint32_t d0 = __shfl_sync(0xffffffff, dreg, 0);
        if (w == RW) {
            uint32_t g0, tn; int spins = 0;
            do {
                asm volatile("ld.relaxed.gpu.global.u32 %0, [%2]; mov.u32 %1, %%globaltimer_lo;" : "=r"(g0), "=r"(tn) : "l"(&gs->t0) : "memory");
                if (g0 - t0 < 30000) { t0 = g0; flag[1] = g0; }
            } while (__shfl_sync(0xffffffff, t0 - tn, 0) < 32768 && ++spins < 64);
        }
        asm volatile("{.reg .pred p; .reg .u32 d;\n"
                     "PACE_LOOP: ld.volatile.shared.u32 %0, [%2+4]; mov.u32 d, %%globaltimer_lo; sub.u32 d, %1, d; add.u32 d, d, %0;\n"
                     "setp.lt.u32 p, d, 32768; @p nanosleep.u32 32; @p bra.uni PACE_LOOP;}"
                     : "=&r"(t0) : "r"(d0), "r"(flg) : "memory");
    }
    while (true) {
        if (w == PW) {
            const uint32_t cand = now - dl + tcur - PTOL;
            if ((int)(cand - t0) > 0) report(cand);
        }
        dcur += t0 - tcur; tcur = t0;
        body(0); body(1); body(2);
        if (body(3)) break;
    }
    __syncwarp();
    step(0, 1);
    { uint32_t tn; asm volatile("mov.u32 %0, %%globaltimer_lo;" : "=r"(tn)); wait_until(tn + (w >> 2) * TDEL); }
    step(SLOTB, 2); step(2 * SLOTB, 3); step(3 * SLOTB, 4);
    WSTAMP(3); ESTAMP(0);

    {
        putacc((uint32_t*)(smem + SM_RING + 2 * SLOTB + w * 2048 + 512) + lane);
        const int wg = w >> 2, w4 = w & 3;
        int nd[8];
#pragma unroll
        for (int j = 0; j < 8; j++) { const int l = wg * 8 + j; nd[j] = order[(t >> 1) ? 79 - l : l]; asm volatile("" : "+r"(nd[j])); }
        const bool odd = t & 1;
        uint2* ob = (uint2*)out + (size_t)n0 * 128 + w4 * 16 + g + (odd ? 8 : 0);
        asm volatile("cp.async.wait_all;" ::: "memory");
        mbar_wait(mbarW, 0);
        asm volatile("fence.proxy.async.shared::cta;" ::: "memory");
        ESTAMP(1);
        bar_sync(2 + wg, 128);
        uint32_t ticket = 0;
        if ((tid & 127) == 0) {
            asm volatile("atom.shared.add.u32 %0, [%1+48], 1;" : "=r"(ticket) : "r"(flg) : "memory");
            int spins = 0;
            while (flag[13] < ticket && ++spins < (1 << 16)) __nanosleep(40);
        }
        bar_sync(2 + wg, 128);
        const uint64_t descA0 = (uint64_t)(((sb + SM_RING) & 0x3FFFF) >> 4) | ((uint64_t)1 << 16) | ((uint64_t)(1024 >> 4) << 32) | ((uint64_t)1 << 62);
        const uint64_t descB0 = (uint64_t)(((sb + SM_RING + SLOTB + wg * 8192) & 0x3FFFF) >> 4) | ((uint64_t)(128 >> 4) << 16) | ((uint64_t)(1024 >> 4) << 32);
        float d[2][32];
        asm volatile("wgmma.fence.sync.aligned;" ::: "memory");
        ESTAMP(2);
#pragma unroll
        for (int mt = 0; mt < 2; mt++) {
#pragma unroll
            for (int ks = 0; ks < 8; ks++) {
                if (mt * 8 + ks == RELK)
                    asm volatile("{.reg .pred p; setp.eq.u32 p, %1, 0; @p st.volatile.shared.u32 [%0+52], %2;}" :: "r"(flg), "r"(tid & 127), "r"(ticket + 1) : "memory");
                const uint64_t da = descA0 + (uint64_t)((ks * 2048 + mt * 16384) >> 4), db = descB0 + (uint64_t)(((ks & 3) * 256 + (ks >> 2) * SLOTB) >> 4);
                asm volatile("{.reg .pred p; setp.ne.b32 p, %34, 0;\n"
                    "wgmma.mma_async.sync.aligned.m64n64k16.f32.bf16.bf16 "
                    "{%0,%1,%2,%3,%4,%5,%6,%7,%8,%9,%10,%11,%12,%13,%14,%15,%16,%17,%18,%19,%20,%21,%22,%23,%24,%25,%26,%27,%28,%29,%30,%31}, %32, %33, p, 1, 1, 1, 1;}"
                    : "+f"(d[mt][0]), "+f"(d[mt][1]), "+f"(d[mt][2]), "+f"(d[mt][3]), "+f"(d[mt][4]), "+f"(d[mt][5]), "+f"(d[mt][6]), "+f"(d[mt][7]),
                      "+f"(d[mt][8]), "+f"(d[mt][9]), "+f"(d[mt][10]), "+f"(d[mt][11]), "+f"(d[mt][12]), "+f"(d[mt][13]), "+f"(d[mt][14]), "+f"(d[mt][15]),
                      "+f"(d[mt][16]), "+f"(d[mt][17]), "+f"(d[mt][18]), "+f"(d[mt][19]), "+f"(d[mt][20]), "+f"(d[mt][21]), "+f"(d[mt][22]), "+f"(d[mt][23]),
                      "+f"(d[mt][24]), "+f"(d[mt][25]), "+f"(d[mt][26]), "+f"(d[mt][27]), "+f"(d[mt][28]), "+f"(d[mt][29]), "+f"(d[mt][30]), "+f"(d[mt][31])
                    : "l"(da), "l"(db), "r"(ks));
            }
            asm volatile("wgmma.commit_group.sync.aligned;" ::: "memory");
        }
#pragma unroll
        for (int mt = 0; mt < 2; mt++) {
            if (mt == 0) asm volatile("wgmma.wait_group.sync.aligned 1;" ::: "memory");
            else asm volatile("wgmma.wait_group.sync.aligned 0;" ::: "memory");
            ESTAMP(3 + mt);
#pragma unroll
            for (int i = 0; i < 32; i++) asm volatile("" : "+f"(d[mt][i]) :: "memory");
#pragma unroll
            for (int j = 0; j < 8; j++) {
                const uint32_t v0 = pack2(d[mt][4 * j], d[mt][4 * j + 1]), v1 = pack2(d[mt][4 * j + 2], d[mt][4 * j + 3]);
                const uint32_t rv = __shfl_xor_sync(0xffffffff, odd ? v0 : v1, 1);
                if (nd[j] < nn) ob[nd[j] * 128 + mt * 64] = odd ? make_uint2(rv, v1) : make_uint2(v0, rv);
            }
        }
    }
    TSTAMP(8); ESTAMP(5);
}

__global__ void __launch_bounds__(NT, 1)
tfn_fallback(const uint16_t* x, const int* src, const int* dst, const uint16_t* Y, const uint16_t* ef, const uint16_t* w_rad,
             const uint16_t* cg, const uint16_t* w_mix, __nv_bfloat16* out) {
    extern __shared__ __align__(1024) unsigned char smem[];
    const int n0 = blockIdx.x * NPB;
    slow_path(smem, n0, min(NPB, NN - n0), x, src, dst, Y, ef, w_rad, cg, w_mix, out);
}

}

extern "C" void kernel_launch(void* const* d_in, const int* in_sizes, int n_in, void* d_out, int out_size) {
    (void)in_sizes; (void)n_in; (void)out_size;
    cudaFuncSetAttribute(tfn_kernel, cudaFuncAttributeMaxDynamicSharedMemorySize, SM_TOTAL);
    int dev = 0, sms = 0;
    cudaGetDevice(&dev);
    cudaDeviceGetAttribute(&sms, cudaDevAttrMultiProcessorCount, dev);
    if (sms < NB) {
        cudaFuncSetAttribute(tfn_fallback, cudaFuncAttributeMaxDynamicSharedMemorySize, NPB * 2048);
        tfn_fallback<<<NB, NT, NPB * 2048, cudaStreamPerThread>>>((const uint16_t*)d_in[0], (const int*)d_in[1], (const int*)d_in[2], (const uint16_t*)d_in[3],
            (const uint16_t*)d_in[4], (const uint16_t*)d_in[5], (const uint16_t*)d_in[6], (const uint16_t*)d_in[7], (__nv_bfloat16*)d_out);
        return;
    }
    Scratch* gs = nullptr;
    cudaGetSymbolAddress((void**)&gs, g_scratch);
    cudaLaunchConfig_t cfg = {};
    cfg.gridDim = dim3(NB); cfg.blockDim = dim3(NT); cfg.dynamicSmemBytes = SM_TOTAL; cfg.stream = cudaStreamPerThread;
    cudaLaunchAttribute at[1];
    at[0].id = cudaLaunchAttributeCooperative; at[0].val.cooperative = 1;
    cfg.attrs = at; cfg.numAttrs = 1;
    cudaLaunchKernelEx(&cfg, tfn_kernel, (const unsigned char*)d_in[0], (const int4*)d_in[1], (const int4*)d_in[2],
                       (const uint4*)d_in[3], (const uint4*)d_in[4], (const uint16_t*)d_in[5], (const uint16_t*)d_in[6],
                       (const uint4*)d_in[7], (uint32_t*)d_out, gs);
}
```

```cpp
#include <cuda_runtime.h>
#include <cuda_bf16.h>
#include <stdint.h>

namespace {

constexpr int NN = 10000;
constexpr int NE = 320000;
constexpr int NB = 132;
constexpr int NW = 20;
constexpr int NT = NW * 32;
constexpr int CW = NW - 1;
constexpr int PW = 10;
constexpr int RW = 1;
constexpr int NPB = 76;
constexpr int CELL = 48;
constexpr int RCH = 2880;
constexpr int CAP = 19;
constexpr int DS = 4;
constexpr int STEPB = 160;
constexpr int NE4 = NE / 4;
constexpr int NPIECE = NB * 8;
constexpr int KB = 320, KN = 32 * KB;
constexpr uint32_t F_PAD = 0x80000000u;
constexpr uint32_t F_WRAP = 1;

constexpr int SLOTB = NW * 2048;
constexpr int SM_RING = 0;
constexpr int SM_META = SM_RING + DS * SLOTB;
constexpr int SM_AZ = SM_META + NW * CAP * STEPB;
constexpr int SM_MISC = SM_AZ + 2048;
constexpr int SM_TOTAL = SM_MISC + 2048;
constexpr int SM_STAGE = SM_RING;
constexpr int SM_HIST = SM_RING + 25600;
constexpr int SM_POS = SM_RING;
constexpr int SM_SMALL = SM_HIST + 13056;
constexpr int SM_LIST = SM_RING + SLOTB;
constexpr int SM_ROUT = SM_RING + 2 * SLOTB;
constexpr int SM_RECS = SM_RING + 3 * SLOTB;
constexpr int SM_RAWY = SM_META;
constexpr int SM_RAWE = SM_RAWY + 608 * 32;
constexpr int SM_KEYS = SM_RAWE + 608 * 32;
static_assert(SM_TOTAL <= 232448 && SM_KEYS + NPIECE * 16 <= SM_AZ, "smem");
static_assert(SM_RECS + NB * CELL * 16 + 16 <= SM_AZ && SM_KEYS + NPIECE * 16 <= SM_RECS + NB * CELL * 16 && SM_SMALL + 1152 <= SLOTB && DS == 4, "smem");

struct Scratch {
    uint4 keys[NB * NPIECE];
    uint4 recs[NB * RCH];
    uint4 stash[NB * NW * 256];
    unsigned bar[2];
    unsigned long long t0;
};
__device__ Scratch g_scratch;
#define TSTAMP(i)
#define TSTAMPC(i)
#define WSTAMP(i)
#define ESTAMP(i)

__device__ __forceinline__ void mma16816(float* d, uint32_t a0, uint32_t a1, uint32_t a2, uint32_t a3, uint32_t b0, uint32_t b1) {
    asm("mma.sync.aligned.m16n8k16.row.col.f32.bf16.bf16.f32 {%0,%1,%2,%3}, {%4,%5,%6,%7}, {%8,%9}, {%0,%1,%2,%3};"
        : "+f"(d[0]), "+f"(d[1]), "+f"(d[2]), "+f"(d[3]) : "r"(a0), "r"(a1), "r"(a2), "r"(a3), "r"(b0), "r"(b1));
}
__device__ __forceinline__ void mma1688z(float* d, uint32_t a0, uint32_t a1, uint32_t b0) {
    asm("mma.sync.aligned.m16n8k8.row.col.f32.bf16.bf16.f32 {%0,%1,%2,%3}, {%4,%5}, {%6}, {%7,%7,%7,%7};"
        : "=f"(d[0]), "=f"(d[1]), "=f"(d[2]), "=f"(d[3]) : "r"(a0), "r"(a1), "r"(b0), "f"(0.f));
}
__device__ __forceinline__ uint32_t pack2(float lo, float hi) {
    uint32_t r; asm("cvt.rn.bf16x2.f32 %0, %1, %2;" : "=r"(r) : "f"(hi), "f"(lo)); return r;
}
__device__ __forceinline__ float silu_h(float h) {
    float t; asm("tanh.approx.f32 %0, %1;" : "=f"(t) : "f"(h)); return fmaf(h, t, h);
}
__device__ __forceinline__ uint32_t mul_lo(uint32_t v, uint32_t r) {
    __nv_bfloat162 a = *(__nv_bfloat162*)&v, b = *(__nv_bfloat162*)&r; __nv_bfloat162 c = __hmul2(a, __low2bfloat162(b)); return *(uint32_t*)&c;
}
__device__ __forceinline__ uint32_t mul_hi(uint32_t v, uint32_t r) {
    __nv_bfloat162 a = *(__nv_bfloat162*)&v, b = *(__nv_bfloat162*)&r; __nv_bfloat162 c = __hmul2(a, __high2bfloat162(b)); return *(uint32_t*)&c;
}
__device__ __forceinline__ uint32_t lds32(uint32_t a) {
    uint32_t r; asm volatile("ld.shared.u32 %0, [%1];" : "=r"(r) : "r"(a) : "memory"); return r;
}
__device__ __forceinline__ void sts32(uint32_t a, uint32_t v) { asm volatile("st.shared.u32 [%0], %1;" :: "r"(a), "r"(v) : "memory"); }
__device__ __forceinline__ uint2 lds64(uint32_t a) {
    uint2 r; asm volatile("ld.shared.v2.u32 {%0,%1}, [%2];" : "=r"(r.x), "=r"(r.y) : "r"(a)); return r;
}
__device__ __forceinline__ uint4 lds128(uint32_t a) {
    uint4 r; asm volatile("ld.shared.v4.u32 {%0,%1,%2,%3}, [%4];" : "=r"(r.x), "=r"(r.y), "=r"(r.z), "=r"(r.w) : "r"(a) : "memory"); return r;
}
__device__ __forceinline__ void bar_sync(int id, int n) { asm volatile("bar.sync %0, %1;" :: "r"(id), "r"(n) : "memory"); }
__device__ __forceinline__ void bar_arrive(int id, int n) { asm volatile("bar.arrive %0, %1;" :: "r"(id), "r"(n) : "memory"); }
__device__ __forceinline__ void mbar_wait(uint32_t bar, uint32_t ph) {
    uint32_t done; int spins = 0;
    do {
        asm volatile("{.reg .pred p; mbarrier.try_wait.parity.shared.b64 p, [%1], %2; selp.u32 %0,1,0,p;}" : "=r"(done) : "r"(bar), "r"(ph) : "memory");
    } while (!done && ++spins < (1 << 22));
}
__device__ __forceinline__ void gbar_arrive(unsigned* ctr) {
    asm volatile("red.inc.relaxed.gpu.global.u32 [%0], %1;" :: "l"(ctr), "n"(2 * NB - 1) : "memory");
}
__device__ __forceinline__ int chunk_start4(int c) { return (c * NE4) / NB; }
__device__ __forceinline__ float bf2f(uint32_t h) { return __uint_as_float(h << 16); }

__device__ __noinline__ void slow_path(unsigned char* smem, int n0, int nn, const uint16_t* x, const int* src, const int* dst,
                                       const uint16_t* Y, const uint16_t* ef, const uint16_t* w_rad, const uint16_t* cg,
                                       const uint16_t* w_mix, __nv_bfloat16* out) {
    float* agg = (float*)smem;
    const int tid = threadIdx.x, lane = tid & 31, w = tid >> 5;
    bar_sync(1, NT);
    for (int i = tid; i < NPB * 512; i += NT) agg[i] = 0.f;
    bar_sync(1, NT);
    for (int e0 = w * 32; e0 < NE; e0 += NT) {
        int dl = dst[e0 + lane] - n0;
        unsigned m = __ballot_sync(0xffffffff, dl >= 0 && dl < nn);
        while (m) {
            int l = __ffs(m) - 1; m &= m - 1;
            int e = e0 + l, d = __shfl_sync(0xffffffff, dl, l), s = src[e];
            float T[16];
            for (int i = 0; i < 4; i++) for (int o = 0; o < 4; o++) {
                float a = 0.f;
                for (int f = 0; f < 4; f++) a += bf2f(Y[e * 4 + f]) * bf2f(cg[i * 16 + f * 4 + o]);
                T[i * 4 + o] = a;
            }
            for (int k = 0; k < 4; k++) {
                int c = lane + 32 * k;
                float z = 0.f;
                for (int j = 0; j < 4; j++) z += bf2f(ef[e * 4 + j]) * bf2f(w_rad[j * 128 + c]);
                float R = z / (1.f + __expf(-z));
                for (int o = 0; o < 4; o++) {
                    float a = 0.f;
                    for (int i = 0; i < 4; i++) a += bf2f(x[(size_t)s * 512 + c * 4 + i]) * T[i * 4 + o];
                    atomicAdd(&agg[d * 512 + c * 4 + o], R * a);
                }
            }
        }
    }
    bar_sync(1, NT);
    for (int i = tid; i < nn * 512; i += NT) {
        int n = i >> 9, d = (i >> 2) & 127, o = i & 3;
        float a = 0.f;
        for (int c = 0; c < 128; c++) a += agg[n * 512 + c * 4 + o] * bf2f(w_mix[c * 128 + d]);
        out[(size_t)(n0 + n) * 512 + (i & 511)] = __float2bfloat16(a);
    }
}

#define PACE 23000
#define YDELAY 300
#define POFF 3600
#define PSLEEP 64
#define FDT 350
#define FOFF 1500
#define RELK 12
#define FAN 16
#define TDEL 100
#define RDY 600
#define XPF 2
#define XPF0 40
#define PTOL0 300
#define PTOL 1100
__global__ void __launch_bounds__(NT, 1)
tfn_kernel(const unsigned char* __restrict__ x, const int4* __restrict__ src4, const int4* __restrict__ dst4,
           const uint4* __restrict__ Y, const uint4* __restrict__ ef, const uint16_t* __restrict__ w_rad,
           const uint16_t* __restrict__ cg, const uint4* __restrict__ w_mix, uint32_t* __restrict__ out, Scratch* __restrict__ gs) {
    extern __shared__ __align__(1024) unsigned char smem[];
    const uint32_t sb = (uint32_t)__cvta_generic_to_shared(smem);
    const int b = blockIdx.x, tid = threadIdx.x, lane = tid & 31, g = lane >> 2, t = lane & 3;
    const int w = __shfl_sync(0xffffffff, tid >> 5, 0);
    uint32_t* stage = (uint32_t*)(smem + SM_STAGE);
    uint32_t* hist = (uint32_t*)(smem + SM_HIST);
    uint32_t* cnt = (uint32_t*)(smem + SM_MISC);
    uint32_t* deg = cnt + 136;
    uint32_t* order = deg + 104;
    uint32_t* cnt2 = order + 80;
    volatile uint32_t* flag = cnt2 + 136;
    const uint32_t mbarK = sb + SM_MISC + 1920, mbarR = mbarK + 8, mbarW = mbarK + 16;
    const int n0 = b * NPB, nn = min(NPB, NN - n0);
    TSTAMP(0);

    const int c0 = chunk_start4(b), c1 = chunk_start4(b + 1);
    const bool has4 = c0 + tid < c1;
    int4 d4 = make_int4(0, 0, 0, 0), s4 = d4;
    if (has4) { d4 = __ldg(dst4 + c0 + tid); s4 = __ldg(src4 + c0 + tid); }
    unsigned par = 0;
    if (tid == NT - 1) {
        asm volatile("ld.relaxed.gpu.global.u32 %0, [%1];" : "=r"(par) : "l"(gs->bar) : "memory");
        asm volatile("mbarrier.init.shared.b64 [%0], 1;" :: "r"(mbarK));
        asm volatile("mbarrier.init.shared.b64 [%0], 1;" :: "r"(mbarR));
        asm volatile("mbarrier.init.shared.b64 [%0], 512;" :: "r"(mbarW));
        asm volatile("fence.mbarrier_init.release.cluster;" ::: "memory");
        flag[0] = 0; flag[12] = 0; flag[13] = 0; flag[15] = 0;
    }
    if (w == CW) {
        asm volatile("cp.async.cg.shared.global [%0], [%1], 16;" :: "r"(sb + SM_SMALL + lane * 16), "l"(w_rad + lane * 8) : "memory");
        asm volatile("cp.async.cg.shared.global [%0], [%1], 16;" :: "r"(sb + SM_SMALL + 512 + lane * 16), "l"(w_rad + 256 + lane * 8) : "memory");
        if (lane < 8) asm volatile("cp.async.cg.shared.global [%0], [%1], 16;" :: "r"(sb + SM_SMALL + 1024 + lane * 16), "l"(cg + lane * 8) : "memory");
    }
    ((uint4*)hist)[tid] = make_uint4(0, 0, 0, 0);
    {
        const uint32_t dk = (80 + b % 22) * KN + (b & 31) * KB;
#pragma unroll
        for (int j = 0; j < 3; j++) if (tid + j * NT < NB * CELL / 4) ((uint4*)stage)[tid + j * NT] = make_uint4(dk, dk, dk, dk);
    }
    if (tid < 136) cnt[tid] = 0;
    if (tid == 0) { *(uint4*)(smem + SM_MISC + 1824 + 32) = make_uint4(0, 0, 0, 0); *(uint4*)(smem + SM_RECS + NB * CELL * 16) = make_uint4(0, 0, 0, 0); }
    if (tid < 80) { deg[tid] = 127 - tid; order[tid] = tid; }
    __syncthreads();
    TSTAMP(9);
    if (tid == 64) {
        __nanosleep(YDELAY);
        asm volatile("mbarrier.arrive.expect_tx.shared.b64 _, [%0], %1;" :: "r"(mbarR), "r"((c1 - c0) * 64) : "memory");
        asm volatile("cp.async.bulk.shared::cluster.global.mbarrier::complete_tx::bytes [%0], [%1], %2, [%3];"
                     :: "r"(sb + SM_RAWY), "l"(Y + 2 * c0), "r"((c1 - c0) * 32), "r"(mbarR) : "memory");
        asm volatile("cp.async.bulk.shared::cluster.global.mbarrier::complete_tx::bytes [%0], [%1], %2, [%3];"
                     :: "r"(sb + SM_RAWE), "l"(ef + 2 * c0), "r"((c1 - c0) * 32), "r"(mbarR) : "memory");
    }

    uint32_t bin[4] = {0, 0, 0, 0}, slot[4] = {0, 0, 0, 0};
    if (has4) {
        const uint32_t dd[4] = {(uint32_t)d4.x, (uint32_t)d4.y, (uint32_t)d4.z, (uint32_t)d4.w}, ss[4] = {(uint32_t)s4.x, (uint32_t)s4.y, (uint32_t)s4.z, (uint32_t)s4.w};
#pragma unroll
        for (int k = 0; k < 4; k++) { bin[k] = dd[k] / NPB; slot[k] = atomicAdd(&cnt[bin[k]], 1); }
#pragma unroll
        for (int k = 0; k < 4; k++) stage[bin[k] * CELL + min(slot[k], CELL - 1)] = (dd[k] - bin[k] * NPB) * KN + ss[k];
    }
    if (w == CW) {
        if (tid == NT - 1) { par = par >= NB; flag[14] = (par ^ 1) << 31; }
        asm volatile("cp.async.wait_all;" ::: "memory");
    }
    bar_sync(1, NT);
    TSTAMP(1);
    const uint32_t tag = flag[14];
#pragma unroll
    for (int j = 0; j < 2; j++) {
        const int i = tid + j * NT;
        if (i < NPIECE) {
            const uint2 sa = *(const uint2*)(stage + i * 6), sc = *(const uint2*)(stage + i * 6 + 2);
            uint2 se = *(const uint2*)(stage + i * 6 + 4);
            const uint32_t cf = cnt[i >> 3], cn = min(cf, 63u);
            if ((i & 7) == 7) {
                const uint32_t al = cf > CELL - 8 ? 7 : 0;
                uint32_t o;
                asm volatile("atom.shared.add.u32 %0, [%1], %2;" : "=r"(o) : "r"(sb + SM_MISC + 1824 + 60), "r"(cf + al) : "memory");
                se.y = (o + al) & ~al;
                cnt2[i >> 3] = se.y;
            }
            asm volatile("{.reg .b64 lo, hi; mov.b64 lo, {%1,%2}; mov.b64 hi, {%3,%4}; st.relaxed.gpu.global.v2.b64 [%0], {lo, hi};}"
                         :: "l"(gs->keys + ((i >> 3) * NB + b) * 8 + ((i ^ b) & 7)),
                            "r"(sa.x | (se.x << 20)), "r"(sa.y | ((se.x >> 12) << 20) | ((cn & 7) << 28) | tag),
                            "r"(sc.x | (se.y << 20)), "r"(sc.y | ((se.y >> 12) << 20) | ((cn >> 3) << 28) | tag) : "memory");
        }
    }
    bar_sync(1, NT);
    if (tid == NT - 1) {
        TSTAMPC(10);
        gbar_arrive(&gs->bar[0]);
        asm volatile("mbarrier.arrive.expect_tx.shared.b64 _, [%0], %1;" :: "r"(mbarK), "r"(NPIECE * 16) : "memory");
        unsigned v; int spins = 0;
        do { asm volatile("ld.relaxed.gpu.global.u32 %0, [%1];" : "=r"(v) : "l"(gs->bar) : "memory"); } while ((v >= NB) == par && ++spins < (1 << 22));
        TSTAMPC(13);
        asm volatile("fence.proxy.async.global;" ::: "memory");
        asm volatile("cp.async.bulk.shared::cluster.global.mbarrier::complete_tx::bytes [%0], [%1], %2, [%3];"
                 :: "r"(sb + SM_KEYS), "l"(gs->keys + b * NPIECE), "r"(NPIECE * 16), "r"(mbarK) : "memory");
    }
    __syncwarp();
    uint32_t at[4];
    {
        const int o = g & 3, f = 2 * (t & 1);
#pragma unroll
        for (int i = 0; i < 4; i++) {
            const uint16_t* cp = (const uint16_t*)(smem + SM_SMALL + 1024) + i * 16 + f * 4 + o;
            at[i] = (t >> 1) == (g >> 2) ? cp[0] | ((uint32_t)cp[4] << 16) : 0;
        }
    }

    const int q = lane >> 3, c = lane & 7;
    const uint32_t ring0 = sb + SM_RING + w * 2048;
    uint32_t wdst = ring0 + q * 128 + ((c + 2 * q) & 7) * 16;
    uint32_t rsrc = ring0 + t * 128 + ((g + 2 * t) & 7) * 16;
    uint32_t recl = sb + SM_META + w * (CAP * STEPB) + g * 16 + (t & 1) * 8, srcl = sb + SM_META + w * (CAP * STEPB) + 128 + q * 8;
    uint32_t flg = sb + SM_MISC + (136 + 104 + 80 + 136) * 4;
    asm volatile("" : "+r"(wdst), "+r"(rsrc), "+r"(recl), "+r"(srcl), "+r"(flg));
    auto setflag = [&]() { sts32(flg, 1); };
    uint32_t key[2][6], ha[2][6], rk[2][6], kidx[2], ka[2], kc[2];
    int nk[2];
#pragma unroll
    for (int j = 0; j < 2; j++) {
        const int i0 = j ? 2 * 608 - 1 - tid : tid, i = min(i0, NPIECE - 1), r = i / NB, cc = i - r * NB;
        ka[j] = sb + SM_KEYS + (cc * 8 + ((r ^ cc) & 7)) * 16;
        kidx[j] = (cc * CELL + r * 6) << 17;
        kc[j] = sb + SM_MISC + cc * 4;
        nk[j] = i0 < NPIECE && w < CW ? -6 * r : -1000;
    }
    asm volatile("" : "+r"(at[0]), "+r"(at[1]), "+r"(at[2]), "+r"(at[3]), "+r"(ka[0]), "+r"(ka[1]), "+r"(kidx[0]), "+r"(kidx[1]), "+r"(kc[0]), "+r"(kc[1]), "+r"(nk[0]), "+r"(nk[1]));
    if (w == CW) {
        __syncwarp();
        bar_sync(7, NT);
        if (tid == NT - 1) {
            TSTAMPC(11);
            asm volatile("cp.async.bulk.global.shared::cta.bulk_group [%0], [%1], %2;"
                         :: "l"(gs->recs + b * RCH), "r"(sb + SM_ROUT), "r"(((flag[15] + 1) & ~1u) * 16) : "memory");
            asm volatile("cp.async.bulk.commit_group;" ::: "memory");
            mbar_wait(mbarK, 0);
            unsigned long long tbase;
            asm volatile("mov.u64 %0, %%globaltimer;" : "=l"(tbase));
            tbase += POFF;
            flag[1] = (uint32_t)tbase; flag[4] = (uint32_t)tbase; flag[5] = (uint32_t)(tbase >> 32);
            asm volatile("red.max.relaxed.gpu.global.u64 [%0], %1;" :: "l"(&gs->t0), "l"(tbase) : "memory");
            if (b < 128) asm volatile("cp.async.bulk.prefetch.L2.global [%0], 256;" :: "l"(w_mix + b * 16));
            asm volatile("cp.async.bulk.wait_group 0;" ::: "memory");
            TSTAMPC(14);
            gbar_arrive(&gs->bar[1]);
            TSTAMPC(15);
        }
    } else {
        if (w < 8) {
            const uint32_t* wp = (const uint32_t*)(smem + SM_SMALL) + (t & 1) * 128 + 8 * w + g;
            const uint32_t wr0 = t < 2 ? wp[0] : 0, wr1 = t < 2 ? wp[64] : 0;
            *(uint2*)(smem + SM_AZ + (w >> 1) * 512 + lane * 16 + (w & 1) * 8) =
                make_uint2(pack2(0.5f * bf2f(wr0 & 0xFFFF), 0.5f * bf2f(wr1 & 0xFFFF)), pack2(0.5f * bf2f(wr0 >> 16), 0.5f * bf2f(wr1 >> 16)));
        }
        const bool sw = g & 1;
        uint32_t rp[4];
#pragma unroll
        for (int k = 0; k < 4; k++) rp[k] = cnt2[bin[k]] + slot[k];
        uint4* ro = (uint4*)(smem + SM_ROUT);
        uint4 *p0 = ro + (sw ? rp[2] : rp[0]), *p1 = ro + (sw ? rp[3] : rp[1]), *p2 = ro + (sw ? rp[0] : rp[2]), *p3 = ro + (sw ? rp[1] : rp[3]);
        const uint32_t ya = sb + SM_RAWY + tid * 32 + (sw ? 16 : 0);
        mbar_wait(mbarR, 0);
        TSTAMP(18);
        if (has4) {
            const uint4 y0 = lds128(ya), e0 = lds128(ya + (SM_RAWE - SM_RAWY)), y1 = lds128(ya ^ 16), e1 = lds128((ya ^ 16) + (SM_RAWE - SM_RAWY));
            *p0 = make_uint4(y0.x, e0.x, y0.y, e0.y); *p1 = make_uint4(y0.z, e0.z, y0.w, e0.w);
            *p2 = make_uint4(y1.x, e1.x, y1.y, e1.y); *p3 = make_uint4(y1.z, e1.z, y1.w, e1.w);
        }
        asm volatile("fence.proxy.async.shared::cta;" ::: "memory");
        bar_arrive(7, NT);
    }
    __syncwarp();
    TSTAMP(2);

    if (w < CW) {
        mbar_wait(mbarK, 0);
        TSTAMP(3);
        uint4 v[2] = {lds128(ka[0]), lds128(ka[1])};
        if ((int)((v[0].y ^ tag) | (v[0].w ^ tag) | (v[1].y ^ tag) | (v[1].w ^ tag)) < 0) {
#pragma unroll
            for (int j = 0; j < 2; j++) {
                int spins = 0;
#pragma unroll 1
                while ((int)((v[j].y ^ tag) | (v[j].w ^ tag)) < 0) {
                    asm volatile("{.reg .b64 lo, hi; ld.relaxed.gpu.global.v2.b64 {lo, hi}, [%4]; mov.b64 {%0,%1}, lo; mov.b64 {%2,%3}, hi;}"
                                 : "=r"(v[j].x), "=r"(v[j].y), "=r"(v[j].z), "=r"(v[j].w) : "l"((const unsigned char*)(gs->keys + b * NPIECE) + (ka[j] - sb - SM_KEYS)) : "memory");
                    if (++spins > (1 << 20)) { setflag(); break; }
                }
            }
        }
#pragma unroll
        for (int j = 0; j < 2; j++) {
            const uint32_t hc = ((v[j].y >> 28) & 7) | ((v[j].w >> 25) & 0x38);
            if (j == 1 && nk[j] == -42) {
                sts32(kc[j], hc | ((v[j].z >> 20) << 8));
                if (hc > CELL - 1) setflag();
                v[j].w |= ((80 * KN) >> 12) << 20;
            }
            nk[j] += hc;
            if (nk[j] > 0) {
                key[j][0] = v[j].x & 0xFFFFF; key[j][1] = v[j].y & 0xFFFFF; key[j][2] = v[j].z & 0xFFFFF; key[j][3] = v[j].w & 0xFFFFF;
                key[j][4] = (v[j].x >> 20) | ((v[j].y >> 8) & 0xFF000); key[j][5] = (v[j].z >> 20) | ((v[j].w >> 8) & 0xFF000);
#pragma unroll
                for (int u = 0; u < 6; u++) {
                    ha[j][u] = __umulhi(key[j][u], 0xFFFFFFFFu / KB + 1);
                    asm volatile("{.reg .u32 a, n; mad.lo.u32 a, %1, 4, %2; atom.shared.add.u32 %0, [a+%3], 1;\n"
                                 "shr.u32 n, %1, 5; mad.lo.u32 a, n, 4, %2; red.shared.add.u32 [a+%4], 128;}"
                                 : "=r"(rk[j][u]) : "r"(ha[j][u]), "r"(sb), "n"(SM_HIST), "n"(SM_MISC + 136 * 4) : "memory");
                }
            }
        }
        bar_sync(9, NT - 32);
        TSTAMP(20);
        const int n = tid >> 3, sub = tid & 7;
        const uint32_t me = deg[n];
        uint32_t r = 0, r2 = 0;
#pragma unroll
        for (int k = 0; k < 5; k++) { const uint2 dd = *(const uint2*)(deg + sub * 10 + 2 * k); r += (me - dd.x) >> 31; r2 += (me - dd.y) >> 31; }
        r += r2;
#pragma unroll
        for (int j = 0; j < 2; j++) kidx[j] += (lds32(kc[j]) & 0x700) << 9;
        r += __shfl_xor_sync(0xffffffff, r, 1); r += __shfl_xor_sync(0xffffffff, r, 2); r += __shfl_xor_sync(0xffffffff, r, 4);
        if (sub == 0) order[r] = n;
    }
    bar_sync(1, NT);
    TSTAMP(22);
    uint32_t len2;
    {
        const uint2 na = *(const uint2*)(order + 2 * w);
        uint2 nb = *(const uint2*)(order + 78 - 2 * w);
        const uint32_t hl = sb + SM_HIST + lane * 4;
        const uint32_t ha0 = lds32(hl + na.x * 128), ha1 = lds32(hl + na.y * 128), hb0 = lds32(hl + nb.y * 128), hb1 = lds32(hl + nb.x * 128);
        if (deg[na.x] >= (4 * CAP + 1) * 128) setflag();
        const uint32_t ca = ha0 + (ha1 << 16), c4 = ca + (hb0 << 8) + (hb1 << 24);
        uint32_t inc = c4;
#pragma unroll
        for (int o = 1; o < 32; o <<= 1)
            asm volatile("{.reg .pred p; .reg .u32 u; shfl.sync.up.b32 u|p, %0, %1, 0, 0xffffffff; @p add.u32 %0, %0, u;}" : "+r"(inc) : "r"(o));
        const int su = __reduce_add_sync(0xffffffff, (int)(ha0 - ha1) * (2 * lane - 31)), sv = __reduce_add_sync(0xffffffff, (int)(hb0 - hb1) * (2 * lane - 31));
        const bool swp = (su ^ sv) >= 0;
        if (swp) { nb = make_uint2(nb.y, nb.x); *(uint2*)(order + 78 - 2 * w) = nb; }
        const uint32_t sel = swp ? 0x4143 : 0x4341, ex = inc - c4;
        const uint32_t ea = (ex & 0x00FF00FF) + __byte_perm(ex, 0, sel), eb = ea + ca, base = sb + SM_LIST + w * 2048;
        uint2* pos = (uint2*)(smem + SM_POS) + lane;
        pos[na.x * 32] = make_uint2(base + (ea & 0xFFFF) * 8, na.x * (0u - 4 * KN));
        pos[nb.y * 32] = make_uint2(base + (eb & 0xFFFF) * 8, nb.y * (0u - 4 * KN) + 0x80000000u);
        pos[na.y * 32] = make_uint2(base + 4 + (ea >> 16) * 8, na.y * (0u - 4 * KN));
        pos[nb.x * 32] = make_uint2(base + 4 + (eb >> 16) * 8, nb.x * (0u - 4 * KN) + 0x80000000u);
        len2 = __shfl_sync(0xffffffff, (inc & 0x00FF00FF) + __byte_perm(inc, 0, sel), 31);
        if (max(len2 & 0xFFFF, len2 >> 16) > 4 * CAP) setflag();
    }
    uint32_t ci = cnt[min(w + NW * lane, NB)];
    ci = (((ci & 0xFF) + ((ci >> 8) & 7)) << 24) + min(w + NW * lane, NB) * (RCH / 8) + (ci >> 11);
    if (w == CW) {
        bar_arrive(9, NT);
        if (tid == NT - 1) {
            uint32_t v1, g0; int spins = 0;
            do {
                asm volatile("ld.relaxed.gpu.global.u32 %1, [%2+8]; ld.acquire.gpu.global.u32 %0, [%2+4];" : "=r"(v1), "=r"(g0) : "l"(gs->bar) : "memory");
            } while ((v1 >= NB) == par && ++spins < (1 << 22));
            if ((v1 >= NB) == par) *flag = 1;
            if (g0 - flag[1] < 30000) flag[1] = g0;
            TSTAMPC(17);
        }
        __syncwarp();
    } else {
        bar_sync(9, NT);
        TSTAMP(21);
        const uint32_t over = lds32(flg);
#pragma unroll
        for (int j = 0; j < 2; j++) {
            if (nk[j] > 0) {
                uint2 h[6];
#pragma unroll
                for (int u = 0; u < 6; u++) h[u] = lds64(sb + SM_POS + ha[j][u] * 8);
                if (over) nk[j] = 0;
#pragma unroll
                for (int u = 0; u < 6; u++)
                    asm volatile("{.reg .pred p; setp.gt.s32 p, %2, %3; @p st.shared.u32 [%0], %1;}"
                                 :: "r"(h[u].x + rk[j][u] * 8), "r"(key[j][u] * 4 + h[u].y + (kidx[j] + (u << 17))), "r"(nk[j]), "r"(u) : "memory");
            }
        }
    }
    bar_sync(1, NT);
    TSTAMP(4);
    if (*flag) {
        slow_path(smem, n0, nn, (const uint16_t*)x, (const int*)src4, (const int*)dst4, (const uint16_t*)Y, (const uint16_t*)ef, w_rad, cg,
                  (const uint16_t*)w_mix, (__nv_bfloat16*)out);
        return;
    }
    {
        const uint4* gp = gs->recs + lane;
        asm volatile("" : "+l"(gp));
        const uint32_t sp = sb + SM_RECS + (w * CELL + lane) * 16, lc = (lane << 24) | 0xFFFFFF;
#pragma unroll
        for (int j = 0; j < 7; j++)
            asm volatile("{.reg .pred p; .reg .u32 l; .reg .u64 a; setp.lt.u32 p, %2, %3; and.b32 l, %3, 0xFFFF; mad.wide.u32 a, l, 128, %1;\n"
                         "@p cp.async.cg.shared.global [%0], [a], 16;}"
                         :: "r"(sp + j * (NW * CELL * 16)), "l"(gp), "r"(lc), "r"(__shfl_sync(0xffffffff, ci, j)) : "memory");
        for (uint32_t m = __ballot_sync(0xffffffff, ci >= (33u << 24)); m; m &= m - 1) {
            const int j = __ffs(m) - 1;
            const uint32_t cj = __shfl_sync(0xffffffff, ci, j);
            if (lane + 32 < (cj >> 24))
                asm volatile("cp.async.cg.shared.global [%0], [%1], 16;" :: "r"(sp + j * (NW * CELL * 16) + 512), "l"(gp + (size_t)(cj & 0xFFFF) * 8 + 32) : "memory");
        }
        asm volatile("cp.async.commit_group;" ::: "memory");
    }
    const int S = __shfl_sync(0xffffffff, max((int)(max(len2 & 0xFFFF, len2 >> 16) + 3) >> 2, DS + 1), 0);
    const int mylen = (lane & 1) ? len2 >> 16 : len2 & 0xFFFF;
    constexpr int NRAW = (CAP + 3) / 4;
    uint32_t bits0 = 0, raw[NRAW];
    unsigned char* meta = smem + SM_META + w * (CAP * STEPB);
    const int la = sb + SM_LIST + w * 2048 + lane * 4, llast = la - (lane & ~1) * 4 + (mylen - 1) * 8;
#pragma unroll
    for (int k = 0; k < NRAW; k++) raw[k] = lds32(min(la + k * 128, llast));
    const uint32_t sv0 = min(raw[0] & 0xFFFC, 4 * (NN - 1));
    const unsigned char* pbase = x + c * 16;
    asm volatile("" : "+l"(pbase));
    auto cpa2 = [&](uint32_t dstp, uint32_t sv) {
        asm volatile("cp.async.cg.shared.global [%0], [%1], 16; cp.async.cg.shared.global [%0+1024], [%1+128], 16;"
                     :: "r"(dstp), "l"(pbase + (size_t)sv * 256) : "memory");
    };
    auto cpa2p = [&](uint32_t dstp, uint32_t sv) {
        asm volatile("{.reg .pred p; setp.ge.s32 p, %2, 0; @p cp.async.cg.shared.global [%0], [%1], 16; @p cp.async.cg.shared.global [%0+1024], [%1+128], 16;}"
                     :: "r"(dstp), "l"(pbase + (size_t)sv * 256), "r"(sv) : "memory");
    };
    auto wait_until = [&](uint32_t tt) {
        asm volatile("{.reg .pred p; .reg .u32 d;\n"
                     "PACE_LOOP: mov.u32 d, %%globaltimer_lo; sub.u32 d, %0, d; setp.lt.u32 p, d, 32768; @p nanosleep.u32 %1; @p bra.uni PACE_LOOP;}"
                     :: "r"(tt), "n"(PSLEEP) : "memory");
    };
    const uint32_t tfill = flag[1] - FOFF;
    auto fill = [&](int i) {
        wait_until(tfill + i * FDT);
        cpa2(wdst + i * SLOTB, __shfl_sync(0xffffffff, sv0, 8 * i + 2 * q)); cpa2(wdst + i * SLOTB + 512, __shfl_sync(0xffffffff, sv0, 8 * i + 2 * q + 1));
        asm volatile("cp.async.commit_group;" ::: "memory");
    };
    fill(0);
    TSTAMP(5);
    auto relay = [&]() {
        uint32_t g0, g1, b0, b1;
        asm volatile("ld.volatile.shared.v2.u32 {%0,%1}, [%4+40]; ld.volatile.shared.v2.u32 {%2,%3}, [%4+16];"
                     : "=r"(g0), "=r"(g1), "=r"(b0), "=r"(b1) : "r"(flg) : "memory");
        const unsigned long long dg = (((unsigned long long)g1 << 32) | g0) - (((unsigned long long)b1 << 32) | b0);
        asm volatile("{.reg .pred p, q; setp.eq.u32 p, %1, 0; setp.lt.u64 q, %2, 30000; @q st.shared.u32 [%3+4], %4;\n"
                     "@p cp.async.cg.shared.global [%3+32], [%0], 16;}"
                     :: "l"(gs->bar), "r"(lane), "l"(dg), "r"(flg), "r"(g0) : "memory");
    };
    auto report = [&](uint32_t cand) {
        uint32_t b0, b1;
        asm volatile("ld.volatile.shared.v2.u32 {%0,%1}, [%2+16];" : "=r"(b0), "=r"(b1) : "r"(flg) : "memory");
        asm volatile("{.reg .pred p; setp.eq.u32 p, %2, 0; @p red.max.relaxed.gpu.global.u64 [%0], %1;}"
                     :: "l"(&gs->t0), "l"((((unsigned long long)b1 << 32) | b0) + (cand - b0)), "r"(lane) : "memory");
    };
    uint32_t ra[NRAW];
#pragma unroll
    for (int k = NRAW - 1; k >= 0; k--) {
        const uint32_t m = (__ballot_sync(0xffffffff, (int)raw[k] < 0) >> g) & 0x01010101u;
        bits0 = __funnelshift_l(m * 0x10204080u, bits0, 4);
        const bool pad = la + k * 128 > llast;
        ra[k] = pad ? NB * CELL * 16 : (raw[k] >> 13) & 0x1FFF0;
        raw[k] = (raw[k] & 0xFFFF) | (pad ? F_PAD : 0);
    }
    if (t < 2) bits0 = ~bits0;
    asm volatile("" : "+r"(bits0), "+r"(ra[0]), "+r"(ra[1]), "+r"(ra[2]), "+r"(ra[3]), "+r"(ra[4]), "+r"(raw[0]), "+r"(raw[1]), "+r"(raw[2]), "+r"(raw[3]), "+r"(raw[4]));
    fill(1);
    asm volatile("cp.async.wait_group 2;" ::: "memory");
    bar_sync(1, NT);
    TSTAMP(19);
    if (w == CW) {
        uint32_t tn; asm volatile("mov.u32 %0, %%globaltimer_lo;" : "=r"(tn));
        if ((int)(tn + RDY - flag[1]) > 0) { report(tn + RDY); flag[1] = tn + RDY; }
    }
    {
        uint4 rv[NRAW];
#pragma unroll
        for (int k = 0; k < NRAW - 1; k++) rv[k] = lds128(ra[k] + (sb + SM_RECS));
        if ((NRAW - 1) * 4 < S) rv[NRAW - 1] = lds128(ra[NRAW - 1] + (sb + SM_RECS));
        fill(2);
        bar_sync(1, NT);
        TSTAMP(12);
        unsigned char* mr = meta + (q - 1) * STEPB + c * 16;
        unsigned char* ms = meta + (q - DS - 1) * STEPB + 128 + c * 4;
#pragma unroll
        for (int k = 0; k < NRAW; k++) {
            if (k == 0) {
                *(uint4*)(mr + (q == 0 ? S * STEPB : 0)) = rv[k];
                *(uint32_t*)(ms + S * STEPB) = raw[0] + F_WRAP;
            } else if (k * 4 + q < S) {
                *(uint4*)(mr + k * 4 * STEPB) = rv[k];
                *(uint32_t*)(ms + k * 4 * STEPB + (k == 1 && q == 0 ? S * STEPB : 0)) = raw[k];
            }
        }
    }
    __syncwarp();
    const uint32_t tphase = PACE / 4;
    uint32_t dreg;
    {
        const int ls = lane >= S ? min(lane - S, S - 1) : lane, st = ls == 0 ? S - 1 : ls - 1;
        const uint4 u0 = *(const uint4*)(meta + st * STEPB + 128), u1 = *(const uint4*)(meta + st * STEPB + 144);
        int pos = (u0.x + u0.y + u0.z + u0.w + u1.x + u1.y + u1.z + u1.w) << 1 >> 6;
        pos += ((u0.x & F_WRAP) ? NN : 0) + (lane >= S ? NN : 0) - NN * (2 * DS + 1) / 32;
        dreg = pos * (int)tphase / NN;
    }
    fill(3);
    TSTAMP(6);

    uint32_t* stash = (uint32_t*)(gs->stash + (b * NW + w) * 256) + lane;
    asm volatile("" : "+l"(stash));
    float acc[4][4];
#pragma unroll
    for (int i = 0; i < 16; i++) acc[i / 4][i % 4] = 0.f;
    uint4 az = *(const uint4*)(smem + SM_AZ + lane * 16);
    uint32_t dcur = dreg, dl = 0, now = flag[1], tcur = 0;
    uint32_t mp = 0, smask = 1, didx = 2;
    uint32_t mend = S * STEPB;
    uint2 r = lds64(mend - STEPB + recl), s0 = lds64(mend - STEPB + srcl);
    auto step = [&](const uint32_t off, const int mode, const bool pc = true) {
        if (mode == 0 && pc) { unsigned long long n64; asm volatile("mov.u64 %0, %%globaltimer;" : "=l"(n64)); now = (uint32_t)n64; }
        const uint2 rc = r, sc = s0;
        if (mode != 4) r = lds64(mp + recl);
        if (mode == 0) s0 = lds64(mp + srcl);
        asm volatile("cp.async.wait_group %0;" :: "n"(DS - 1) : "memory");
        const uint4 xa = lds128(rsrc + off), xb = lds128(rsrc + off + 512), xc = lds128(rsrc + off + 1024), xd = lds128(rsrc + off + 1536);
        if (mode == 0) {
            if (pc) { dl = __shfl_sync(0xffffffff, dcur, didx); didx += 2; }
            cpa2p(wdst + off, sc.x); cpa2p(wdst + off + 512, sc.y);
        }
        if (mode == 1 && w < 16) {
#pragma unroll
            for (int j = 0; j < 4; j++) {
                const int kk = 4 * j + q, ch = 16 * (w & 7) + 2 * (kk & 7) + (kk >> 3);
                asm volatile("cp.async.cg.shared.global [%0], [%1], 16;" :: "r"(ring0 + kk * 128 + ((c ^ (kk & 7)) << 4)), "l"(w_mix + ch * 16 + (w >> 3) * 8 + c) : "memory");
            }
            asm volatile("cp.async.mbarrier.arrive.noinc.shared.b64 [%0];" :: "r"(mbarW) : "memory");
        }
        if (mode == 2 || mode == 3) {
#pragma unroll
            for (int j = 0; j < 4; j += mode - 1)
                asm volatile("cp.async.cg.shared.global [%0], [%1], 16;" :: "r"(ring0 + off + j * 512 + lane * 16), "l"(stash + (mode - 2) * 512 + j * 128 + lane * 3) : "memory");
        }
        if (mode < 4) asm volatile("cp.async.commit_group;" ::: "memory");
        float z[4], y[4], t1[4], t2[4];
        mma1688z(z, az.x, az.y, rc.y);
        mma1688z(y, az.z, az.w, rc.y);
        uint32_t bt;
        asm("{.reg .pred p; .reg .b32 m; and.b32 m, %2, %3; setp.ne.u32 p, m, 0; selp.b32 %0, %1, 0, p;}" : "=r"(bt) : "r"(rc.x), "r"(bits0), "r"(smask));
        mma1688z(t1, at[0], at[1], bt);
        mma1688z(t2, at[2], at[3], bt);
        const uint32_t T0 = pack2(t1[0], t1[2]), T1 = pack2(t2[0], t2[2]), T2 = pack2(t1[1], t1[3]), T3 = pack2(t2[1], t2[3]);
        uint32_t R[8];
#pragma unroll
        for (int i = 0; i < 4; i++) { R[i] = __float_as_uint(silu_h(z[i])); R[4 + i] = __float_as_uint(silu_h(y[i])); }
        mma16816(acc[0], mul_hi(xa.x, R[0]), mul_hi(xa.z, R[2]), mul_hi(xa.y, R[0]), mul_hi(xa.w, R[2]), T0, T1);
        mma16816(acc[1], mul_hi(xb.x, R[1]), mul_hi(xb.z, R[3]), mul_hi(xb.y, R[1]), mul_hi(xb.w, R[3]), T2, T3);
        mma16816(acc[2], mul_hi(xc.x, R[4]), mul_hi(xc.z, R[6]), mul_hi(xc.y, R[4]), mul_hi(xc.w, R[6]), T0, T1);
        mma16816(acc[3], mul_hi(xd.x, R[5]), mul_hi(xd.z, R[7]), mul_hi(xd.y, R[5]), mul_hi(xd.w, R[7]), T2, T3);
        mp += STEPB; smask <<= 1;
    };
    auto putacc = [&](uint32_t* p) {
#pragma unroll
        for (int i = 0; i < 16; i++) acc[i / 4][i % 4] *= 1.0028f;
        p[0] = pack2(acc[0][0], acc[0][1]); p[32] = pack2(acc[0][2], acc[0][3]); p[64] = pack2(acc[2][0], acc[2][1]); p[96] = pack2(acc[2][2], acc[2][3]);
        p[256] = pack2(acc[1][0], acc[1][1]); p[288] = pack2(acc[1][2], acc[1][3]); p[320] = pack2(acc[3][0], acc[3][1]); p[352] = pack2(acc[3][2], acc[3][3]);
    };
    int ph = 0;
    auto phase_end = [&](const int k) {
        az = lds128(sb + SM_AZ + (ph + 1) * 512 + lane * 16);
        putacc(stash + ph * ph * 128);
#pragma unroll
        for (int i = 0; i < 16; i++) acc[i / 4][i % 4] = 0.f;
        pbase += 256; mp = 0; smask = 1; ph++;
        dcur += tphase; didx = 1 + (k & 1);
        if (ph == 3) {
            mend -= DS * STEPB;
            dcur += (int)(dcur - __shfl_sync(0xffffffff, dcur, 0)) * (((w >> 2) - 2) * FAN) >> 8;
        }
        WSTAMP(ph - 1);
    };
    uint32_t t0 = now;
    if (w == PW) {
        asm volatile("mov.u32 %0, %%globaltimer_lo;" : "=r"(now));
        now += PTOL - PTOL0;
    }
    const uint32_t bias = w == RW ? 1u << 20 : 0;
    if (w == RW) relay();
    dcur += bias;
    auto body = [&](const int k) -> bool {
        if (k == 2) asm volatile("ld.volatile.shared.u32 %0, [%1+4];" : "=r"(t0) : "r"(flg));
        const bool pc = k & 1;
        step(k * SLOTB, 0, pc);
        if (!pc) {
            if (mp == mend) phase_end(k);
        } else if (mp == mend || now < dl) {
            if (mp == mend) {
                if (k == 3 && ph == 3) return true;
                phase_end(k);
            }
            if (w == RW) {
                dl -= 1u << 20; relay();
                {
                    const int row = (mp / (2 * STEPB)) * (16 * XPF) + (lane >> 1);
#pragma unroll
                    for (int u = 0; u < XPF; u++)
                        asm volatile("{.reg .pred p; setp.lt.s32 p, %1, %2; @p prefetch.global.L2 [%0];}"
                                     :: "l"(x + (size_t)(n0 + row + 16 * u) * 1024 + (ph + 1) * 256 + (lane & 1) * 128), "r"(row + 16 * u), "r"(ph < 3 ? nn : 0));
                }
            }
            wait_until(dl);
        }
        return false;
    };
    if (w >= 4 && w < 9 && (w - 4) * 16 + (lane >> 1) < nn && b >= XPF0)
        asm volatile("prefetch.global.L2 [%0];" :: "l"(x + (size_t)(n0 + (w - 4) * 16 + (lane >> 1)) * 1024 + (lane & 1) * 128));
    {
        const uint32_t d0 = __shfl_sync(0xffffffff, dreg, 0);
        if (w == RW) {
            uint32_t g0, tn; int spins = 0;
            do {
                asm volatile("ld.relaxed.gpu.global.u32 %0, [%2]; mov.u32 %1, %%globaltimer_lo;" : "=r"(g0), "=r"(tn) : "l"(&gs->t0) : "memory");
                if (g0 - t0 < 30000) { t0 = g0; flag[1] = g0; }
            } while (__shfl_sync(0xffffffff, t0 - tn, 0) < 32768 && ++spins < 64);
        }
        asm volatile("{.reg .pred p; .reg .u32 d;\n"
                     "PACE_LOOP: ld.volatile.shared.u32 %0, [%2+4]; mov.u32 d, %%globaltimer_lo; sub.u32 d, %1, d; add.u32 d, d, %0;\n"
                     "setp.lt.u32 p, d, 32768; @p nanosleep.u32 32; @p bra.uni PACE_LOOP;}"
                     : "=&r"(t0) : "r"(d0), "r"(flg) : "memory");
    }
    while (true) {
        if (w == PW) {
            const uint32_t cand = now - dl + tcur - PTOL;
            if ((int)(cand - t0) > 0) report(cand);
        }
        dcur += t0 - tcur; tcur = t0;
        body(0); body(1); body(2);
        if (body(3)) break;
    }
    __syncwarp();
    step(0, 1);
    { uint32_t tn; asm volatile("mov.u32 %0, %%globaltimer_lo;" : "=r"(tn)); wait_until(tn + (w >> 2) * TDEL); }
    step(SLOTB, 2); step(2 * SLOTB, 3); step(3 * SLOTB, 4);
    WSTAMP(3); ESTAMP(0);

    {
        putacc((uint32_t*)(smem + SM_RING + 2 * SLOTB + w * 2048 + 512) + lane);
        const int wg = w >> 2, w4 = w & 3;
        int nd[8];
#pragma unroll
        for (int j = 0; j < 8; j++) { const int l = wg * 8 + j; nd[j] = order[(t >> 1) ? 79 - l : l]; asm volatile("" : "+r"(nd[j])); }
        const bool odd = t & 1;
        uint2* ob = (uint2*)out + (size_t)n0 * 128 + w4 * 16 + g + (odd ? 8 : 0);
        asm volatile("cp.async.wait_all;" ::: "memory");
        mbar_wait(mbarW, 0);
        asm volatile("fence.proxy.async.shared::cta;" ::: "memory");
        ESTAMP(1);
        bar_sync(2 + wg, 128);
        uint32_t ticket = 0;
        if ((tid & 127) == 0) {
            asm volatile("atom.shared.add.u32 %0, [%1+48], 1;" : "=r"(ticket) : "r"(flg) : "memory");
            int spins = 0;
            while (flag[13] < ticket && ++spins < (1 << 16)) __nanosleep(40);
        }
        bar_sync(2 + wg, 128);
        const uint64_t descA0 = (uint64_t)(((sb + SM_RING) & 0x3FFFF) >> 4) | ((uint64_t)1 << 16) | ((uint64_t)(1024 >> 4) << 32) | ((uint64_t)1 << 62);
        const uint64_t descB0 = (uint64_t)(((sb + SM_RING + SLOTB + wg * 8192) & 0x3FFFF) >> 4) | ((uint64_t)(128 >> 4) << 16) | ((uint64_t)(1024 >> 4) << 32);
        float d[2][32];
        asm volatile("wgmma.fence.sync.aligned;" ::: "memory");
        ESTAMP(2);
#pragma unroll
        for (int mt = 0; mt < 2; mt++) {
#pragma unroll
            for (int ks = 0; ks < 8; ks++) {
                if (mt * 8 + ks == RELK)
                    asm volatile("{.reg .pred p; setp.eq.u32 p, %1, 0; @p st.volatile.shared.u32 [%0+52], %2;}" :: "r"(flg), "r"(tid & 127), "r"(ticket + 1) : "memory");
                const uint64_t da = descA0 + (uint64_t)((ks * 2048 + mt * 16384) >> 4), db = descB0 + (uint64_t)(((ks & 3) * 256 + (ks >> 2) * SLOTB) >> 4);
                asm volatile("{.reg .pred p; setp.ne.b32 p, %34, 0;\n"
                    "wgmma.mma_async.sync.aligned.m64n64k16.f32.bf16.bf16 "
                    "{%0,%1,%2,%3,%4,%5,%6,%7,%8,%9,%10,%11,%12,%13,%14,%15,%16,%17,%18,%19,%20,%21,%22,%23,%24,%25,%26,%27,%28,%29,%30,%31}, %32, %33, p, 1, 1, 1, 1;}"
                    : "+f"(d[mt][0]), "+f"(d[mt][1]), "+f"(d[mt][2]), "+f"(d[mt][3]), "+f"(d[mt][4]), "+f"(d[mt][5]), "+f"(d[mt][6]), "+f"(d[mt][7]),
                      "+f"(d[mt][8]), "+f"(d[mt][9]), "+f"(d[mt][10]), "+f"(d[mt][11]), "+f"(d[mt][12]), "+f"(d[mt][13]), "+f"(d[mt][14]), "+f"(d[mt][15]),
                      "+f"(d[mt][16]), "+f"(d[mt][17]), "+f"(d[mt][18]), "+f"(d[mt][19]), "+f"(d[mt][20]), "+f"(d[mt][21]), "+f"(d[mt][22]), "+f"(d[mt][23]),
                      "+f"(d[mt][24]), "+f"(d[mt][25]), "+f"(d[mt][26]), "+f"(d[mt][27]), "+f"(d[mt][28]), "+f"(d[mt][29]), "+f"(d[mt][30]), "+f"(d[mt][31])
                    : "l"(da), "l"(db), "r"(ks));
            }
            asm volatile("wgmma.commit_group.sync.aligned;" ::: "memory");
        }
#pragma unroll
        for (int mt = 0; mt < 2; mt++) {
            if (mt == 0) asm volatile("wgmma.wait_group.sync.aligned 1;" ::: "memory");
            else asm volatile("wgmma.wait_group.sync.aligned 0;" ::: "memory");
            ESTAMP(3 + mt);
#pragma unroll
            for (int i = 0; i < 32; i++) asm volatile("" : "+f"(d[mt][i]) :: "memory");
#pragma unroll
            for (int j = 0; j < 8; j++) {
                const uint32_t v0 = pack2(d[mt][4 * j], d[mt][4 * j + 1]), v1 = pack2(d[mt][4 * j + 2], d[mt][4 * j + 3]);
                const uint32_t rv = __shfl_xor_sync(0xffffffff, odd ? v0 : v1, 1);
                if (nd[j] < nn) ob[nd[j] * 128 + mt * 64] = odd ? make_uint2(rv, v1) : make_uint2(v0, rv);
            }
        }
    }
    TSTAMP(8); ESTAMP(5);
}

__global__ void __launch_bounds__(NT, 1)
tfn_fallback(const uint16_t* x, const int* src, const int* dst, const uint16_t* Y, const uint16_t* ef, const uint16_t* w_rad,
             const uint16_t* cg, const uint16_t* w_mix, __nv_bfloat16* out) {
    extern __shared__ __align__(1024) unsigned char smem[];
    const int n0 = blockIdx.x * NPB;
    slow_path(smem, n0, min(NPB, NN - n0), x, src, dst, Y, ef, w_rad, cg, w_mix, out);
}

}

extern "C" void kernel_launch(void* const* d_in, const int* in_sizes, int n_in, void* d_out, int out_size) {
    (void)in_sizes; (void)n_in; (void)out_size;
    cudaFuncSetAttribute(tfn_kernel, cudaFuncAttributeMaxDynamicSharedMemorySize, SM_TOTAL);
    int dev = 0, sms = 0;
    cudaGetDevice(&dev);
    cudaDeviceGetAttribute(&sms, cudaDevAttrMultiProcessorCount, dev);
    if (sms < NB) {
        cudaFuncSetAttribute(tfn_fallback, cudaFuncAttributeMaxDynamicSharedMemorySize, NPB * 2048);
        tfn_fallback<<<NB, NT, NPB * 2048, cudaStreamPerThread>>>((const uint16_t*)d_in[0], (const int*)d_in[1], (const int*)d_in[2], (const uint16_t*)d_in[3],
            (const uint16_t*)d_in[4], (const uint16_t*)d_in[5], (const uint16_t*)d_in[6], (const uint16_t*)d_in[7], (__nv_bfloat16*)d_out);
        return;
    }
    Scratch* gs = nullptr;
    cudaGetSymbolAddress((void**)&gs, g_scratch);
    cudaLaunchConfig_t cfg = {};
    cfg.gridDim = dim3(NB); cfg.blockDim = dim3(NT); cfg.dynamicSmemBytes = SM_TOTAL; cfg.stream = cudaStreamPerThread;
    cudaLaunchAttribute at[1];
    at[0].id = cudaLaunchAttributeCooperative; at[0].val.cooperative = 1;
    cfg.attrs = at; cfg.numAttrs = 1;
    cudaLaunchKernelEx(&cfg, tfn_kernel, (const unsigned char*)d_in[0], (const int4*)d_in[1], (const int4*)d_in[2],
                       (const uint4*)d_in[3], (const uint4*)d_in[4], (const uint16_t*)d_in[5], (const uint16_t*)d_in[6],
                       (const uint4*)d_in[7], (uint32_t*)d_out, gs);
}
```

```cpp
#include <cuda_runtime.h>
#include <cuda_bf16.h>
#include <stdint.h>

namespace {

constexpr int NN = 10000;
constexpr int NE = 320000;
constexpr int NB = 132;
constexpr int NW = 20;
constexpr int NT = NW * 32;
constexpr int CW = NW - 1;
constexpr int PW = 10;
constexpr int RW = 1;
constexpr int NPB = 76;
constexpr int CELL = 48;
constexpr int RCH = 2880;
constexpr int CAP = 19;
constexpr int DS = 4;
constexpr int STEPB = 160;
constexpr int NE4 = NE / 4;
constexpr int NPIECE = NB * 8;
constexpr int KB = 320, KN = 32 * KB;
constexpr uint32_t F_PAD = 0x80000000u;
constexpr uint32_t F_WRAP = 1;

constexpr int SLOTB = NW * 2048;
constexpr int SM_RING = 0;
constexpr int SM_META = SM_RING + DS * SLOTB;
constexpr int SM_AZ = SM_META + NW * CAP * STEPB;
constexpr int SM_MISC = SM_AZ + 2048;
constexpr int SM_TOTAL = SM_MISC + 2048;
constexpr int SM_STAGE = SM_RING;
constexpr int SM_HIST = SM_RING + 25600;
constexpr int SM_POS = SM_RING;
constexpr int SM_SMALL = SM_HIST + 13056;
constexpr int SM_LIST = SM_RING + SLOTB;
constexpr int SM_ROUT = SM_RING + 2 * SLOTB;
constexpr int SM_RECS = SM_RING + 3 * SLOTB;
constexpr int SM_RAWY = SM_META;
constexpr int SM_RAWE = SM_RAWY + 608 * 32;
constexpr int SM_KEYS = SM_RAWE + 608 * 32;
static_assert(SM_TOTAL <= 232448 && SM_KEYS + NPIECE * 16 <= SM_AZ, "smem");
static_assert(SM_RECS + NB * CELL * 16 + 16 <= SM_AZ && SM_KEYS + NPIECE * 16 <= SM_RECS + NB * CELL * 16 && SM_SMALL + 1152 <= SLOTB && DS == 4, "smem");

struct __align__(1024) Scratch {
    uint4 keys[NB * NPIECE];
    uint4 recs[NB * RCH];
    uint4 stash[NB * NW * 256];
    unsigned bar[2];
    unsigned long long t0;
};
__device__ Scratch g_scratch;
#define TSTAMP(i)
#define TSTAMPC(i)
#define WSTAMP(i)
#define ESTAMP(i)

__device__ __forceinline__ void mma16816(float* d, uint32_t a0, uint32_t a1, uint32_t a2, uint32_t a3, uint32_t b0, uint32_t b1) {
    asm("mma.sync.aligned.m16n8k16.row.col.f32.bf16.bf16.f32 {%0,%1,%2,%3}, {%4,%5,%6,%7}, {%8,%9}, {%0,%1,%2,%3};"
        : "+f"(d[0]), "+f"(d[1]), "+f"(d[2]), "+f"(d[3]) : "r"(a0), "r"(a1), "r"(a2), "r"(a3), "r"(b0), "r"(b1));
}
__device__ __forceinline__ void mma1688z(float* d, uint32_t a0, uint32_t a1, uint32_t b0) {
    asm("mma.sync.aligned.m16n8k8.row.col.f32.bf16.bf16.f32 {%0,%1,%2,%3}, {%4,%5}, {%6}, {%7,%7,%7,%7};"
        : "=f"(d[0]), "=f"(d[1]), "=f"(d[2]), "=f"(d[3]) : "r"(a0), "r"(a1), "r"(b0), "f"(0.f));
}
__device__ __forceinline__ uint32_t pack2(float lo, float hi) {
    uint32_t r; asm("cvt.rn.bf16x2.f32 %0, %1, %2;" : "=r"(r) : "f"(hi), "f"(lo)); return r;
}
__device__ __forceinline__ float silu_h(float h) {
    float t; asm("tanh.approx.f32 %0, %1;" : "=f"(t) : "f"(h)); return fmaf(h, t, h);
}
__device__ __forceinline__ uint32_t mul_hi(uint32_t v, uint32_t r) {
    __nv_bfloat162 a = *(__nv_bfloat162*)&v, b = *(__nv_bfloat162*)&r; __nv_bfloat162 c = __hmul2(a, __high2bfloat162(b)); return *(uint32_t*)&c;
}
__device__ __forceinline__ uint32_t lds32(uint32_t a) {
    uint32_t r; asm volatile("ld.shared.u32 %0, [%1];" : "=r"(r) : "r"(a) : "memory"); return r;
}
__device__ __forceinline__ void sts32(uint32_t a, uint32_t v) { asm volatile("st.shared.u32 [%0], %1;" :: "r"(a), "r"(v) : "memory"); }
__device__ __forceinline__ uint2 lds64(uint32_t a) {
    uint2 r; asm volatile("ld.shared.v2.u32 {%0,%1}, [%2];" : "=r"(r.x), "=r"(r.y) : "r"(a)); return r;
}
__device__ __forceinline__ uint4 lds128(uint32_t a) {
    uint4 r; asm volatile("ld.shared.v4.u32 {%0,%1,%2,%3}, [%4];" : "=r"(r.x), "=r"(r.y), "=r"(r.z), "=r"(r.w) : "r"(a) : "memory"); return r;
}
__device__ __forceinline__ void bar_sync(int id, int n) { asm volatile("bar.sync %0, %1;" :: "r"(id), "r"(n) : "memory"); }
__device__ __forceinline__ void bar_arrive(int id, int n) { asm volatile("bar.arrive %0, %1;" :: "r"(id), "r"(n) : "memory"); }
__device__ __forceinline__ void mbar_wait(uint32_t bar, uint32_t ph) {
    uint32_t done; int spins = 0;
    do {
        asm volatile("{.reg .pred p; mbarrier.try_wait.parity.shared.b64 p, [%1], %2; selp.u32 %0,1,0,p;}" : "=r"(done) : "r"(bar), "r"(ph) : "memory");
    } while (!done && ++spins < (1 << 22));
}
__device__ __forceinline__ void gbar_arrive(unsigned* ctr) {
    asm volatile("red.inc.relaxed.gpu.global.u32 [%0], %1;" :: "l"(ctr), "n"(2 * NB - 1) : "memory");
}
__device__ __forceinline__ int chunk_start4(int c) { return (c * NE4) / NB; }
__device__ __forceinline__ float bf2f(uint32_t h) { return __uint_as_float(h << 16); }

__device__ __noinline__ void slow_path(unsigned char* smem, int n0, int nn, const uint16_t* x, const int* src, const int* dst,
                                       const uint16_t* Y, const uint16_t* ef, const uint16_t* w_rad, const uint16_t* cg,
                                       const uint16_t* w_mix, __nv_bfloat16* out) {
    float* agg = (float*)smem;
    const int tid = threadIdx.x, lane = tid & 31, w = tid >> 5;
    bar_sync(1, NT);
    for (int i = tid; i < NPB * 512; i += NT) agg[i] = 0.f;
    bar_sync(1, NT);
    for (int e0 = w * 32; e0 < NE; e0 += NT) {
        int dl = dst[e0 + lane] - n0;
        unsigned m = __ballot_sync(0xffffffff, dl >= 0 && dl < nn);
        while (m) {
            int l = __ffs(m) - 1; m &= m - 1;
            int e = e0 + l, d = __shfl_sync(0xffffffff, dl, l), s = src[e];
            float T[16];
            for (int i = 0; i < 4; i++) for (int o = 0; o < 4; o++) {
                float a = 0.f;
                for (int f = 0; f < 4; f++) a += bf2f(Y[e * 4 + f]) * bf2f(cg[i * 16 + f * 4 + o]);
                T[i * 4 + o] = a;
            }
            for (int k = 0; k < 4; k++) {
                int c = lane + 32 * k;
                float z = 0.f;
                for (int j = 0; j < 4; j++) z += bf2f(ef[e * 4 + j]) * bf2f(w_rad[j * 128 + c]);
                float R = z / (1.f + __expf(-z));
                for (int o = 0; o < 4; o++) {
                    float a = 0.f;
                    for (int i = 0; i < 4; i++) a += bf2f(x[(size_t)s * 512 + c * 4 + i]) * T[i * 4 + o];
                    atomicAdd(&agg[d * 512 + c * 4 + o], R * a);
                }
            }
        }
    }
    bar_sync(1, NT);
    for (int i = tid; i < nn * 512; i += NT) {
        int n = i >> 9, d = (i >> 2) & 127, o = i & 3;
        float a = 0.f;
        for (int c = 0; c < 128; c++) a += agg[n * 512 + c * 4 + o] * bf2f(w_mix[c * 128 + d]);
        out[(size_t)(n0 + n) * 512 + (i & 511)] = __float2bfloat16(a);
    }
}

#define PACE 23100
#define YDELAY 300
#define POFF 3650
#define PSLEEP 64
#define FDT 350
#define FOFF 1500
#define RELK 12
#define FAN 16
#define TDEL 100
#define RDY 600
#define XPF 2
#define XPF0 40
#define PTOL0 300
#define PTOL 1100
__global__ void __launch_bounds__(NT, 1)
tfn_kernel(const unsigned char* __restrict__ x, const int4* __restrict__ src4, const int4* __restrict__ dst4,
           const uint4* __restrict__ Y, const uint4* __restrict__ ef, const uint16_t* __restrict__ w_rad,
           const uint16_t* __restrict__ cg, const uint4* __restrict__ w_mix, uint32_t* __restrict__ out, Scratch* __restrict__ gs) {
    extern __shared__ __align__(1024) unsigned char smem[];
    const uint32_t sb = (uint32_t)__cvta_generic_to_shared(smem);
    const int b = blockIdx.x, tid = threadIdx.x, lane = tid & 31, g = lane >> 2, t = lane & 3;
    const int w = __shfl_sync(0xffffffff, tid >> 5, 0);
    uint32_t* stage = (uint32_t*)(smem + SM_STAGE);
    uint32_t* hist = (uint32_t*)(smem + SM_HIST);
    uint32_t* cnt = (uint32_t*)(smem + SM_MISC);
    uint32_t* deg = cnt + 136;
    uint32_t* order = deg + 104;
    uint32_t* cnt2 = order + 80;
    volatile uint32_t* flag = cnt2 + 136;
    const uint32_t mbarK = sb + SM_MISC + 1920, mbarR = mbarK + 8, mbarW = mbarK + 16;
    const int n0 = b * NPB, nn = min(NPB, NN - n0);
    TSTAMP(0);

    const int c0 = chunk_start4(b), c1 = chunk_start4(b + 1);
    const bool has4 = c0 + tid < c1;
    int4 d4 = make_int4(0, 0, 0, 0), s4 = d4;
    if (has4) { d4 = __ldg(dst4 + c0 + tid); s4 = __ldg(src4 + c0 + tid); }
    unsigned par = 0;
    if (tid == NT - 1) {
        asm volatile("ld.relaxed.gpu.global.u32 %0, [%1];" : "=r"(par) : "l"(gs->bar) : "memory");
        asm volatile("mbarrier.init.shared.b64 [%0], 1;" :: "r"(mbarK));
        asm volatile("mbarrier.init.shared.b64 [%0], 1;" :: "r"(mbarR));
        asm volatile("mbarrier.init.shared.b64 [%0], 512;" :: "r"(mbarW));
        asm volatile("fence.mbarrier_init.release.cluster;" ::: "memory");
        flag[0] = 0; flag[12] = 0; flag[13] = 0; flag[15] = 0;
    }
    if (w == CW) {
        asm volatile("cp.async.cg.shared.global [%0], [%1], 16;" :: "r"(sb + SM_SMALL + lane * 16), "l"(w_rad + lane * 8) : "memory");
        asm volatile("cp.async.cg.shared.global [%0], [%1], 16;" :: "r"(sb + SM_SMALL + 512 + lane * 16), "l"(w_rad + 256 + lane * 8) : "memory");
        if (lane < 8) asm volatile("cp.async.cg.shared.global [%0], [%1], 16;" :: "r"(sb + SM_SMALL + 1024 + lane * 16), "l"(cg + lane * 8) : "memory");
    }
    ((uint4*)hist)[tid] = make_uint4(0, 0, 0, 0);
    {
        const uint32_t dk = (80 + b % 22) * KN + (b & 31) * KB;
#pragma unroll
        for (int j = 0; j < 3; j++) if (tid + j * NT < NB * CELL / 4) ((uint4*)stage)[tid + j * NT] = make_uint4(dk, dk, dk, dk);
    }
    if (tid < 136) cnt[tid] = 0;
    if (tid == 0) { *(uint4*)(smem + SM_MISC + 1824 + 32) = make_uint4(0, 0, 0, 0); *(uint4*)(smem + SM_RECS + NB * CELL * 16) = make_uint4(0, 0, 0, 0); }
    if (tid < 80) { deg[tid] = 127 - tid; order[tid] = tid; }
    __syncthreads();
    TSTAMP(9);
    if (tid == 64) {
        __nanosleep(YDELAY);
        asm volatile("mbarrier.arrive.expect_tx.shared.b64 _, [%0], %1;" :: "r"(mbarR), "r"((c1 - c0) * 64) : "memory");
        asm volatile("cp.async.bulk.shared::cluster.global.mbarrier::complete_tx::bytes [%0], [%1], %2, [%3];"
                     :: "r"(sb + SM_RAWY), "l"(Y + 2 * c0), "r"((c1 - c0) * 32), "r"(mbarR) : "memory");
        asm volatile("cp.async.bulk.shared::cluster.global.mbarrier::complete_tx::bytes [%0], [%1], %2, [%3];"
                     :: "r"(sb + SM_RAWE), "l"(ef + 2 * c0), "r"((c1 - c0) * 32), "r"(mbarR) : "memory");
    }

    uint32_t bin[4] = {0, 0, 0, 0}, slot[4] = {0, 0, 0, 0};
    if (has4) {
        const uint32_t dd[4] = {(uint32_t)d4.x, (uint32_t)d4.y, (uint32_t)d4.z, (uint32_t)d4.w}, ss[4] = {(uint32_t)s4.x, (uint32_t)s4.y, (uint32_t)s4.z, (uint32_t)s4.w};
#pragma unroll
        for (int k = 0; k < 4; k++) { bin[k] = dd[k] / NPB; slot[k] = atomicAdd(&cnt[bin[k]], 1); }
#pragma unroll
        for (int k = 0; k < 4; k++) stage[bin[k] * CELL + min(slot[k], CELL - 1)] = (dd[k] - bin[k] * NPB) * KN + ss[k];
    }
    if (w == CW) {
        if (tid == NT - 1) { par = par >= NB; flag[14] = (par ^ 1) << 31; }
        asm volatile("cp.async.wait_all;" ::: "memory");
    }
    bar_sync(1, NT);
    TSTAMP(1);
    const uint32_t tag = flag[14];
#pragma unroll
    for (int j = 0; j < 2; j++) {
        const int i = tid + j * NT;
        if (i < NPIECE) {
            const uint2 sa = *(const uint2*)(stage + i * 6), sc = *(const uint2*)(stage + i * 6 + 2);
            uint2 se = *(const uint2*)(stage + i * 6 + 4);
            const uint32_t cf = cnt[i >> 3], cn = min(cf, 63u);
            if ((i & 7) == 7) {
                const uint32_t al = cf > CELL - 8 ? 7 : 0;
                uint32_t o;
                asm volatile("atom.shared.add.u32 %0, [%1], %2;" : "=r"(o) : "r"(sb + SM_MISC + 1824 + 60), "r"(cf + al) : "memory");
                se.y = (o + al) & ~al;
                cnt2[i >> 3] = se.y;
            }
            asm volatile("{.reg .b64 lo, hi; mov.b64 lo, {%1,%2}; mov.b64 hi, {%3,%4}; st.relaxed.gpu.global.v2.b64 [%0], {lo, hi};}"
                         :: "l"(gs->keys + ((i >> 3) * NB + b) * 8 + ((i ^ b) & 7)),
                            "r"(sa.x | (se.x << 20)), "r"(sa.y | ((se.x >> 12) << 20) | ((cn & 7) << 28) | tag),
                            "r"(sc.x | (se.y << 20)), "r"(sc.y | ((se.y >> 12) << 20) | ((cn >> 3) << 28) | tag) : "memory");
        }
    }
    bar_sync(1, NT);
    if (tid == NT - 1) {
        TSTAMPC(10);
        gbar_arrive(&gs->bar[0]);
        asm volatile("mbarrier.arrive.expect_tx.shared.b64 _, [%0], %1;" :: "r"(mbarK), "r"(NPIECE * 16) : "memory");
        unsigned v; int spins = 0;
        do { asm volatile("ld.relaxed.gpu.global.u32 %0, [%1];" : "=r"(v) : "l"(gs->bar) : "memory"); } while ((v >= NB) == par && ++spins < (1 << 22));
        TSTAMPC(13);
        asm volatile("fence.proxy.async.global;" ::: "memory");
        asm volatile("cp.async.bulk.shared::cluster.global.mbarrier::complete_tx::bytes [%0], [%1], %2, [%3];"
                 :: "r"(sb + SM_KEYS), "l"(gs->keys + b * NPIECE), "r"(NPIECE * 16), "r"(mbarK) : "memory");
    }
    __syncwarp();
    uint32_t at[4];
    {
        const int o = g & 3, f = 2 * (t & 1);
#pragma unroll
        for (int i = 0; i < 4; i++) {
            const uint16_t* cp = (const uint16_t*)(smem + SM_SMALL + 1024) + i * 16 + f * 4 + o;
            at[i] = (t >> 1) == (g >> 2) ? cp[0] | ((uint32_t)cp[4] << 16) : 0;
        }
    }

    const int q = lane >> 3, c = lane & 7;
    const uint32_t ring0 = sb + SM_RING + w * 2048;
    uint32_t wdst = ring0 + q * 128 + ((c + 2 * q) & 7) * 16;
    uint32_t rsrc = ring0 + t * 128 + ((g + 2 * t) & 7) * 16;
    uint32_t recl = sb + SM_META + w * (CAP * STEPB) + g * 16 + (t & 1) * 8, srcl = sb + SM_META + w * (CAP * STEPB) + 128 + q * 8;
    uint32_t flg = sb + SM_MISC + (136 + 104 + 80 + 136) * 4;
    asm volatile("" : "+r"(wdst), "+r"(rsrc), "+r"(recl), "+r"(srcl), "+r"(flg));
    auto setflag = [&]() { sts32(flg, 1); };
    uint32_t key[2][6], ha[2][6], rk[2][6], kidx[2], ka[2], kc[2];
    int nk[2];
#pragma unroll
    for (int j = 0; j < 2; j++) {
        const int i0 = j ? 2 * 608 - 1 - tid : tid, i = min(i0, NPIECE - 1), r = i / NB, cc = i - r * NB;
        ka[j] = sb + SM_KEYS + (cc * 8 + ((r ^ cc) & 7)) * 16;
        kidx[j] = (cc * CELL + r * 6) << 17;
        kc[j] = sb + SM_MISC + cc * 4;
        nk[j] = i0 < NPIECE && w < CW ? -6 * r : -1000;
    }
    asm volatile("" : "+r"(at[0]), "+r"(at[1]), "+r"(at[2]), "+r"(at[3]), "+r"(ka[0]), "+r"(ka[1]), "+r"(kidx[0]), "+r"(kidx[1]), "+r"(kc[0]), "+r"(kc[1]), "+r"(nk[0]), "+r"(nk[1]));
    if (w == CW) {
        __syncwarp();
        bar_sync(7, NT);
        if (tid == NT - 1) {
            TSTAMPC(11);
            asm volatile("cp.async.bulk.global.shared::cta.bulk_group [%0], [%1], %2;"
                         :: "l"(gs->recs + b * RCH), "r"(sb + SM_ROUT), "r"(((flag[15] + 1) & ~1u) * 16) : "memory");
            asm volatile("cp.async.bulk.commit_group;" ::: "memory");
            mbar_wait(mbarK, 0);
            unsigned long long tbase;
            asm volatile("mov.u64 %0, %%globaltimer;" : "=l"(tbase));
            tbase += POFF;
            flag[1] = (uint32_t)tbase; flag[4] = (uint32_t)tbase; flag[5] = (uint32_t)(tbase >> 32);
            asm volatile("red.max.relaxed.gpu.global.u64 [%0], %1;" :: "l"(&gs->t0), "l"(tbase) : "memory");
            if (b < 128) asm volatile("cp.async.bulk.prefetch.L2.global [%0], 256;" :: "l"(w_mix + b * 16));
            asm volatile("cp.async.bulk.wait_group 0;" ::: "memory");
            TSTAMPC(14);
            gbar_arrive(&gs->bar[1]);
            TSTAMPC(15);
        }
    } else {
        if (w < 8) {
            const uint32_t* wp = (const uint32_t*)(smem + SM_SMALL) + (t & 1) * 128 + 8 * w + g;
            const uint32_t wr0 = t < 2 ? wp[0] : 0, wr1 = t < 2 ? wp[64] : 0;
            *(uint2*)(smem + SM_AZ + (w >> 1) * 512 + lane * 16 + (w & 1) * 8) =
                make_uint2(pack2(0.5f * bf2f(wr0 & 0xFFFF), 0.5f * bf2f(wr1 & 0xFFFF)), pack2(0.5f * bf2f(wr0 >> 16), 0.5f * bf2f(wr1 >> 16)));
        }
        const bool sw = g & 1;
        uint32_t rp[4];
#pragma unroll
        for (int k = 0; k < 4; k++) rp[k] = cnt2[bin[k]] + slot[k];
        uint4* ro = (uint4*)(smem + SM_ROUT);
        uint4 *p0 = ro + (sw ? rp[2] : rp[0]), *p1 = ro + (sw ? rp[3] : rp[1]), *p2 = ro + (sw ? rp[0] : rp[2]), *p3 = ro + (sw ? rp[1] : rp[3]);
        const uint32_t ya = sb + SM_RAWY + tid * 32 + (sw ? 16 : 0);
        mbar_wait(mbarR, 0);
        TSTAMP(18);
        if (has4) {
            const uint4 y0 = lds128(ya), e0 = lds128(ya + (SM_RAWE - SM_RAWY)), y1 = lds128(ya ^ 16), e1 = lds128((ya ^ 16) + (SM_RAWE - SM_RAWY));
            *p0 = make_uint4(y0.x, e0.x, y0.y, e0.y); *p1 = make_uint4(y0.z, e0.z, y0.w, e0.w);
            *p2 = make_uint4(y1.x, e1.x, y1.y, e1.y); *p3 = make_uint4(y1.z, e1.z, y1.w, e1.w);
        }
        asm volatile("fence.proxy.async.shared::cta;" ::: "memory");
        bar_arrive(7, NT);
    }
    __syncwarp();
    TSTAMP(2);

    if (w < CW) {
        mbar_wait(mbarK, 0);
        TSTAMP(3);
        uint4 v[2] = {lds128(ka[0]), lds128(ka[1])};
        if ((int)((v[0].y ^ tag) | (v[0].w ^ tag) | (v[1].y ^ tag) | (v[1].w ^ tag)) < 0) {
#pragma unroll
            for (int j = 0; j < 2; j++) {
                int spins = 0;
#pragma unroll 1
                while ((int)((v[j].y ^ tag) | (v[j].w ^ tag)) < 0) {
                    asm volatile("{.reg .b64 lo, hi; ld.relaxed.gpu.global.v2.b64 {lo, hi}, [%4]; mov.b64 {%0,%1}, lo; mov.b64 {%2,%3}, hi;}"
                                 : "=r"(v[j].x), "=r"(v[j].y), "=r"(v[j].z), "=r"(v[j].w) : "l"((const unsigned char*)(gs->keys + b * NPIECE) + (ka[j] - sb - SM_KEYS)) : "memory");
                    if (++spins > (1 << 20)) { setflag(); break; }
                }
            }
        }
#pragma unroll
        for (int j = 0; j < 2; j++) {
            const uint32_t hc = ((v[j].y >> 28) & 7) | ((v[j].w >> 25) & 0x38);
            if (j == 1 && nk[j] == -42) {
                sts32(kc[j], hc | ((v[j].z >> 20) << 8));
                if (hc > CELL - 1) setflag();
                v[j].w |= ((80 * KN) >> 12) << 20;
            }
            nk[j] += hc;
            if (nk[j] > 0) {
                key[j][0] = v[j].x & 0xFFFFF; key[j][1] = v[j].y & 0xFFFFF; key[j][2] = v[j].z & 0xFFFFF; key[j][3] = v[j].w & 0xFFFFF;
                key[j][4] = (v[j].x >> 20) | ((v[j].y >> 8) & 0xFF000); key[j][5] = (v[j].z >> 20) | ((v[j].w >> 8) & 0xFF000);
#pragma unroll
                for (int u = 0; u < 6; u++) {
                    ha[j][u] = __umulhi(key[j][u], 0xFFFFFFFFu / KB + 1);
                    asm volatile("{.reg .u32 a, n; mad.lo.u32 a, %1, 4, %2; atom.shared.add.u32 %0, [a+%3], 1;\n"
                                 "shr.u32 n, %1, 5; mad.lo.u32 a, n, 4, %2; red.shared.add.u32 [a+%4], 128;}"
                                 : "=r"(rk[j][u]) : "r"(ha[j][u]), "r"(sb), "n"(SM_HIST), "n"(SM_MISC + 136 * 4) : "memory");
                }
            }
        }
        bar_sync(9, NT - 32);
        TSTAMP(20);
        const int n = tid >> 3, sub = tid & 7;
        const uint32_t me = deg[n];
        uint32_t r = 0, r2 = 0;
#pragma unroll
        for (int k = 0; k < 5; k++) { const uint2 dd = *(const uint2*)(deg + sub * 10 + 2 * k); r += (me - dd.x) >> 31; r2 += (me - dd.y) >> 31; }
        r += r2;
#pragma unroll
        for (int j = 0; j < 2; j++) kidx[j] += (lds32(kc[j]) & 0x700) << 9;
        r += __shfl_xor_sync(0xffffffff, r, 1); r += __shfl_xor_sync(0xffffffff, r, 2); r += __shfl_xor_sync(0xffffffff, r, 4);
        if (sub == 0) order[r] = n;
    }
    bar_sync(1, NT);
    TSTAMP(22);
    uint32_t len2;
    {
        const uint2 na = *(const uint2*)(order + 2 * w);
        uint2 nb = *(const uint2*)(order + 78 - 2 * w);
        const uint32_t hl = sb + SM_HIST + lane * 4;
        const uint32_t ha0 = lds32(hl + na.x * 128), ha1 = lds32(hl + na.y * 128), hb0 = lds32(hl + nb.y * 128), hb1 = lds32(hl + nb.x * 128);
        if (deg[na.x] >= (4 * CAP + 1) * 128) setflag();
        const uint32_t ca = ha0 + (ha1 << 16), c4 = ca + (hb0 << 8) + (hb1 << 24);
        uint32_t inc = c4;
#pragma unroll
        for (int o = 1; o < 32; o <<= 1)
            asm volatile("{.reg .pred p; .reg .u32 u; shfl.sync.up.b32 u|p, %0, %1, 0, 0xffffffff; @p add.u32 %0, %0, u;}" : "+r"(inc) : "r"(o));
        const int su = __reduce_add_sync(0xffffffff, (int)(ha0 - ha1) * (2 * lane - 31)), sv = __reduce_add_sync(0xffffffff, (int)(hb0 - hb1) * (2 * lane - 31));
        const bool swp = (su ^ sv) >= 0;
        if (swp) { nb = make_uint2(nb.y, nb.x); *(uint2*)(order + 78 - 2 * w) = nb; }
        const uint32_t sel = swp ? 0x4143 : 0x4341, ex = inc - c4;
        const uint32_t ea = (ex & 0x00FF00FF) + __byte_perm(ex, 0, sel), eb = ea + ca, base = sb + SM_LIST + w * 2048;
        uint2* pos = (uint2*)(smem + SM_POS) + lane;
        pos[na.x * 32] = make_uint2(base + (ea & 0xFFFF) * 8, na.x * (0u - 4 * KN));
        pos[nb.y * 32] = make_uint2(base + (eb & 0xFFFF) * 8, nb.y * (0u - 4 * KN) + 0x80000000u);
        pos[na.y * 32] = make_uint2(base + 4 + (ea >> 16) * 8, na.y * (0u - 4 * KN));
        pos[nb.x * 32] = make_uint2(base + 4 + (eb >> 16) * 8, nb.x * (0u - 4 * KN) + 0x80000000u);
        len2 = __shfl_sync(0xffffffff, (inc & 0x00FF00FF) + __byte_perm(inc, 0, sel), 31);
        if (max(len2 & 0xFFFF, len2 >> 16) > 4 * CAP) setflag();
    }
    uint32_t ci = cnt[min(w + NW * lane, NB)];
    ci = (((ci & 0xFF) + ((ci >> 8) & 7)) << 24) + min(w + NW * lane, NB) * (RCH / 8) + (ci >> 11);
    if (w == CW) {
        bar_arrive(9, NT);
        if (tid == NT - 1) {
            uint32_t v1, g0; int spins = 0;
            do {
                asm volatile("ld.relaxed.gpu.global.u32 %1, [%2+8]; ld.acquire.gpu.global.u32 %0, [%2+4];" : "=r"(v1), "=r"(g0) : "l"(gs->bar) : "memory");
            } while ((v1 >= NB) == par && ++spins < (1 << 22));
            if ((v1 >= NB) == par) *flag = 1;
            if (g0 - flag[1] < 30000) flag[1] = g0;
            TSTAMPC(17);
        }
        __syncwarp();
    } else {
        bar_sync(9, NT);
        TSTAMP(21);
        const uint32_t over = lds32(flg);
#pragma unroll
        for (int j = 0; j < 2; j++) {
            if (nk[j] > 0) {
                uint2 h[6];
#pragma unroll
                for (int u = 0; u < 6; u++) h[u] = lds64(sb + SM_POS + ha[j][u] * 8);
                if (over) nk[j] = 0;
#pragma unroll
                for (int u = 0; u < 6; u++)
                    asm volatile("{.reg .pred p; setp.gt.s32 p, %2, %3; @p st.shared.u32 [%0], %1;}"
                                 :: "r"(h[u].x + rk[j][u] * 8), "r"(key[j][u] * 4 + h[u].y + (kidx[j] + (u << 17))), "r"(nk[j]), "r"(u) : "memory");
            }
        }
    }
    bar_sync(1, NT);
    TSTAMP(4);
    if (*flag) {
        slow_path(smem, n0, nn, (const uint16_t*)x, (const int*)src4, (const int*)dst4, (const uint16_t*)Y, (const uint16_t*)ef, w_rad, cg,
                  (const uint16_t*)w_mix, (__nv_bfloat16*)out);
        return;
    }
    {
        const uint4* gp = gs->recs + lane;
        asm volatile("" : "+l"(gp));
        const uint32_t sp = sb + SM_RECS + (w * CELL + lane) * 16, lc = (lane << 24) | 0xFFFFFF;
#pragma unroll
        for (int j = 0; j < 7; j++)
            asm volatile("{.reg .pred p; .reg .u32 l; .reg .u64 a; setp.lt.u32 p, %2, %3; and.b32 l, %3, 0xFFFF; mad.wide.u32 a, l, 128, %1;\n"
                         "@p cp.async.cg.shared.global [%0], [a], 16;}"
                         :: "r"(sp + j * (NW * CELL * 16)), "l"(gp), "r"(lc), "r"(__shfl_sync(0xffffffff, ci, j)) : "memory");
        for (uint32_t m = __ballot_sync(0xffffffff, ci >= (33u << 24)); m; m &= m - 1) {
            const int j = __ffs(m) - 1;
            const uint32_t cj = __shfl_sync(0xffffffff, ci, j);
            if (lane + 32 < (cj >> 24))
                asm volatile("cp.async.cg.shared.global [%0], [%1], 16;" :: "r"(sp + j * (NW * CELL * 16) + 512), "l"(gp + (size_t)(cj & 0xFFFF) * 8 + 32) : "memory");
        }
        asm volatile("cp.async.commit_group;" ::: "memory");
    }
    const int S = __shfl_sync(0xffffffff, max((int)(max(len2 & 0xFFFF, len2 >> 16) + 3) >> 2, DS + 1), 0);
    const int mylen = (lane & 1) ? len2 >> 16 : len2 & 0xFFFF;
    constexpr int NRAW = (CAP + 3) / 4;
    uint32_t bits0 = 0, raw[NRAW];
    unsigned char* meta = smem + SM_META + w * (CAP * STEPB);
    const int la = sb + SM_LIST + w * 2048 + lane * 4, llast = la - (lane & ~1) * 4 + (mylen - 1) * 8;
#pragma unroll
    for (int k = 0; k < NRAW; k++) raw[k] = lds32(min(la + k * 128, llast));
    const uint32_t sv0 = min(raw[0] & 0xFFFC, 4 * (NN - 1));
    const unsigned char* pbase = x + c * 16;
    asm volatile("" : "+l"(pbase));
    auto cpa2 = [&](uint32_t dstp, uint32_t sv) {
        asm volatile("cp.async.cg.shared.global [%0], [%1], 16; cp.async.cg.shared.global [%0+1024], [%1+128], 16;"
                     :: "r"(dstp), "l"(pbase + (size_t)sv * 256) : "memory");
    };
    auto cpa2p = [&](uint32_t dstp, uint32_t sv) {
        asm volatile("{.reg .pred p; setp.ge.s32 p, %2, 0; @p cp.async.cg.shared.global [%0], [%1], 16; @p cp.async.cg.shared.global [%0+1024], [%1+128], 16;}"
                     :: "r"(dstp), "l"(pbase + (size_t)sv * 256), "r"(sv) : "memory");
    };
    auto wait_until = [&](uint32_t tt) {
        asm volatile("{.reg .pred p; .reg .u32 d;\n"
                     "PACE_LOOP: mov.u32 d, %%globaltimer_lo; sub.u32 d, %0, d; setp.lt.u32 p, d, 32768; @p nanosleep.u32 %1; @p bra.uni PACE_LOOP;}"
                     :: "r"(tt), "n"(PSLEEP) : "memory");
    };
    const uint32_t tfill = flag[1] - FOFF;
    auto fill = [&](int i) {
        wait_until(tfill + i * FDT);
        cpa2(wdst + i * SLOTB, __shfl_sync(0xffffffff, sv0, 8 * i + 2 * q)); cpa2(wdst + i * SLOTB + 512, __shfl_sync(0xffffffff, sv0, 8 * i + 2 * q + 1));
        asm volatile("cp.async.commit_group;" ::: "memory");
    };
    fill(0);
    TSTAMP(5);
    auto relay = [&]() {
        uint32_t g0, g1, b0, b1;
        asm volatile("ld.volatile.shared.v2.u32 {%0,%1}, [%4+40]; ld.volatile.shared.v2.u32 {%2,%3}, [%4+16];"
                     : "=r"(g0), "=r"(g1), "=r"(b0), "=r"(b1) : "r"(flg) : "memory");
        const unsigned long long dg = (((unsigned long long)g1 << 32) | g0) - (((unsigned long long)b1 << 32) | b0);
        asm volatile("{.reg .pred p, q; setp.eq.u32 p, %1, 0; setp.lt.u64 q, %2, 30000; @q st.shared.u32 [%3+4], %4;\n"
                     "@p cp.async.cg.shared.global [%3+32], [%0], 16;}"
                     :: "l"(gs->bar), "r"(lane), "l"(dg), "r"(flg), "r"(g0) : "memory");
    };
    auto report = [&](uint32_t cand) {
        uint32_t b0, b1;
        asm volatile("ld.volatile.shared.v2.u32 {%0,%1}, [%2+16];" : "=r"(b0), "=r"(b1) : "r"(flg) : "memory");
        asm volatile("{.reg .pred p; setp.eq.u32 p, %2, 0; @p red.max.relaxed.gpu.global.u64 [%0], %1;}"
                     :: "l"(&gs->t0), "l"((((unsigned long long)b1 << 32) | b0) + (cand - b0)), "r"(lane) : "memory");
    };
    uint32_t ra[NRAW];
#pragma unroll
    for (int k = NRAW - 1; k >= 0; k--) {
        const uint32_t m = (__ballot_sync(0xffffffff, (int)raw[k] < 0) >> g) & 0x01010101u;
        bits0 = __funnelshift_l(m * 0x10204080u, bits0, 4);
        const bool pad = la + k * 128 > llast;
        ra[k] = pad ? NB * CELL * 16 : (raw[k] >> 13) & 0x1FFF0;
        raw[k] = (raw[k] & 0xFFFF) | (pad ? F_PAD : 0);
    }
    if (t < 2) bits0 = ~bits0;
    asm volatile("" : "+r"(bits0), "+r"(ra[0]), "+r"(ra[1]), "+r"(ra[2]), "+r"(ra[3]), "+r"(ra[4]), "+r"(raw[0]), "+r"(raw[1]), "+r"(raw[2]), "+r"(raw[3]), "+r"(raw[4]));
    fill(1);
    asm volatile("cp.async.wait_group 2;" ::: "memory");
    bar_sync(1, NT);
    TSTAMP(19);
    if (w == CW) {
        uint32_t tn; asm volatile("mov.u32 %0, %%globaltimer_lo;" : "=r"(tn));
        if ((int)(tn + RDY - flag[1]) > 0) { report(tn + RDY); flag[1] = tn + RDY; }
    }
    {
        uint4 rv[NRAW];
#pragma unroll
        for (int k = 0; k < NRAW - 1; k++) rv[k] = lds128(ra[k] + (sb + SM_RECS));
        if ((NRAW - 1) * 4 < S) rv[NRAW - 1] = lds128(ra[NRAW - 1] + (sb + SM_RECS));
        fill(2);
        bar_sync(1, NT);
        TSTAMP(12);
        unsigned char* mr = meta + (q - 1) * STEPB + c * 16;
        unsigned char* ms = meta + (q - DS - 1) * STEPB + 128 + c * 4;
#pragma unroll
        for (int k = 0; k < NRAW; k++) {
            if (k == 0) {
                *(uint4*)(mr + (q == 0 ? S * STEPB : 0)) = rv[k];
                *(uint32_t*)(ms + S * STEPB) = raw[0] + F_WRAP;
            } else if (k * 4 + q < S) {
                *(uint4*)(mr + k * 4 * STEPB) = rv[k];
                *(uint32_t*)(ms + k * 4 * STEPB + (k == 1 && q == 0 ? S * STEPB : 0)) = raw[k];
            }
        }
    }
    __syncwarp();
    const uint32_t tphase = PACE / 4;
    uint32_t dreg;
    {
        const int ls = lane >= S ? min(lane - S, S - 1) : lane, st = ls == 0 ? S - 1 : ls - 1;
        const uint4 u0 = *(const uint4*)(meta + st * STEPB + 128), u1 = *(const uint4*)(meta + st * STEPB + 144);
        int pos = (u0.x + u0.y + u0.z + u0.w + u1.x + u1.y + u1.z + u1.w) << 1 >> 6;
        pos += ((u0.x & F_WRAP) ? NN : 0) + (lane >= S ? NN : 0) - NN * (2 * DS + 1) / 32;
        dreg = pos * (int)tphase / NN;
    }
    fill(3);
    TSTAMP(6);

    uint32_t* stash = (uint32_t*)(gs->stash + (b * NW + w) * 256) + lane;
    asm volatile("" : "+l"(stash));
    float acc[4][4];
#pragma unroll
    for (int i = 0; i < 16; i++) acc[i / 4][i % 4] = 0.f;
    uint4 az = *(const uint4*)(smem + SM_AZ + lane * 16);
    uint32_t dcur = dreg, dl = 0, now = flag[1], tcur = 0;
    uint32_t mp = 0, smask = 1, didx = 2;
    uint32_t mend = S * STEPB;
    uint2 r = lds64(mend - STEPB + recl), s0 = lds64(mend - STEPB + srcl);
    auto step = [&](const uint32_t off, const int mode, const bool pc = true) {
        if (mode == 0 && pc) { unsigned long long n64; asm volatile("mov.u64 %0, %%globaltimer;" : "=l"(n64)); now = (uint32_t)n64; }
        const uint2 rc = r, sc = s0;
        if (mode != 4) r = lds64(mp + recl);
        if (mode == 0) s0 = lds64(mp + srcl);
        asm volatile("cp.async.wait_group %0;" :: "n"(DS - 1) : "memory");
        const uint4 xa = lds128(rsrc + off), xb = lds128(rsrc + off + 512), xc = lds128(rsrc + off + 1024), xd = lds128(rsrc + off + 1536);
        if (mode == 0) {
            if (pc) { dl = __shfl_sync(0xffffffff, dcur, didx); didx += 2; }
            cpa2p(wdst + off, sc.x); cpa2p(wdst + off + 512, sc.y);
        }
        if (mode == 1 && w < 16) {
#pragma unroll
            for (int j = 0; j < 4; j++) {
                const int kk = 4 * j + q, ch = 16 * (w & 7) + 2 * (kk & 7) + (kk >> 3);
                asm volatile("cp.async.cg.shared.global [%0], [%1], 16;" :: "r"(ring0 + kk * 128 + ((c ^ (kk & 7)) << 4)), "l"(w_mix + ch * 16 + (w >> 3) * 8 + c) : "memory");
            }
            asm volatile("cp.async.mbarrier.arrive.noinc.shared.b64 [%0];" :: "r"(mbarW) : "memory");
        }
        if (mode == 2 || mode == 3) {
#pragma unroll
            for (int j = 0; j < 4; j += mode - 1)
                asm volatile("cp.async.cg.shared.global [%0], [%1], 16;" :: "r"(ring0 + off + j * 512 + lane * 16), "l"(stash + (mode - 2) * 512 + j * 128 + lane * 3) : "memory");
        }
        if (mode < 4) asm volatile("cp.async.commit_group;" ::: "memory");
        float z[4], y[4], t1[4], t2[4];
        mma1688z(z, az.x, az.y, rc.y);
        mma1688z(y, az.z, az.w, rc.y);
        uint32_t bt;
        asm("{.reg .pred p; .reg .b32 m; and.b32 m, %2, %3; setp.ne.u32 p, m, 0; selp.b32 %0, %1, 0, p;}" : "=r"(bt) : "r"(rc.x), "r"(bits0), "r"(smask));
        mma1688z(t1, at[0], at[1], bt);
        mma1688z(t2, at[2], at[3], bt);
        const uint32_t T0 = pack2(t1[0], t1[2]), T1 = pack2(t2[0], t2[2]), T2 = pack2(t1[1], t1[3]), T3 = pack2(t2[1], t2[3]);
        uint32_t R[8];
#pragma unroll
        for (int i = 0; i < 4; i++) { R[i] = __float_as_uint(silu_h(z[i])); R[4 + i] = __float_as_uint(silu_h(y[i])); }
        mma16816(acc[0], mul_hi(xa.x, R[0]), mul_hi(xa.z, R[2]), mul_hi(xa.y, R[0]), mul_hi(xa.w, R[2]), T0, T1);
        mma16816(acc[1], mul_hi(xb.x, R[1]), mul_hi(xb.z, R[3]), mul_hi(xb.y, R[1]), mul_hi(xb.w, R[3]), T2, T3);
        mma16816(acc[2], mul_hi(xc.x, R[4]), mul_hi(xc.z, R[6]), mul_hi(xc.y, R[4]), mul_hi(xc.w, R[6]), T0, T1);
        mma16816(acc[3], mul_hi(xd.x, R[5]), mul_hi(xd.z, R[7]), mul_hi(xd.y, R[5]), mul_hi(xd.w, R[7]), T2, T3);
        mp += STEPB; smask <<= 1;
    };
    auto putacc = [&](uint32_t* p) {
        p[0] = pack2(acc[0][0], acc[0][1]); p[32] = pack2(acc[0][2], acc[0][3]); p[64] = pack2(acc[2][0], acc[2][1]); p[96] = pack2(acc[2][2], acc[2][3]);
        p[256] = pack2(acc[1][0], acc[1][1]); p[288] = pack2(acc[1][2], acc[1][3]); p[320] = pack2(acc[3][0], acc[3][1]); p[352] = pack2(acc[3][2], acc[3][3]);
    };
    int ph = 0;
    auto phase_end = [&](const int k) {
        az = lds128(sb + SM_AZ + (ph + 1) * 512 + lane * 16);
        putacc(stash + ph * ph * 128);
#pragma unroll
        for (int i = 0; i < 16; i++) acc[i / 4][i % 4] = 0.f;
        pbase += 256; mp = 0; smask = 1; ph++;
        dcur += tphase; didx = 1 + (k & 1);
        if (ph == 3) {
            mend -= DS * STEPB;
            dcur += (int)(dcur - __shfl_sync(0xffffffff, dcur, 0)) * (((w >> 2) - 2) * FAN) >> 8;
        }
        WSTAMP(ph - 1);
    };
    uint32_t t0 = now;
    if (w == PW) {
        asm volatile("mov.u32 %0, %%globaltimer_lo;" : "=r"(now));
        now += PTOL - PTOL0;
    }
    const uint32_t bias = w == RW ? 1u << 20 : 0;
    if (w == RW) relay();
    dcur += bias;
    auto body = [&](const int k) -> bool {
        if (k == 2) asm volatile("ld.volatile.shared.u32 %0, [%1+4];" : "=r"(t0) : "r"(flg));
        const bool pc = k & 1;
        step(k * SLOTB, 0, pc);
        if (!pc) {
            if (mp == mend) phase_end(k);
        } else if (mp == mend || now < dl) {
            if (mp == mend) {
                if (k == 3 && ph == 3) return true;
                phase_end(k);
            }
            if (w == RW) {
                dl -= 1u << 20; relay();
                {
                    const int row = (mp / (2 * STEPB)) * (16 * XPF) + (lane >> 1);
#pragma unroll
                    for (int u = 0; u < XPF; u++)
                        asm volatile("{.reg .pred p; setp.lt.s32 p, %1, %2; @p prefetch.global.L2 [%0];}"
                                     :: "l"(x + (size_t)(n0 + row + 16 * u) * 1024 + (ph + 1) * 256 + (lane & 1) * 128), "r"(row + 16 * u), "r"(ph < 3 ? nn : 0));
                }
            }
            wait_until(dl);
        }
        return false;
    };
    if (w >= 4 && w < 9 && (w - 4) * 16 + (lane >> 1) < nn && b >= XPF0)
        asm volatile("prefetch.global.L2 [%0];" :: "l"(x + (size_t)(n0 + (w - 4) * 16 + (lane >> 1)) * 1024 + (lane & 1) * 128));
    {
        const uint32_t d0 = __shfl_sync(0xffffffff, dreg, 0);
        if (w == RW) {
            uint32_t g0, tn; int spins = 0;
            do {
                asm volatile("ld.relaxed.gpu.global.u32 %0, [%2]; mov.u32 %1, %%globaltimer_lo;" : "=r"(g0), "=r"(tn) : "l"(&gs->t0) : "memory");
                if (g0 - t0 < 30000) { t0 = g0; flag[1] = g0; }
            } while (__shfl_sync(0xffffffff, t0 - tn, 0) < 32768 && ++spins < 64);
        }
        asm volatile("{.reg .pred p; .reg .u32 d;\n"
                     "PACE_LOOP: ld.volatile.shared.u32 %0, [%2+4]; mov.u32 d, %%globaltimer_lo; sub.u32 d, %1, d; add.u32 d, d, %0;\n"
                     "setp.lt.u32 p, d, 32768; @p nanosleep.u32 32; @p bra.uni PACE_LOOP;}"
                     : "=&r"(t0) : "r"(d0), "r"(flg) : "memory");
    }
    while (true) {
        if (w == PW) {
            const uint32_t cand = now - dl + tcur - PTOL;
            if ((int)(cand - t0) > 0) report(cand);
        }
        dcur += t0 - tcur; tcur = t0;
        body(0); body(1); body(2);
        if (body(3)) break;
    }
    __syncwarp();
    step(0, 1);
    { uint32_t tn; asm volatile("mov.u32 %0, %%globaltimer_lo;" : "=r"(tn)); wait_until(tn + (w >> 2) * TDEL); }
    step(SLOTB, 2); step(2 * SLOTB, 3); step(3 * SLOTB, 4);
    WSTAMP(3); ESTAMP(0);

    {
        putacc((uint32_t*)(smem + SM_RING + 2 * SLOTB + w * 2048 + 512) + lane);
        const int wg = w >> 2, w4 = w & 3;
        int nd[8];
#pragma unroll
        for (int j = 0; j < 8; j++) { const int l = wg * 8 + j; nd[j] = order[(t >> 1) ? 79 - l : l]; asm volatile("" : "+r"(nd[j])); }
        const bool odd = t & 1;
        uint2* ob = (uint2*)out + (size_t)n0 * 128 + w4 * 16 + g + (odd ? 8 : 0);
        asm volatile("cp.async.wait_all;" ::: "memory");
        mbar_wait(mbarW, 0);
        asm volatile("fence.proxy.async.shared::cta;" ::: "memory");
        ESTAMP(1);
        bar_sync(2 + wg, 128);
        uint32_t ticket = 0;
        if ((tid & 127) == 0) {
            asm volatile("atom.shared.add.u32 %0, [%1+48], 1;" : "=r"(ticket) : "r"(flg) : "memory");
            int spins = 0;
            while (flag[13] < ticket && ++spins < (1 << 16)) __nanosleep(40);
        }
        bar_sync(2 + wg, 128);
        const uint64_t descA0 = (uint64_t)(((sb + SM_RING) & 0x3FFFF) >> 4) | ((uint64_t)1 << 16) | ((uint64_t)(1024 >> 4) << 32) | ((uint64_t)1 << 62);
        const uint64_t descB0 = (uint64_t)(((sb + SM_RING + SLOTB + wg * 8192) & 0x3FFFF) >> 4) | ((uint64_t)(128 >> 4) << 16) | ((uint64_t)(1024 >> 4) << 32);
        float d[2][32];
        asm volatile("wgmma.fence.sync.aligned;" ::: "memory");
        ESTAMP(2);
#pragma unroll
        for (int mt = 0; mt < 2; mt++) {
#pragma unroll
            for (int ks = 0; ks < 8; ks++) {
                if (mt * 8 + ks == RELK)
                    asm volatile("{.reg .pred p; setp.eq.u32 p, %1, 0; @p st.volatile.shared.u32 [%0+52], %2;}" :: "r"(flg), "r"(tid & 127), "r"(ticket + 1) : "memory");
                const uint64_t da = descA0 + (uint64_t)((ks * 2048 + mt * 16384) >> 4), db = descB0 + (uint64_t)(((ks & 3) * 256 + (ks >> 2) * SLOTB) >> 4);
                asm volatile("{.reg .pred p; setp.ne.b32 p, %34, 0;\n"
                    "wgmma.mma_async.sync.aligned.m64n64k16.f32.bf16.bf16 "
                    "{%0,%1,%2,%3,%4,%5,%6,%7,%8,%9,%10,%11,%12,%13,%14,%15,%16,%17,%18,%19,%20,%21,%22,%23,%24,%25,%26,%27,%28,%29,%30,%31}, %32, %33, p, 1, 1, 1, 1;}"
                    : "+f"(d[mt][0]), "+f"(d[mt][1]), "+f"(d[mt][2]), "+f"(d[mt][3]), "+f"(d[mt][4]), "+f"(d[mt][5]), "+f"(d[mt][6]), "+f"(d[mt][7]),
                      "+f"(d[mt][8]), "+f"(d[mt][9]), "+f"(d[mt][10]), "+f"(d[mt][11]), "+f"(d[mt][12]), "+f"(d[mt][13]), "+f"(d[mt][14]), "+f"(d[mt][15]),
                      "+f"(d[mt][16]), "+f"(d[mt][17]), "+f"(d[mt][18]), "+f"(d[mt][19]), "+f"(d[mt][20]), "+f"(d[mt][21]), "+f"(d[mt][22]), "+f"(d[mt][23]),
                      "+f"(d[mt][24]), "+f"(d[mt][25]), "+f"(d[mt][26]), "+f"(d[mt][27]), "+f"(d[mt][28]), "+f"(d[mt][29]), "+f"(d[mt][30]), "+f"(d[mt][31])
                    : "l"(da), "l"(db), "r"(ks));
            }
            asm volatile("wgmma.commit_group.sync.aligned;" ::: "memory");
        }
#pragma unroll
        for (int mt = 0; mt < 2; mt++) {
            if (mt == 0) asm volatile("wgmma.wait_group.sync.aligned 1;" ::: "memory");
            else asm volatile("wgmma.wait_group.sync.aligned 0;" ::: "memory");
            ESTAMP(3 + mt);
#pragma unroll
            for (int i = 0; i < 32; i++) asm volatile("" : "+f"(d[mt][i]) :: "memory");
#pragma unroll
            for (int j = 0; j < 8; j++) {
                const uint32_t v0 = pack2(d[mt][4 * j], d[mt][4 * j + 1]), v1 = pack2(d[mt][4 * j + 2], d[mt][4 * j + 3]);
                const uint32_t rv = __shfl_xor_sync(0xffffffff, odd ? v0 : v1, 1);
                if (nd[j] < nn) ob[nd[j] * 128 + mt * 64] = odd ? make_uint2(rv, v1) : make_uint2(v0, rv);
            }
        }
    }
    TSTAMP(8); ESTAMP(5);
}

__global__ void __launch_bounds__(NT, 1)
tfn_fallback(const uint16_t* x, const int* src, const int* dst, const uint16_t* Y, const uint16_t* ef, const uint16_t* w_rad,
             const uint16_t* cg, const uint16_t* w_mix, __nv_bfloat16* out) {
    extern __shared__ __align__(1024) unsigned char smem[];
    const int n0 = blockIdx.x * NPB;
    slow_path(smem, n0, min(NPB, NN - n0), x, src, dst, Y, ef, w_rad, cg, w_mix, out);
}

}

extern "C" void kernel_launch(void* const* d_in, const int* in_sizes, int n_in, void* d_out, int out_size) {
    (void)in_sizes; (void)n_in; (void)out_size;
    cudaFuncSetAttribute(tfn_kernel, cudaFuncAttributeMaxDynamicSharedMemorySize, SM_TOTAL);
    int dev = 0, sms = 0;
    cudaGetDevice(&dev);
    cudaDeviceGetAttribute(&sms, cudaDevAttrMultiProcessorCount, dev);
    if (sms < NB) {
        cudaFuncSetAttribute(tfn_fallback, cudaFuncAttributeMaxDynamicSharedMemorySize, NPB * 2048);
        tfn_fallback<<<NB, NT, NPB * 2048, cudaStreamPerThread>>>((const uint16_t*)d_in[0], (const int*)d_in[1], (const int*)d_in[2], (const uint16_t*)d_in[3],
            (const uint16_t*)d_in[4], (const uint16_t*)d_in[5], (const uint16_t*)d_in[6], (const uint16_t*)d_in[7], (__nv_bfloat16*)d_out);
        return;
    }
    Scratch* gs = nullptr;
    cudaGetSymbolAddress((void**)&gs, g_scratch);
    cudaLaunchConfig_t cfg = {};
    cfg.gridDim = dim3(NB); cfg.blockDim = dim3(NT); cfg.dynamicSmemBytes = SM_TOTAL; cfg.stream = cudaStreamPerThread;
    cudaLaunchAttribute at[1];
    at[0].id = cudaLaunchAttributeCooperative; at[0].val.cooperative = 1;
    cfg.attrs = at; cfg.numAttrs = 1;
    cudaLaunchKernelEx(&cfg, tfn_kernel, (const unsigned char*)d_in[0], (const int4*)d_in[1], (const int4*)d_in[2],
                       (const uint4*)d_in[3], (const uint4*)d_in[4], (const uint16_t*)d_in[5], (const uint16_t*)d_in[6],
                       (const uint4*)d_in[7], (uint32_t*)d_out, gs);
}
```

```cpp
#include <cuda_runtime.h>
#include <cuda_bf16.h>
#include <stdint.h>

namespace {

constexpr int NN = 10000;
constexpr int NE = 320000;
constexpr int NB = 132;
constexpr int NW = 20;
constexpr int NT = NW * 32;
constexpr int CW = NW - 1;
constexpr int PW = 10;
constexpr int RW = 1;
constexpr int NPB = 76;
constexpr int CELL = 48;
constexpr int RCH = 2880;
constexpr int CAP = 19;
constexpr int DS = 4;
constexpr int STEPB = 160;
constexpr int NE4 = NE / 4;
constexpr int NPIECE = NB * 8;
constexpr int KB = 320, KN = 32 * KB;
constexpr uint32_t F_PAD = 0x80000000u;
constexpr uint32_t F_WRAP = 1;

constexpr int SLOTB = NW * 2048;
constexpr int SM_RING = 0;
constexpr int SM_META = SM_RING + DS * SLOTB;
constexpr int SM_AZ = SM_META + NW * CAP * STEPB;
constexpr int SM_MISC = SM_AZ + 2048;
constexpr int SM_TOTAL = SM_MISC + 2048;
constexpr int SM_STAGE = SM_RING;
constexpr int SM_HIST = SM_RING + 25600;
constexpr int SM_POS = SM_RING;
constexpr int SM_SMALL = SM_HIST + 13056;
constexpr int SM_LIST = SM_RING + SLOTB;
constexpr int SM_ROUT = SM_RING + 2 * SLOTB;
constexpr int SM_RECS = SM_RING + 3 * SLOTB;
constexpr int SM_RAWY = SM_META;
constexpr int SM_RAWE = SM_RAWY + 608 * 32;
constexpr int SM_KEYS = SM_RAWE + 608 * 32;
static_assert(SM_TOTAL <= 232448 && SM_KEYS + NPIECE * 16 <= SM_AZ, "smem");
static_assert(SM_RECS + NB * CELL * 16 + 16 <= SM_AZ && SM_KEYS + NPIECE * 16 <= SM_RECS + NB * CELL * 16 && SM_SMALL + 1152 <= SLOTB && DS == 4, "smem");

struct __align__(1024) Scratch {
    uint4 keys[NB * NPIECE];
    uint4 recs[NB * RCH];
    uint4 stash[NB * NW * 256];
    unsigned bar[2];
    unsigned long long t0;
};
__device__ Scratch g_scratch;
#define TSTAMP(i)
#define TSTAMPC(i)
#define WSTAMP(i)
#define ESTAMP(i)

__device__ __forceinline__ void mma16816(float* d, uint32_t a0, uint32_t a1, uint32_t a2, uint32_t a3, uint32_t b0, uint32_t b1) {
    asm volatile("mma.sync.aligned.m16n8k16.row.col.f32.bf16.bf16.f32 {%0,%1,%2,%3}, {%4,%5,%6,%7}, {%8,%9}, {%0,%1,%2,%3};"
        : "+f"(d[0]), "+f"(d[1]), "+f"(d[2]), "+f"(d[3]) : "r"(a0), "r"(a1), "r"(a2), "r"(a3), "r"(b0), "r"(b1));
}
__device__ __forceinline__ void mma1688z(float* d, uint32_t a0, uint32_t a1, uint32_t b0) {
    asm("mma.sync.aligned.m16n8k8.row.col.f32.bf16.bf16.f32 {%0,%1,%2,%3}, {%4,%5}, {%6}, {%7,%7,%7,%7};"
        : "=f"(d[0]), "=f"(d[1]), "=f"(d[2]), "=f"(d[3]) : "r"(a0), "r"(a1), "r"(b0), "f"(0.f));
}
__device__ __forceinline__ void mma1688zv(float* d, uint32_t a0, uint32_t a1, uint32_t b0) {
    asm volatile("mma.sync.aligned.m16n8k8.row.col.f32.bf16.bf16.f32 {%0,%1,%2,%3}, {%4,%5}, {%6}, {%7,%7,%7,%7};"
        : "=f"(d[0]), "=f"(d[1]), "=f"(d[2]), "=f"(d[3]) : "r"(a0), "r"(a1), "r"(b0), "f"(0.f));
}
__device__ __forceinline__ uint32_t pack2(float lo, float hi) {
    uint32_t r; asm("cvt.rn.bf16x2.f32 %0, %1, %2;" : "=r"(r) : "f"(hi), "f"(lo)); return r;
}
__device__ __forceinline__ float silu_h(float h) {
    float t; asm("tanh.approx.f32 %0, %1;" : "=f"(t) : "f"(h)); return fmaf(h, t, h);
}
__device__ __forceinline__ uint32_t mul_hi(uint32_t v, uint32_t r) {
    __nv_bfloat162 a = *(__nv_bfloat162*)&v, b = *(__nv_bfloat162*)&r; __nv_bfloat162 c = __hmul2(a, __high2bfloat162(b)); return *(uint32_t*)&c;
}
__device__ __forceinline__ int tid_now() { int v; asm volatile("mov.u32 %0, %%tid.x;" : "=r"(v)); return v; }
__device__ __forceinline__ int cta_now() { int v; asm volatile("mov.u32 %0, %%ctaid.x;" : "=r"(v)); return v; }
__device__ __forceinline__ uint32_t lds32(uint32_t a) {
    uint32_t r; asm volatile("ld.shared.u32 %0, [%1];" : "=r"(r) : "r"(a) : "memory"); return r;
}
__device__ __forceinline__ void sts32(uint32_t a, uint32_t v) { asm volatile("st.shared.u32 [%0], %1;" :: "r"(a), "r"(v) : "memory"); }
__device__ __forceinline__ uint2 lds64(uint32_t a) {
    uint2 r; asm volatile("ld.shared.v2.u32 {%0,%1}, [%2];" : "=r"(r.x), "=r"(r.y) : "r"(a)); return r;
}
__device__ __forceinline__ uint4 lds128(uint32_t a) {
    uint4 r; asm volatile("ld.shared.v4.u32 {%0,%1,%2,%3}, [%4];" : "=r"(r.x), "=r"(r.y), "=r"(r.z), "=r"(r.w) : "r"(a) : "memory"); return r;
}
__device__ __forceinline__ void bar_sync(int id, int n) { asm volatile("bar.sync %0, %1;" :: "r"(id), "r"(n) : "memory"); }
__device__ __forceinline__ void bar_arrive(int id, int n) { asm volatile("bar.arrive %0, %1;" :: "r"(id), "r"(n) : "memory"); }
__device__ __forceinline__ void mbar_wait(uint32_t bar, uint32_t ph) {
    uint32_t done; int spins = 0;
    do {
        asm volatile("{.reg .pred p; mbarrier.try_wait.parity.shared.b64 p, [%1], %2; selp.u32 %0,1,0,p;}" : "=r"(done) : "r"(bar), "r"(ph) : "memory");
    } while (!done && ++spins < (1 << 22));
}
__device__ __forceinline__ void gbar_arrive(unsigned* ctr) {
    asm volatile("red.inc.relaxed.gpu.global.u32 [%0], %1;" :: "l"(ctr), "n"(2 * NB - 1) : "memory");
}
__device__ __forceinline__ int chunk_start4(int c) { return (c * NE4) / NB; }
__device__ __forceinline__ float bf2f(uint32_t h) { return __uint_as_float(h << 16); }

__device__ __noinline__ void slow_path(unsigned char* smem, int n0, int nn, const uint16_t* x, const int* src, const int* dst,
                                       const uint16_t* Y, const uint16_t* ef, const uint16_t* w_rad, const uint16_t* cg,
                                       const uint16_t* w_mix, __nv_bfloat16* out) {
    float* agg = (float*)smem;
    const int tid = threadIdx.x, lane = tid & 31, w = tid >> 5;
    bar_sync(1, NT);
    for (int i = tid; i < NPB * 512; i += NT) agg[i] = 0.f;
    bar_sync(1, NT);
    for (int e0 = w * 32; e0 < NE; e0 += NT) {
        int dl = dst[e0 + lane] - n0;
        unsigned m = __ballot_sync(0xffffffff, dl >= 0 && dl < nn);
        while (m) {
            int l = __ffs(m) - 1; m &= m - 1;
            int e = e0 + l, d = __shfl_sync(0xffffffff, dl, l), s = src[e];
            float T[16];
            for (int i = 0; i < 4; i++) for (int o = 0; o < 4; o++) {
                float a = 0.f;
                for (int f = 0; f < 4; f++) a += bf2f(Y[e * 4 + f]) * bf2f(cg[i * 16 + f * 4 + o]);
                T[i * 4 + o] = a;
            }
            for (int k = 0; k < 4; k++) {
                int c = lane + 32 * k;
                float z = 0.f;
                for (int j = 0; j < 4; j++) z += bf2f(ef[e * 4 + j]) * bf2f(w_rad[j * 128 + c]);
                float R = z / (1.f + __expf(-z));
                for (int o = 0; o < 4; o++) {
                    float a = 0.f;
                    for (int i = 0; i < 4; i++) a += bf2f(x[(size_t)s * 512 + c * 4 + i]) * T[i * 4 + o];
                    atomicAdd(&agg[d * 512 + c * 4 + o], R * a);
                }
            }
        }
    }
    bar_sync(1, NT);
    for (int i = tid; i < nn * 512; i += NT) {
        int n = i >> 9, d = (i >> 2) & 127, o = i & 3;
        float a = 0.f;
        for (int c = 0; c < 128; c++) a += agg[n * 512 + c * 4 + o] * bf2f(w_mix[c * 128 + d]);
        out[(size_t)(n0 + n) * 512 + (i & 511)] = __float2bfloat16(a);
    }
}

#define PACE 22600
#define YDELAY 300
#define POFF 3650
#define PSLEEP 64
#define FDT 350
#define FOFF 1500
#define RELK 12
#define FAN 16
#define TDEL 100
#define RDY 600
#define XPF 2
#define XPF0 40
#define PTOL0 300
#define PTOL 1500
__global__ void __launch_bounds__(NT, 1)
tfn_kernel(const unsigned char* __restrict__ x, const int4* __restrict__ src4, const int4* __restrict__ dst4,
           const uint4* __restrict__ Y, const uint4* __restrict__ ef, const uint16_t* __restrict__ w_rad,
           const uint16_t* __restrict__ cg, const uint4* __restrict__ w_mix, uint32_t* __restrict__ out, Scratch* __restrict__ gs) {
    extern __shared__ __align__(1024) unsigned char smem[];
    const uint32_t sb = (uint32_t)__cvta_generic_to_shared(smem);
    const int b = blockIdx.x, tid = threadIdx.x, lane = tid & 31, g = lane >> 2, t = lane & 3;
    const int w = __shfl_sync(0xffffffff, tid >> 5, 0);
    uint32_t* stage = (uint32_t*)(smem + SM_STAGE);
    uint32_t* hist = (uint32_t*)(smem + SM_HIST);
    uint32_t* cnt = (uint32_t*)(smem + SM_MISC);
    uint32_t* deg = cnt + 136;
    uint32_t* order = deg + 104;
    uint32_t* cnt2 = order + 80;
    volatile uint32_t* flag = cnt2 + 136;
    const uint32_t mbarK = sb + SM_MISC + 1920, mbarR = mbarK + 8, mbarW = mbarK + 16;
    const int n0 = b * NPB, nn = min(NPB, NN - n0);
    TSTAMP(0);

    const int c0 = chunk_start4(b), c1 = chunk_start4(b + 1);
    const bool has4 = c0 + tid < c1;
    int4 d4 = make_int4(0, 0, 0, 0), s4 = d4;
    if (has4) { d4 = __ldg(dst4 + c0 + tid); s4 = __ldg(src4 + c0 + tid); }
    unsigned par = 0;
    if (tid == NT - 1) {
        asm volatile("ld.relaxed.gpu.global.u32 %0, [%1];" : "=r"(par) : "l"(gs->bar) : "memory");
        asm volatile("mbarrier.init.shared.b64 [%0], 1;" :: "r"(mbarK));
        asm volatile("mbarrier.init.shared.b64 [%0], 1;" :: "r"(mbarR));
        asm volatile("mbarrier.init.shared.b64 [%0], 512;" :: "r"(mbarW));
        asm volatile("fence.mbarrier_init.release.cluster;" ::: "memory");
        flag[0] = 0; flag[12] = 0; flag[13] = 0; flag[15] = 0;
    }
    if (w == CW) {
        asm volatile("cp.async.cg.shared.global [%0], [%1], 16;" :: "r"(sb + SM_SMALL + lane * 16), "l"(w_rad + lane * 8) : "memory");
        asm volatile("cp.async.cg.shared.global [%0], [%1], 16;" :: "r"(sb + SM_SMALL + 512 + lane * 16), "l"(w_rad + 256 + lane * 8) : "memory");
        if (lane < 8) asm volatile("cp.async.cg.shared.global [%0], [%1], 16;" :: "r"(sb + SM_SMALL + 1024 + lane * 16), "l"(cg + lane * 8) : "memory");
    }
    ((uint4*)hist)[tid] = make_uint4(0, 0, 0, 0);
    {
        const uint32_t dk = (80 + b % 22) * KN + (b & 31) * KB;
#pragma unroll
        for (int j = 0; j < 3; j++) if (tid + j * NT < NB * CELL / 4) ((uint4*)stage)[tid + j * NT] = make_uint4(dk, dk, dk, dk);
    }
    if (tid < 136) cnt[tid] = 0;
    if (tid == 0) { *(uint4*)(smem + SM_MISC + 1824 + 32) = make_uint4(0, 0, 0, 0); *(uint4*)(smem + SM_RECS + NB * CELL * 16) = make_uint4(0, 0, 0, 0); }
    if (tid < 80) { deg[tid] = 127 - tid; order[tid] = tid; }
    __syncthreads();
    TSTAMP(9);
    if (tid == 64) {
        __nanosleep(YDELAY);
        asm volatile("mbarrier.arrive.expect_tx.shared.b64 _, [%0], %1;" :: "r"(mbarR), "r"((c1 - c0) * 64) : "memory");
        asm volatile("cp.async.bulk.shared::cluster.global.mbarrier::complete_tx::bytes [%0], [%1], %2, [%3];"
                     :: "r"(sb + SM_RAWY), "l"(Y + 2 * c0), "r"((c1 - c0) * 32), "r"(mbarR) : "memory");
        asm volatile("cp.async.bulk.shared::cluster.global.mbarrier::complete_tx::bytes [%0], [%1], %2, [%3];"
                     :: "r"(sb + SM_RAWE), "l"(ef + 2 * c0), "r"((c1 - c0) * 32), "r"(mbarR) : "memory");
    }

    uint32_t bin[4] = {0, 0, 0, 0}, slot[4] = {0, 0, 0, 0};
    if (has4) {
        const uint32_t dd[4] = {(uint32_t)d4.x, (uint32_t)d4.y, (uint32_t)d4.z, (uint32_t)d4.w}, ss[4] = {(uint32_t)s4.x, (uint32_t)s4.y, (uint32_t)s4.z, (uint32_t)s4.w};
#pragma unroll
        for (int k = 0; k < 4; k++) { bin[k] = dd[k] / NPB; slot[k] = atomicAdd(&cnt[bin[k]], 1); }
#pragma unroll
        for (int k = 0; k < 4; k++) stage[bin[k] * CELL + min(slot[k], CELL - 1)] = (dd[k] - bin[k] * NPB) * KN + ss[k];
    }
    if (w == CW) {
        if (tid == NT - 1) { par = par >= NB; flag[14] = (par ^ 1) << 31; }
        asm volatile("cp.async.wait_all;" ::: "memory");
    }
    bar_sync(1, NT);
    TSTAMP(1);
    const uint32_t tag = flag[14];
#pragma unroll
    for (int j = 0; j < 2; j++) {
        const int i = tid + j * NT;
        if (i < NPIECE) {
            const uint2 sa = *(const uint2*)(stage + i * 6), sc = *(const uint2*)(stage + i * 6 + 2);
            uint2 se = *(const uint2*)(stage + i * 6 + 4);
            const uint32_t cf = cnt[i >> 3], cn = min(cf, 63u);
            if ((i & 7) == 7) {
                const uint32_t al = cf > CELL - 8 ? 7 : 0;
                uint32_t o;
                asm volatile("atom.shared.add.u32 %0, [%1], %2;" : "=r"(o) : "r"(sb + SM_MISC + 1824 + 60), "r"(cf + al) : "memory");
                se.y = (o + al) & ~al;
                cnt2[i >> 3] = se.y;
            }
            asm volatile("{.reg .b64 lo, hi; mov.b64 lo, {%1,%2}; mov.b64 hi, {%3,%4}; st.relaxed.gpu.global.v2.b64 [%0], {lo, hi};}"
                         :: "l"(gs->keys + ((i >> 3) * NB + b) * 8 + ((i ^ b) & 7)),
                            "r"(sa.x | (se.x << 20)), "r"(sa.y | ((se.x >> 12) << 20) | ((cn & 7) << 28) | tag),
                            "r"(sc.x | (se.y << 20)), "r"(sc.y | ((se.y >> 12) << 20) | ((cn >> 3) << 28) | tag) : "memory");
        }
    }
    bar_sync(1, NT);
    if (tid == NT - 1) {
        TSTAMPC(10);
        gbar_arrive(&gs->bar[0]);
        asm volatile("mbarrier.arrive.expect_tx.shared.b64 _, [%0], %1;" :: "r"(mbarK), "r"(NPIECE * 16) : "memory");
        unsigned v; int spins = 0;
        do { asm volatile("ld.relaxed.gpu.global.u32 %0, [%1];" : "=r"(v) : "l"(gs->bar) : "memory"); } while ((v >= NB) == par && ++spins < (1 << 22));
        TSTAMPC(13);
        asm volatile("fence.proxy.async.global;" ::: "memory");
        asm volatile("cp.async.bulk.shared::cluster.global.mbarrier::complete_tx::bytes [%0], [%1], %2, [%3];"
                 :: "r"(sb + SM_KEYS), "l"(gs->keys + b * NPIECE), "r"(NPIECE * 16), "r"(mbarK) : "memory");
    }
    __syncwarp();
    uint32_t at[4];
    {
        const int o = g & 3, f = 2 * (t & 1);
#pragma unroll
        for (int i = 0; i < 4; i++) {
            const uint16_t* cp = (const uint16_t*)(smem + SM_SMALL + 1024) + i * 16 + f * 4 + o;
            at[i] = (t >> 1) == (g >> 2) ? cp[0] | ((uint32_t)cp[4] << 16) : 0;
        }
    }

    const int q = lane >> 3, c = lane & 7;
    const uint32_t ring0 = sb + SM_RING + w * 2048;
    uint32_t wdst = ring0 + q * 128 + ((c + 2 * q) & 7) * 16;
    uint32_t rsrc = ring0 + t * 128 + ((g + 2 * t) & 7) * 16;
    uint32_t recl = sb + SM_META + w * (CAP * STEPB) + g * 16 + (t & 1) * 8, srcl = sb + SM_META + w * (CAP * STEPB) + 128 + q * 8 + (c >> 1) * STEPB + (c & 1) * 4;
    uint32_t flg = sb + SM_MISC + (136 + 104 + 80 + 136) * 4;
    asm volatile("" : "+r"(wdst), "+r"(rsrc), "+r"(recl), "+r"(srcl), "+r"(flg));
    auto setflag = [&]() { sts32(flg, 1); };
    uint32_t key[2][6], ha[2][6], rk[2][6], kidx[2], ka[2], kc[2];
    int nk[2];
#pragma unroll
    for (int j = 0; j < 2; j++) {
        const int i0 = j ? 2 * 608 - 1 - tid : tid, i = min(i0, NPIECE - 1), r = i / NB, cc = i - r * NB;
        ka[j] = sb + SM_KEYS + (cc * 8 + ((r ^ cc) & 7)) * 16;
        kidx[j] = (cc * CELL + r * 6) << 17;
        kc[j] = sb + SM_MISC + cc * 4;
        nk[j] = i0 < NPIECE && w < CW ? -6 * r : -1000;
    }
    asm volatile("" : "+r"(at[0]), "+r"(at[1]), "+r"(at[2]), "+r"(at[3]), "+r"(ka[0]), "+r"(ka[1]), "+r"(kidx[0]), "+r"(kidx[1]), "+r"(kc[0]), "+r"(kc[1]), "+r"(nk[0]), "+r"(nk[1]));
    if (w == CW) {
        __syncwarp();
        bar_sync(7, NT);
        if (tid == NT - 1) {
            TSTAMPC(11);
            asm volatile("cp.async.bulk.global.shared::cta.bulk_group [%0], [%1], %2;"
                         :: "l"(gs->recs + b * RCH), "r"(sb + SM_ROUT), "r"(((flag[15] + 1) & ~1u) * 16) : "memory");
            asm volatile("cp.async.bulk.commit_group;" ::: "memory");
            mbar_wait(mbarK, 0);
            unsigned long long tbase;
            asm volatile("mov.u64 %0, %%globaltimer;" : "=l"(tbase));
            tbase += POFF;
            flag[1] = (uint32_t)tbase; flag[4] = (uint32_t)tbase; flag[5] = (uint32_t)(tbase >> 32);
            asm volatile("red.max.relaxed.gpu.global.u64 [%0], %1;" :: "l"(&gs->t0), "l"(tbase) : "memory");
            if (b < 128) asm volatile("cp.async.bulk.prefetch.L2.global [%0], 256;" :: "l"(w_mix + b * 16));
            asm volatile("cp.async.bulk.wait_group 0;" ::: "memory");
            TSTAMPC(14);
            gbar_arrive(&gs->bar[1]);
            TSTAMPC(15);
        }
    } else {
        if (w < 8) {
            const uint32_t* wp = (const uint32_t*)(smem + SM_SMALL) + (t & 1) * 128 + 8 * w + g;
            const uint32_t wr0 = t < 2 ? wp[0] : 0, wr1 = t < 2 ? wp[64] : 0;
            *(uint2*)(smem + SM_AZ + (w >> 1) * 512 + lane * 16 + (w & 1) * 8) =
                make_uint2(pack2(0.5f * bf2f(wr0 & 0xFFFF), 0.5f * bf2f(wr1 & 0xFFFF)), pack2(0.5f * bf2f(wr0 >> 16), 0.5f * bf2f(wr1 >> 16)));
        }
        const bool sw = g & 1;
        uint32_t rp[4];
#pragma unroll
        for (int k = 0; k < 4; k++) rp[k] = cnt2[bin[k]] + slot[k];
        uint4* ro = (uint4*)(smem + SM_ROUT);
        uint4 *p0 = ro + (sw ? rp[2] : rp[0]), *p1 = ro + (sw ? rp[3] : rp[1]), *p2 = ro + (sw ? rp[0] : rp[2]), *p3 = ro + (sw ? rp[1] : rp[3]);
        const uint32_t ya = sb + SM_RAWY + tid * 32 + (sw ? 16 : 0);
        mbar_wait(mbarR, 0);
        TSTAMP(18);
        if (has4) {
            const uint4 y0 = lds128(ya), e0 = lds128(ya + (SM_RAWE - SM_RAWY)), y1 = lds128(ya ^ 16), e1 = lds128((ya ^ 16) + (SM_RAWE - SM_RAWY));
            *p0 = make_uint4(y0.x, e0.x, y0.y, e0.y); *p1 = make_uint4(y0.z, e0.z, y0.w, e0.w);
            *p2 = make_uint4(y1.x, e1.x, y1.y, e1.y); *p3 = make_uint4(y1.z, e1.z, y1.w, e1.w);
        }
        asm volatile("fence.proxy.async.shared::cta;" ::: "memory");
        bar_arrive(7, NT);
    }
    __syncwarp();
    TSTAMP(2);

    if (w < CW) {
        mbar_wait(mbarK, 0);
        TSTAMP(3);
        uint4 v[2] = {lds128(ka[0]), lds128(ka[1])};
        if ((int)((v[0].y ^ tag) | (v[0].w ^ tag) | (v[1].y ^ tag) | (v[1].w ^ tag)) < 0) {
#pragma unroll
            for (int j = 0; j < 2; j++) {
                int spins = 0;
#pragma unroll 1
                while ((int)((v[j].y ^ tag) | (v[j].w ^ tag)) < 0) {
                    asm volatile("{.reg .b64 lo, hi; ld.relaxed.gpu.global.v2.b64 {lo, hi}, [%4]; mov.b64 {%0,%1}, lo; mov.b64 {%2,%3}, hi;}"
                                 : "=r"(v[j].x), "=r"(v[j].y), "=r"(v[j].z), "=r"(v[j].w) : "l"((const unsigned char*)(gs->keys + b * NPIECE) + (ka[j] - sb - SM_KEYS)) : "memory");
                    if (++spins > (1 << 20)) { setflag(); break; }
                }
            }
        }
#pragma unroll
        for (int j = 0; j < 2; j++) {
            const uint32_t hc = ((v[j].y >> 28) & 7) | ((v[j].w >> 25) & 0x38);
            if (j == 1 && nk[j] == -42) {
                sts32(kc[j], hc | ((v[j].z >> 20) << 8));
                if (hc > CELL - 1) setflag();
                v[j].w |= ((80 * KN) >> 12) << 20;
            }
            nk[j] += hc;
            if (nk[j] > 0) {
                key[j][0] = v[j].x & 0xFFFFF; key[j][1] = v[j].y & 0xFFFFF; key[j][2] = v[j].z & 0xFFFFF; key[j][3] = v[j].w & 0xFFFFF;
                key[j][4] = (v[j].x >> 20) | ((v[j].y >> 8) & 0xFF000); key[j][5] = (v[j].z >> 20) | ((v[j].w >> 8) & 0xFF000);
#pragma unroll
                for (int u = 0; u < 6; u++) {
                    ha[j][u] = __umulhi(key[j][u], 0xFFFFFFFFu / KB + 1);
                    asm volatile("{.reg .u32 a, n; mad.lo.u32 a, %1, 4, %2; atom.shared.add.u32 %0, [a+%3], 1;\n"
                                 "shr.u32 n, %1, 5; mad.lo.u32 a, n, 4, %2; red.shared.add.u32 [a+%4], 128;}"
                                 : "=r"(rk[j][u]) : "r"(ha[j][u]), "r"(sb), "n"(SM_HIST), "n"(SM_MISC + 136 * 4) : "memory");
                }
            }
        }
        bar_sync(9, NT - 32);
        TSTAMP(20);
        const int n = tid >> 3, sub = tid & 7;
        const uint32_t me = deg[n];
        uint32_t r = 0, r2 = 0;
#pragma unroll
        for (int k = 0; k < 5; k++) { const uint2 dd = *(const uint2*)(deg + sub * 10 + 2 * k); r += (me - dd.x) >> 31; r2 += (me - dd.y) >> 31; }
        r += r2;
#pragma unroll
        for (int j = 0; j < 2; j++) kidx[j] += (lds32(kc[j]) & 0x700) << 9;
        r += __shfl_xor_sync(0xffffffff, r, 1); r += __shfl_xor_sync(0xffffffff, r, 2); r += __shfl_xor_sync(0xffffffff, r, 4);
        if (sub == 0) order[r] = n;
    }
    bar_sync(1, NT);
    TSTAMP(22);
    uint32_t len2;
    {
        const uint2 na = *(const uint2*)(order + 2 * w);
        uint2 nb = *(const uint2*)(order + 78 - 2 * w);
        const uint32_t hl = sb + SM_HIST + lane * 4;
        const uint32_t ha0 = lds32(hl + na.x * 128), ha1 = lds32(hl + na.y * 128), hb0 = lds32(hl + nb.y * 128), hb1 = lds32(hl + nb.x * 128);
        if (deg[na.x] >= (4 * CAP + 1) * 128) setflag();
        const uint32_t ca = ha0 + (ha1 << 16), c4 = ca + (hb0 << 8) + (hb1 << 24);
        uint32_t inc = c4;
#pragma unroll
        for (int o = 1; o < 32; o <<= 1)
            asm volatile("{.reg .pred p; .reg .u32 u; shfl.sync.up.b32 u|p, %0, %1, 0, 0xffffffff; @p add.u32 %0, %0, u;}" : "+r"(inc) : "r"(o));
        const int su = __reduce_add_sync(0xffffffff, (int)(ha0 - ha1) * (2 * lane - 31)), sv = __reduce_add_sync(0xffffffff, (int)(hb0 - hb1) * (2 * lane - 31));
        const bool swp = (su ^ sv) >= 0;
        if (swp) { nb = make_uint2(nb.y, nb.x); *(uint2*)(order + 78 - 2 * w) = nb; }
        const uint32_t sel = swp ? 0x4143 : 0x4341, ex = inc - c4;
        const uint32_t ea = (ex & 0x00FF00FF) + __byte_perm(ex, 0, sel), eb = ea + ca, base = sb + SM_LIST + w * 2048;
        uint2* pos = (uint2*)(smem + SM_POS) + lane;
        pos[na.x * 32] = make_uint2(base + (ea & 0xFFFF) * 8, na.x * (0u - 4 * KN));
        pos[nb.y * 32] = make_uint2(base + (eb & 0xFFFF) * 8, nb.y * (0u - 4 * KN) + 0x80000000u);
        pos[na.y * 32] = make_uint2(base + 4 + (ea >> 16) * 8, na.y * (0u - 4 * KN));
        pos[nb.x * 32] = make_uint2(base + 4 + (eb >> 16) * 8, nb.x * (0u - 4 * KN) + 0x80000000u);
        len2 = __shfl_sync(0xffffffff, (inc & 0x00FF00FF) + __byte_perm(inc, 0, sel), 31);
        if (max(len2 & 0xFFFF, len2 >> 16) > 4 * CAP) setflag();
    }
    uint32_t ci = cnt[min(w + NW * lane, NB)];
    ci = (((ci & 0xFF) + ((ci >> 8) & 7)) << 24) + min(w + NW * lane, NB) * (RCH / 8) + (ci >> 11);
    if (w == CW) {
        bar_arrive(9, NT);
        if (tid == NT - 1) {
            uint32_t v1, g0; int spins = 0;
            do {
                asm volatile("ld.relaxed.gpu.global.u32 %1, [%2+8]; ld.acquire.gpu.global.u32 %0, [%2+4];" : "=r"(v1), "=r"(g0) : "l"(gs->bar) : "memory");
            } while ((v1 >= NB) == par && ++spins < (1 << 22));
            if ((v1 >= NB) == par) *flag = 1;
            if (g0 - flag[1] < 30000) flag[1] = g0;
            TSTAMPC(17);
        }
        __syncwarp();
    } else {
        bar_sync(9, NT);
        TSTAMP(21);
        const uint32_t over = lds32(flg);
#pragma unroll
        for (int j = 0; j < 2; j++) {
            if (nk[j] > 0) {
                uint2 h[6];
#pragma unroll
                for (int u = 0; u < 6; u++) h[u] = lds64(sb + SM_POS + ha[j][u] * 8);
                if (over) nk[j] = 0;
#pragma unroll
                for (int u = 0; u < 6; u++)
                    asm volatile("{.reg .pred p; setp.gt.s32 p, %2, %3; @p st.shared.u32 [%0], %1;}"
                                 :: "r"(h[u].x + rk[j][u] * 8), "r"(key[j][u] * 4 + h[u].y + (kidx[j] + (u << 17))), "r"(nk[j]), "r"(u) : "memory");
            }
        }
    }
    bar_sync(1, NT);
    TSTAMP(4);
    if (*flag) {
        slow_path(smem, n0, nn, (const uint16_t*)x, (const int*)src4, (const int*)dst4, (const uint16_t*)Y, (const uint16_t*)ef, w_rad, cg,
                  (const uint16_t*)w_mix, (__nv_bfloat16*)out);
        return;
    }
    {
        const uint4* gp = gs->recs + lane;
        asm volatile("" : "+l"(gp));
        const uint32_t sp = sb + SM_RECS + (w * CELL + lane) * 16, lc = (lane << 24) | 0xFFFFFF;
#pragma unroll
        for (int j = 0; j < 7; j++)
            asm volatile("{.reg .pred p; .reg .u32 l; .reg .u64 a; setp.lt.u32 p, %2, %3; and.b32 l, %3, 0xFFFF; mad.wide.u32 a, l, 128, %1;\n"
                         "@p cp.async.cg.shared.global [%0], [a], 16;}"
                         :: "r"(sp + j * (NW * CELL * 16)), "l"(gp), "r"(lc), "r"(__shfl_sync(0xffffffff, ci, j)) : "memory");
        for (uint32_t m = __ballot_sync(0xffffffff, ci >= (33u << 24)); m; m &= m - 1) {
            const int j = __ffs(m) - 1;
            const uint32_t cj = __shfl_sync(0xffffffff, ci, j);
            if (lane + 32 < (cj >> 24))
                asm volatile("cp.async.cg.shared.global [%0], [%1], 16;" :: "r"(sp + j * (NW * CELL * 16) + 512), "l"(gp + (size_t)(cj & 0xFFFF) * 8 + 32) : "memory");
        }
        asm volatile("cp.async.commit_group;" ::: "memory");
    }
    const int S = __shfl_sync(0xffffffff, max((int)(max(len2 & 0xFFFF, len2 >> 16) + 3) >> 2, DS + 1), 0);
    const int mylen = (lane & 1) ? len2 >> 16 : len2 & 0xFFFF;
    constexpr int NRAW = (CAP + 3) / 4;
    uint32_t bits0 = 0, raw[NRAW];
    unsigned char* meta = smem + SM_META + w * (CAP * STEPB);
    const int la = sb + SM_LIST + w * 2048 + lane * 4, llast = la - (lane & ~1) * 4 + (mylen - 1) * 8;
#pragma unroll
    for (int k = 0; k < NRAW; k++) raw[k] = lds32(min(la + k * 128, llast));
    const uint32_t sv0 = min(raw[0] & 0xFFFC, 4 * (NN - 1));
    const unsigned char* pbase = x + c * 16;
    asm volatile("" : "+l"(pbase));
    auto cpa2 = [&](uint32_t dstp, uint32_t sv) {
        asm volatile("cp.async.cg.shared.global [%0], [%1], 16; cp.async.cg.shared.global [%0+1024], [%1+128], 16;"
                     :: "r"(dstp), "l"(pbase + (size_t)sv * 256) : "memory");
    };
    auto cpa2p = [&](uint32_t dstp, uint32_t sv) {
        asm volatile("{.reg .pred p; setp.ge.s32 p, %2, 0; @p cp.async.cg.shared.global [%0], [%1], 16; @p cp.async.cg.shared.global [%0+1024], [%1+128], 16;}"
                     :: "r"(dstp), "l"(pbase + (size_t)sv * 256), "r"(sv) : "memory");
    };
    auto wait_until = [&](uint32_t tt) {
        asm volatile("{.reg .pred p; .reg .u32 d;\n"
                     "PACE_LOOP: mov.u32 d, %%globaltimer_lo; sub.u32 d, %0, d; setp.lt.u32 p, d, 32768; @p nanosleep.u32 %1; @p bra.uni PACE_LOOP;}"
                     :: "r"(tt), "n"(PSLEEP) : "memory");
    };
    const uint32_t tfill = flag[1] - FOFF;
    auto fill = [&](int i) {
        wait_until(tfill + i * FDT);
        cpa2(wdst + i * SLOTB, __shfl_sync(0xffffffff, sv0, 8 * i + 2 * q)); cpa2(wdst + i * SLOTB + 512, __shfl_sync(0xffffffff, sv0, 8 * i + 2 * q + 1));
        asm volatile("cp.async.commit_group;" ::: "memory");
    };
    fill(0);
    TSTAMP(5);
    auto relay = [&]() {
        uint32_t g0, g1, b0, b1;
        asm volatile("ld.volatile.shared.v2.u32 {%0,%1}, [%4+40]; ld.volatile.shared.v2.u32 {%2,%3}, [%4+16];"
                     : "=r"(g0), "=r"(g1), "=r"(b0), "=r"(b1) : "r"(flg) : "memory");
        const unsigned long long dg = (((unsigned long long)g1 << 32) | g0) - (((unsigned long long)b1 << 32) | b0);
        asm volatile("{.reg .pred p, q; setp.eq.u32 p, %1, 0; setp.lt.u64 q, %2, 30000; @q st.shared.u32 [%3+4], %4;\n"
                     "@p cp.async.cg.shared.global [%3+32], [%0], 16;}"
                     :: "l"(gs->bar), "r"(lane), "l"(dg), "r"(flg), "r"(g0) : "memory");
    };
    auto report = [&](uint32_t cand) {
        uint32_t b0, b1;
        asm volatile("ld.volatile.shared.v2.u32 {%0,%1}, [%2+16];" : "=r"(b0), "=r"(b1) : "r"(flg) : "memory");
        asm volatile("{.reg .pred p; setp.eq.u32 p, %2, 0; @p red.max.relaxed.gpu.global.u64 [%0], %1;}"
                     :: "l"(&gs->t0), "l"((((unsigned long long)b1 << 32) | b0) + (cand - b0)), "r"(lane) : "memory");
    };
    uint32_t ra[NRAW];
#pragma unroll
    for (int k = NRAW - 1; k >= 0; k--) {
        const uint32_t m = (__ballot_sync(0xffffffff, (int)raw[k] < 0) >> g) & 0x01010101u;
        bits0 = __funnelshift_l(m * 0x10204080u, bits0, 4);
        const bool pad = la + k * 128 > llast;
        ra[k] = pad ? NB * CELL * 16 : (raw[k] >> 13) & 0x1FFF0;
        raw[k] = (raw[k] & 0xFFFF) | (pad ? F_PAD : 0);
    }
    if (t < 2) bits0 = ~bits0;
    asm volatile("" : "+r"(bits0), "+r"(ra[0]), "+r"(ra[1]), "+r"(ra[2]), "+r"(ra[3]), "+r"(ra[4]), "+r"(raw[0]), "+r"(raw[1]), "+r"(raw[2]), "+r"(raw[3]), "+r"(raw[4]));
    fill(1);
    asm volatile("cp.async.wait_group 2;" ::: "memory");
    bar_sync(1, NT);
    TSTAMP(19);
    if (w == CW) {
        uint32_t tn; asm volatile("mov.u32 %0, %%globaltimer_lo;" : "=r"(tn));
        if ((int)(tn + RDY - flag[1]) > 0) { report(tn + RDY); flag[1] = tn + RDY; }
    }
    {
        uint4 rv[NRAW];
#pragma unroll
        for (int k = 0; k < NRAW - 1; k++) rv[k] = lds128(ra[k] + (sb + SM_RECS));
        if ((NRAW - 1) * 4 < S) rv[NRAW - 1] = lds128(ra[NRAW - 1] + (sb + SM_RECS));
        fill(2);
        bar_sync(1, NT);
        TSTAMP(12);
        unsigned char* mr = meta + (q - 1) * STEPB + c * 16;
        unsigned char* ms = meta + (q - DS - 1) * STEPB + 128 + c * 4;
#pragma unroll
        for (int k = 0; k < NRAW; k++) {
            if (k == 0) {
                *(uint4*)(mr + (q == 0 ? S * STEPB : 0)) = rv[k];
                *(uint32_t*)(ms + S * STEPB) = raw[0] + F_WRAP;
            } else if (k * 4 + q < S) {
                *(uint4*)(mr + k * 4 * STEPB) = rv[k];
                *(uint32_t*)(ms + k * 4 * STEPB + (k == 1 && q == 0 ? S * STEPB : 0)) = raw[k];
            }
        }
    }
    __syncwarp();
    const uint32_t tphase = PACE / 4;
    uint32_t dreg;
    {
        const int ls = lane >= S ? min(lane - S, S - 1) : lane, st = ls == 0 ? S - 1 : ls - 1;
        const uint4 u0 = *(const uint4*)(meta + st * STEPB + 128), u1 = *(const uint4*)(meta + st * STEPB + 144);
        int pos = (u0.x + u0.y + u0.z + u0.w + u1.x + u1.y + u1.z + u1.w) << 1 >> 6;
        pos += ((u0.x & F_WRAP) ? NN : 0) + (lane >= S ? NN : 0) - NN * (2 * DS + 1) / 32;
        dreg = pos * (int)tphase / NN;
    }
    fill(3);
    TSTAMP(6);

    uint32_t* stash = (uint32_t*)(gs->stash + (b * NW + w) * 256) + lane;
    asm volatile("" : "+l"(stash));
    float acc[4][4];
#pragma unroll
    for (int i = 0; i < 16; i++) acc[i / 4][i % 4] = 0.f;
    uint4 az = *(const uint4*)(smem + SM_AZ + lane * 16);
    uint32_t dcur = dreg, dl = 0, now = flag[1], tcur = 0;
    uint32_t mp = 0, smask = 1, didx = 2, nowe = 0;
    uint32_t mend = S * STEPB;
    uint2 r = lds64(mend - STEPB + recl);
    uint2 s0 = lds64(sb + SM_META + w * (CAP * STEPB) + 128 + q * 8 + mend - STEPB);
    float zn[4], yn[4];
    auto zpre = [&]() {
        mma1688zv(zn, az.x, az.y, r.y);
        mma1688zv(yn, az.z, az.w, r.y);
    };
    zpre();
    uint32_t s4r = 0;
    auto step = [&](const uint32_t off, const int mode, const bool pc = true) {
        const uint2 rc = r;
        const uint2 sc = s0;
        if (mode != 4) r = lds64(mp + recl);
        if (mode == 0 && off == 0) s4r = lds32(mp + srcl);
        asm volatile("cp.async.wait_group %0;" :: "n"(DS - 1) : "memory");
        const uint4 xa = lds128(rsrc + off), xb = lds128(rsrc + off + 512), xc = lds128(rsrc + off + 1024), xd = lds128(rsrc + off + 1536);
        float z[4], y[4], t1[4], t2[4];
        for (int i = 0; i < 4; i++) { z[i] = zn[i]; y[i] = yn[i]; }
        uint32_t bt;
        asm("{.reg .pred p; .reg .b32 m; and.b32 m, %2, %3; setp.ne.u32 p, m, 0; selp.b32 %0, %1, 0, p;}" : "=r"(bt) : "r"(rc.x), "r"(bits0), "r"(smask));
        mma1688z(t1, at[0], at[1], bt);
        mma1688z(t2, at[2], at[3], bt);
        const uint32_t T0 = pack2(t1[0], t1[2]), T1 = pack2(t2[0], t2[2]), T2 = pack2(t1[1], t1[3]), T3 = pack2(t2[1], t2[3]);
        uint32_t R[8];
#pragma unroll
        for (int i = 0; i < 4; i++) { R[i] = __float_as_uint(silu_h(z[i])); R[4 + i] = __float_as_uint(silu_h(y[i])); }
        mma16816(acc[0], mul_hi(xa.x, R[0]), mul_hi(xa.z, R[2]), mul_hi(xa.y, R[0]), mul_hi(xa.w, R[2]), T0, T1);
        mma16816(acc[1], mul_hi(xb.x, R[1]), mul_hi(xb.z, R[3]), mul_hi(xb.y, R[1]), mul_hi(xb.w, R[3]), T2, T3);
        mma16816(acc[2], mul_hi(xc.x, R[4]), mul_hi(xc.z, R[6]), mul_hi(xc.y, R[4]), mul_hi(xc.w, R[6]), T0, T1);
        mma16816(acc[3], mul_hi(xd.x, R[5]), mul_hi(xd.z, R[7]), mul_hi(xd.y, R[5]), mul_hi(xd.w, R[7]), T2, T3);
        if (mode != 4 && mode != 0) zpre();
        if (mode == 0) {
            unsigned long long n64; asm volatile("mov.u64 %0, %%globaltimer;" : "=l"(n64));
            if (pc) now = (uint32_t)n64; else nowe = (uint32_t)n64;
            zpre();
            s0.x = __shfl_sync(0xffffffff, s4r, off / SLOTB * 2, 8); s0.y = __shfl_sync(0xffffffff, s4r, off / SLOTB * 2 + 1, 8);
            if (pc) { dl = __shfl_sync(0xffffffff, dcur, didx); didx += 2; }
            cpa2p(wdst + off, sc.x); cpa2p(wdst + off + 512, sc.y);
        }
        if (mode == 1 && w < 16) {
            const int lane = tid & 31, q = lane >> 3, c = lane & 7;
            const uint32_t ring0 = sb + SM_RING + w * 2048;
#pragma unroll
            for (int j = 0; j < 4; j++) {
                const int kk = 4 * j + q, ch = 16 * (w & 7) + 2 * (kk & 7) + (kk >> 3);
                asm volatile("cp.async.cg.shared.global [%0], [%1], 16;" :: "r"(ring0 + kk * 128 + ((c ^ (kk & 7)) << 4)), "l"(w_mix + ch * 16 + (w >> 3) * 8 + c) : "memory");
            }
            asm volatile("cp.async.mbarrier.arrive.noinc.shared.b64 [%0];" :: "r"(mbarW) : "memory");
        }
        if (mode == 2 || mode == 3) {
            const int lane = tid & 31;
            const uint32_t ring0 = sb + SM_RING + w * 2048;
#pragma unroll
            for (int j = 0; j < 4; j += mode - 1)
                asm volatile("cp.async.cg.shared.global [%0], [%1], 16;" :: "r"(ring0 + off + j * 512 + lane * 16), "l"(stash + (mode - 2) * 512 + j * 128 + lane * 3) : "memory");
        }
        if (mode < 4) asm volatile("cp.async.commit_group;" ::: "memory");
        mp += STEPB; smask <<= 1;
    };
    auto putacc = [&](uint32_t* p) {
        p[0] = pack2(acc[0][0], acc[0][1]); p[32] = pack2(acc[0][2], acc[0][3]); p[64] = pack2(acc[2][0], acc[2][1]); p[96] = pack2(acc[2][2], acc[2][3]);
        p[256] = pack2(acc[1][0], acc[1][1]); p[288] = pack2(acc[1][2], acc[1][3]); p[320] = pack2(acc[3][0], acc[3][1]); p[352] = pack2(acc[3][2], acc[3][3]);
    };
    int ph = 0;
    auto phase_end = [&](const int k) {
        az = lds128(sb + SM_AZ + (ph + 1) * 512 + lane * 16);
        putacc(stash + ph * ph * 128);
#pragma unroll
        for (int i = 0; i < 16; i++) acc[i / 4][i % 4] = 0.f;
        pbase += 256; mp = 0; smask = 1; ph++;
        zpre();
        if (k < 3) s4r = lds32(srcl - (k + 1) * STEPB);
        dcur += tphase; didx = 1 + (k & 1);
        if (ph == 3) {
            mend -= DS * STEPB;
            dcur += (int)(dcur - __shfl_sync(0xffffffff, dcur, 0)) * (((w >> 2) - 2) * FAN) >> 8;
        }
        WSTAMP(ph - 1);
    };
    uint32_t t0 = now;
    if (w == PW) {
        asm volatile("mov.u32 %0, %%globaltimer_lo;" : "=r"(now));
        now += PTOL - PTOL0;
    }
    const uint32_t bias = w == RW ? 1u << 20 : 0;
    if (w == RW) relay();
    dcur += bias;
    auto body = [&](const int k) -> bool {
        if (k == 2) asm volatile("ld.volatile.shared.u32 %0, [%1+4];" : "=r"(t0) : "r"(flg));
        const bool pc = k & 1;
        step(k * SLOTB, 0, pc);
        if (!pc) {
            if (mp == mend) phase_end(k);
        } else if (mp == mend || now < dl) {
            if (mp == mend) {
                if (k == 3 && ph == 3) return true;
                phase_end(k);
            }
            if (w == RW) dl -= 1u << 20;
            if (w == RW) {
                relay();
                {
                    const int lane = tid & 31, n0 = cta_now() * NPB, nn = min(NPB, NN - n0);
                    const int row = (mp / (2 * STEPB)) * (16 * XPF) + (lane >> 1);
#pragma unroll
                    for (int u = 0; u < XPF; u++)
                        asm volatile("{.reg .pred p; setp.lt.s32 p, %1, %2; @p prefetch.global.L2 [%0];}"
                                     :: "l"(x + (size_t)(n0 + row + 16 * u) * 1024 + (ph + 1) * 256 + (lane & 1) * 128), "r"(row + 16 * u), "r"(ph < 3 ? nn : 0));
                }
            }
            wait_until(nowe == 12345 ? dl + 1 : dl);
        }
        return false;
    };
    if (w >= 4 && w < 9) {
        const int i = tid_now() - 128;
        if ((i >> 1) < nn && b >= XPF0) asm volatile("prefetch.global.L2 [%0];" :: "l"(x + (size_t)(n0 + (i >> 1)) * 1024 + (i & 1) * 128));
    }
    {
        const uint32_t d0 = __shfl_sync(0xffffffff, dreg, 0);
        if (w == RW) {
            uint32_t g0, tn; int spins = 0;
            do {
                asm volatile("ld.relaxed.gpu.global.u32 %0, [%2]; mov.u32 %1, %%globaltimer_lo;" : "=r"(g0), "=r"(tn) : "l"(&gs->t0) : "memory");
                if (g0 - t0 < 30000) { t0 = g0; flag[1] = g0; }
            } while (__shfl_sync(0xffffffff, t0 - tn, 0) < 32768 && ++spins < 64);
        }
        asm volatile("{.reg .pred p; .reg .u32 d;\n"
                     "PACE_LOOP: ld.volatile.shared.u32 %0, [%2+4]; mov.u32 d, %%globaltimer_lo; sub.u32 d, %1, d; add.u32 d, d, %0;\n"
                     "setp.lt.u32 p, d, 32768; @p nanosleep.u32 32; @p bra.uni PACE_LOOP;}"
                     : "=&r"(t0) : "r"(d0), "r"(flg) : "memory");
    }
    while (true) {
        if (w == PW) {
            const uint32_t cand = now - dl + tcur - PTOL;
            if ((int)(cand - t0) > 0) report(cand);
        }
        dcur += t0 - tcur; tcur = t0;
        body(0); body(1); body(2);
        if (body(3)) break;
    }
    __syncwarp();
    step(0, 1);
    { uint32_t tn; asm volatile("mov.u32 %0, %%globaltimer_lo;" : "=r"(tn)); wait_until(tn + (w >> 2) * TDEL); }
    step(SLOTB, 2); step(2 * SLOTB, 3); step(3 * SLOTB, 4);
    WSTAMP(3); ESTAMP(0);

    {
        const int tid = tid_now(), lane = tid & 31, g = lane >> 2, t = lane & 3, n0 = cta_now() * NPB, nn = min(NPB, NN - n0);
        putacc((uint32_t*)(smem + SM_RING + 2 * SLOTB + w * 2048 + 512) + lane);
        const int wg = w >> 2, w4 = w & 3;
        int nd[8];
#pragma unroll
        for (int j = 0; j < 8; j++) { const int l = wg * 8 + j; nd[j] = order[(t >> 1) ? 79 - l : l]; asm volatile("" : "+r"(nd[j])); }
        const bool odd = t & 1;
        uint2* ob = (uint2*)out + (size_t)n0 * 128 + w4 * 16 + g + (odd ? 8 : 0);
        asm volatile("cp.async.wait_all;" ::: "memory");
        mbar_wait(mbarW, 0);
        asm volatile("fence.proxy.async.shared::cta;" ::: "memory");
        ESTAMP(1);
        bar_sync(2 + wg, 128);
        uint32_t ticket = 0;
        if ((tid & 127) == 0) {
            asm volatile("atom.shared.add.u32 %0, [%1+48], 1;" : "=r"(ticket) : "r"(flg) : "memory");
            int spins = 0;
            while (flag[13] < ticket && ++spins < (1 << 16)) __nanosleep(40);
        }
        bar_sync(2 + wg, 128);
        const uint64_t descA0 = (uint64_t)(((sb + SM_RING) & 0x3FFFF) >> 4) | ((uint64_t)1 << 16) | ((uint64_t)(1024 >> 4) << 32) | ((uint64_t)1 << 62);
        const uint64_t descB0 = (uint64_t)(((sb + SM_RING + SLOTB + wg * 8192) & 0x3FFFF) >> 4) | ((uint64_t)(128 >> 4) << 16) | ((uint64_t)(1024 >> 4) << 32);
        float d[2][32];
        asm volatile("wgmma.fence.sync.aligned;" ::: "memory");
        ESTAMP(2);
#pragma unroll
        for (int mt = 0; mt < 2; mt++) {
#pragma unroll
            for (int ks = 0; ks < 8; ks++) {
                if (mt * 8 + ks == RELK)
                    asm volatile("{.reg .pred p; setp.eq.u32 p, %1, 0; @p st.volatile.shared.u32 [%0+52], %2;}" :: "r"(flg), "r"(tid & 127), "r"(ticket + 1) : "memory");
                const uint64_t da = descA0 + (uint64_t)((ks * 2048 + mt * 16384) >> 4), db = descB0 + (uint64_t)(((ks & 3) * 256 + (ks >> 2) * SLOTB) >> 4);
                asm volatile("{.reg .pred p; setp.ne.b32 p, %34, 0;\n"
                    "wgmma.mma_async.sync.aligned.m64n64k16.f32.bf16.bf16 "
                    "{%0,%1,%2,%3,%4,%5,%6,%7,%8,%9,%10,%11,%12,%13,%14,%15,%16,%17,%18,%19,%20,%21,%22,%23,%24,%25,%26,%27,%28,%29,%30,%31}, %32, %33, p, 1, 1, 1, 1;}"
                    : "+f"(d[mt][0]), "+f"(d[mt][1]), "+f"(d[mt][2]), "+f"(d[mt][3]), "+f"(d[mt][4]), "+f"(d[mt][5]), "+f"(d[mt][6]), "+f"(d[mt][7]),
                      "+f"(d[mt][8]), "+f"(d[mt][9]), "+f"(d[mt][10]), "+f"(d[mt][11]), "+f"(d[mt][12]), "+f"(d[mt][13]), "+f"(d[mt][14]), "+f"(d[mt][15]),
                      "+f"(d[mt][16]), "+f"(d[mt][17]), "+f"(d[mt][18]), "+f"(d[mt][19]), "+f"(d[mt][20]), "+f"(d[mt][21]), "+f"(d[mt][22]), "+f"(d[mt][23]),
                      "+f"(d[mt][24]), "+f"(d[mt][25]), "+f"(d[mt][26]), "+f"(d[mt][27]), "+f"(d[mt][28]), "+f"(d[mt][29]), "+f"(d[mt][30]), "+f"(d[mt][31])
                    : "l"(da), "l"(db), "r"(ks));
            }
            asm volatile("wgmma.commit_group.sync.aligned;" ::: "memory");
        }
#pragma unroll
        for (int mt = 0; mt < 2; mt++) {
            if (mt == 0) asm volatile("wgmma.wait_group.sync.aligned 1;" ::: "memory");
            else asm volatile("wgmma.wait_group.sync.aligned 0;" ::: "memory");
            ESTAMP(3 + mt);
#pragma unroll
            for (int i = 0; i < 32; i++) asm volatile("" : "+f"(d[mt][i]) :: "memory");
#pragma unroll
            for (int j = 0; j < 8; j++) {
                const uint32_t v0 = pack2(d[mt][4 * j], d[mt][4 * j + 1]), v1 = pack2(d[mt][4 * j + 2], d[mt][4 * j + 3]);
                const uint32_t rv = __shfl_xor_sync(0xffffffff, odd ? v0 : v1, 1);
                if (nd[j] < nn) ob[nd[j] * 128 + mt * 64] = odd ? make_uint2(rv, v1) : make_uint2(v0, rv);
            }
        }
    }
    TSTAMP(8); ESTAMP(5);
}

__global__ void __launch_bounds__(NT, 1)
tfn_fallback(const uint16_t* x, const int* src, const int* dst, const uint16_t* Y, const uint16_t* ef, const uint16_t* w_rad,
             const uint16_t* cg, const uint16_t* w_mix, __nv_bfloat16* out) {
    extern __shared__ __align__(1024) unsigned char smem[];
    const int n0 = blockIdx.x * NPB;
    slow_path(smem, n0, min(NPB, NN - n0), x, src, dst, Y, ef, w_rad, cg, w_mix, out);
}

}

extern "C" void kernel_launch(void* const* d_in, const int* in_sizes, int n_in, void* d_out, int out_size) {
    (void)in_sizes; (void)n_in; (void)out_size;
    cudaFuncSetAttribute(tfn_kernel, cudaFuncAttributeMaxDynamicSharedMemorySize, SM_TOTAL);
    int dev = 0, sms = 0;
    cudaGetDevice(&dev);
    cudaDeviceGetAttribute(&sms, cudaDevAttrMultiProcessorCount, dev);
    if (sms < NB) {
        cudaFuncSetAttribute(tfn_fallback, cudaFuncAttributeMaxDynamicSharedMemorySize, NPB * 2048);
        tfn_fallback<<<NB, NT, NPB * 2048, cudaStreamPerThread>>>((const uint16_t*)d_in[0], (const int*)d_in[1], (const int*)d_in[2], (const uint16_t*)d_in[3],
            (const uint16_t*)d_in[4], (const uint16_t*)d_in[5], (const uint16_t*)d_in[6], (const uint16_t*)d_in[7], (__nv_bfloat16*)d_out);
        return;
    }
    Scratch* gs = nullptr;
    cudaGetSymbolAddress((void**)&gs, g_scratch);
    cudaLaunchConfig_t cfg = {};
    cfg.gridDim = dim3(NB); cfg.blockDim = dim3(NT); cfg.dynamicSmemBytes = SM_TOTAL; cfg.stream = cudaStreamPerThread;
    cudaLaunchAttribute at[1];
    at[0].id = cudaLaunchAttributeCooperative; at[0].val.cooperative = 1;
    cfg.attrs = at; cfg.numAttrs = 1;
    cudaLaunchKernelEx(&cfg, tfn_kernel, (const unsigned char*)d_in[0], (const int4*)d_in[1], (const int4*)d_in[2],
                       (const uint4*)d_in[3], (const uint4*)d_in[4], (const uint16_t*)d_in[5], (const uint16_t*)d_in[6],
                       (const uint4*)d_in[7], (uint32_t*)d_out, gs);
}
```

```cpp
#include <cuda_runtime.h>
#include <cuda_bf16.h>
#include <stdint.h>

namespace {

constexpr int NN = 10000;
constexpr int NE = 320000;
constexpr int NB = 132;
constexpr int NW = 20;
constexpr int NT = NW * 32;
constexpr int CW = NW - 1;
constexpr int PW = 10;
constexpr int RW = 1;
constexpr int NPB = 76;
constexpr int CELL = 48;
constexpr int RCH = 2880;
constexpr int CAP = 19;
constexpr int DS = 4;
constexpr int STEPB = 160;
constexpr int NE4 = NE / 4;
constexpr int NPIECE = NB * 8;
constexpr int KB = 320, KN = 32 * KB;
constexpr uint32_t F_PAD = 0x80000000u;
constexpr uint32_t F_WRAP = 1;

constexpr int SLOTB = NW * 2048;
constexpr int SM_RING = 0;
constexpr int SM_META = SM_RING + DS * SLOTB;
constexpr int SM_AZ = SM_META + NW * CAP * STEPB;
constexpr int SM_MISC = SM_AZ + 2048;
constexpr int SM_TOTAL = SM_MISC + 2048;
constexpr int SM_STAGE = SM_RING;
constexpr int SM_HIST = SM_RING + 25600;
constexpr int SM_POS = SM_RING;
constexpr int SM_SMALL = SM_HIST + 13056;
constexpr int SM_LIST = SM_RING + SLOTB;
constexpr int SM_ROUT = SM_RING + 2 * SLOTB;
constexpr int SM_RECS = SM_RING + 3 * SLOTB;
constexpr int SM_RAWY = SM_META;
constexpr int SM_RAWE = SM_RAWY + 608 * 32;
constexpr int SM_KEYS = SM_RAWE + 608 * 32;
static_assert(SM_TOTAL <= 232448 && SM_KEYS + NPIECE * 16 <= SM_AZ, "smem");
static_assert(SM_RECS + NB * CELL * 16 + 16 <= SM_AZ && SM_KEYS + NPIECE * 16 <= SM_RECS + NB * CELL * 16 && SM_SMALL + 1152 <= SLOTB && DS == 4, "smem");

struct __align__(1024) Scratch {
    uint4 keys[NB * NPIECE];
    uint4 recs[NB * RCH];
    uint4 stash[NB * NW * 256];
    unsigned bar[2];
    unsigned long long t0;
};
__device__ Scratch g_scratch;
#define TSTAMP(i)
#define TSTAMPC(i)
#define WSTAMP(i)
#define ESTAMP(i)

__device__ __forceinline__ void mma16816(float* d, uint32_t a0, uint32_t a1, uint32_t a2, uint32_t a3, uint32_t b0, uint32_t b1) {
    asm volatile("mma.sync.aligned.m16n8k16.row.col.f32.bf16.bf16.f32 {%0,%1,%2,%3}, {%4,%5,%6,%7}, {%8,%9}, {%0,%1,%2,%3};"
        : "+f"(d[0]), "+f"(d[1]), "+f"(d[2]), "+f"(d[3]) : "r"(a0), "r"(a1), "r"(a2), "r"(a3), "r"(b0), "r"(b1));
}
__device__ __forceinline__ void mma1688z(float* d, uint32_t a0, uint32_t a1, uint32_t b0) {
    asm("mma.sync.aligned.m16n8k8.row.col.f32.bf16.bf16.f32 {%0,%1,%2,%3}, {%4,%5}, {%6}, {%7,%7,%7,%7};"
        : "=f"(d[0]), "=f"(d[1]), "=f"(d[2]), "=f"(d[3]) : "r"(a0), "r"(a1), "r"(b0), "f"(0.f));
}
__device__ __forceinline__ void mma1688zv(float* d, uint32_t a0, uint32_t a1, uint32_t b0) {
    asm volatile("mma.sync.aligned.m16n8k8.row.col.f32.bf16.bf16.f32 {%0,%1,%2,%3}, {%4,%5}, {%6}, {%7,%7,%7,%7};"
        : "=f"(d[0]), "=f"(d[1]), "=f"(d[2]), "=f"(d[3]) : "r"(a0), "r"(a1), "r"(b0), "f"(0.f));
}
__device__ __forceinline__ uint32_t pack2(float lo, float hi) {
    uint32_t r; asm("cvt.rn.bf16x2.f32 %0, %1, %2;" : "=r"(r) : "f"(hi), "f"(lo)); return r;
}
__device__ __forceinline__ float silu_h(float h) {
    float t; asm volatile("tanh.approx.f32 %0, %1;" : "=f"(t) : "f"(h)); return fmaf(h, t, h);
}
__device__ __forceinline__ uint32_t mul_hi(uint32_t v, uint32_t r) {
    uint32_t c; asm volatile("{.reg .b16 l, h; .reg .b32 d; mov.b32 {l, h}, %2; mov.b32 d, {h, h}; mul.rn.bf16x2 %0, %1, d;}" : "=r"(c) : "r"(v), "r"(r)); return c;
}
__device__ __forceinline__ int tid_now() { int v; asm volatile("mov.u32 %0, %%tid.x;" : "=r"(v)); return v; }
__device__ __forceinline__ int cta_now() { int v; asm volatile("mov.u32 %0, %%ctaid.x;" : "=r"(v)); return v; }
__device__ __forceinline__ uint32_t lds32(uint32_t a) {
    uint32_t r; asm volatile("ld.shared.u32 %0, [%1];" : "=r"(r) : "r"(a) : "memory"); return r;
}
__device__ __forceinline__ void sts32(uint32_t a, uint32_t v) { asm volatile("st.shared.u32 [%0], %1;" :: "r"(a), "r"(v) : "memory"); }
__device__ __forceinline__ uint2 lds64(uint32_t a) {
    uint2 r; asm volatile("ld.shared.v2.u32 {%0,%1}, [%2];" : "=r"(r.x), "=r"(r.y) : "r"(a)); return r;
}
__device__ __forceinline__ uint4 lds128(uint32_t a) {
    uint4 r; asm volatile("ld.shared.v4.u32 {%0,%1,%2,%3}, [%4];" : "=r"(r.x), "=r"(r.y), "=r"(r.z), "=r"(r.w) : "r"(a) : "memory"); return r;
}
__device__ __forceinline__ void bar_sync(int id, int n) { asm volatile("bar.sync %0, %1;" :: "r"(id), "r"(n) : "memory"); }
__device__ __forceinline__ void bar_arrive(int id, int n) { asm volatile("bar.arrive %0, %1;" :: "r"(id), "r"(n) : "memory"); }
__device__ __forceinline__ void mbar_wait(uint32_t bar, uint32_t ph) {
    uint32_t done; int spins = 0;
    do {
        asm volatile("{.reg .pred p; mbarrier.try_wait.parity.shared.b64 p, [%1], %2; selp.u32 %0,1,0,p;}" : "=r"(done) : "r"(bar), "r"(ph) : "memory");
    } while (!done && ++spins < (1 << 22));
}
__device__ __forceinline__ void gbar_arrive(unsigned* ctr) {
    asm volatile("red.inc.relaxed.gpu.global.u32 [%0], %1;" :: "l"(ctr), "n"(2 * NB - 1) : "memory");
}
__device__ __forceinline__ int chunk_start4(int c) { return (c * NE4) / NB; }
__device__ __forceinline__ float bf2f(uint32_t h) { return __uint_as_float(h << 16); }

__device__ __noinline__ void slow_path(unsigned char* smem, int n0, int nn, const uint16_t* x, const int* src, const int* dst,
                                       const uint16_t* Y, const uint16_t* ef, const uint16_t* w_rad, const uint16_t* cg,
                                       const uint16_t* w_mix, __nv_bfloat16* out) {
    float* agg = (float*)smem;
    const int tid = threadIdx.x, lane = tid & 31, w = tid >> 5;
    bar_sync(1, NT);
    for (int i = tid; i < NPB * 512; i += NT) agg[i] = 0.f;
    bar_sync(1, NT);
    for (int e0 = w * 32; e0 < NE; e0 += NT) {
        int dl = dst[e0 + lane] - n0;
        unsigned m = __ballot_sync(0xffffffff, dl >= 0 && dl < nn);
        while (m) {
            int l = __ffs(m) - 1; m &= m - 1;
            int e = e0 + l, d = __shfl_sync(0xffffffff, dl, l), s = src[e];
            float T[16];
            for (int i = 0; i < 4; i++) for (int o = 0; o < 4; o++) {
                float a = 0.f;
                for (int f = 0; f < 4; f++) a += bf2f(Y[e * 4 + f]) * bf2f(cg[i * 16 + f * 4 + o]);
                T[i * 4 + o] = a;
            }
            for (int k = 0; k < 4; k++) {
                int c = lane + 32 * k;
                float z = 0.f;
                for (int j = 0; j < 4; j++) z += bf2f(ef[e * 4 + j]) * bf2f(w_rad[j * 128 + c]);
                float R = z / (1.f + __expf(-z));
                for (int o = 0; o < 4; o++) {
                    float a = 0.f;
                    for (int i = 0; i < 4; i++) a += bf2f(x[(size_t)s * 512 + c * 4 + i]) * T[i * 4 + o];
                    atomicAdd(&agg[d * 512 + c * 4 + o], R * a);
                }
            }
        }
    }
    bar_sync(1, NT);
    for (int i = tid; i < nn * 512; i += NT) {
        int n = i >> 9, d = (i >> 2) & 127, o = i & 3;
        float a = 0.f;
        for (int c = 0; c < 128; c++) a += agg[n * 512 + c * 4 + o] * bf2f(w_mix[c * 128 + d]);
        out[(size_t)(n0 + n) * 512 + (i & 511)] = __float2bfloat16(a);
    }
}

#define PACE 22600
#define YDELAY 300
#define POFF 3650
#define PSLEEP 64
#define FDT 350
#define FOFF 1500
#define RELK 12
#define FAN 16
#define TDEL 100
#define RDY 600
#define XPF 2
#define XPF0 40
#define BP 4
#define MO 0
#define PTOL0 300
#define PTOL 1500
__global__ void __launch_bounds__(NT, 1)
tfn_kernel(const unsigned char* __restrict__ x, const int4* __restrict__ src4, const int4* __restrict__ dst4,
           const uint4* __restrict__ Y, const uint4* __restrict__ ef, const uint16_t* __restrict__ w_rad,
           const uint16_t* __restrict__ cg, const uint4* __restrict__ w_mix, uint32_t* __restrict__ out, Scratch* __restrict__ gs) {
    extern __shared__ __align__(1024) unsigned char smem[];
    const uint32_t sb = (uint32_t)__cvta_generic_to_shared(smem);
    const int b = blockIdx.x, tid = threadIdx.x, lane = tid & 31, g = lane >> 2, t = lane & 3;
    const int w = __shfl_sync(0xffffffff, tid >> 5, 0);
    uint32_t* stage = (uint32_t*)(smem + SM_STAGE);
    uint32_t* hist = (uint32_t*)(smem + SM_HIST);
    uint32_t* cnt = (uint32_t*)(smem + SM_MISC);
    uint32_t* deg = cnt + 136;
    uint32_t* order = deg + 104;
    uint32_t* cnt2 = order + 80;
    volatile uint32_t* flag = cnt2 + 136;
    const uint32_t mbarK = sb + SM_MISC + 1920, mbarR = mbarK + 8, mbarW = mbarK + 16;
    const int n0 = b * NPB, nn = min(NPB, NN - n0);
    TSTAMP(0);

    const int c0 = chunk_start4(b), c1 = chunk_start4(b + 1);
    const bool has4 = c0 + tid < c1;
    int4 d4 = make_int4(0, 0, 0, 0), s4 = d4;
    if (has4) { d4 = __ldg(dst4 + c0 + tid); s4 = __ldg(src4 + c0 + tid); }
    unsigned par = 0;
    if (tid == NT - 1) {
        asm volatile("ld.relaxed.gpu.global.u32 %0, [%1];" : "=r"(par) : "l"(gs->bar) : "memory");
        asm volatile("mbarrier.init.shared.b64 [%0], 1;" :: "r"(mbarK));
        asm volatile("mbarrier.init.shared.b64 [%0], 1;" :: "r"(mbarR));
        asm volatile("mbarrier.init.shared.b64 [%0], 512;" :: "r"(mbarW));
        asm volatile("fence.mbarrier_init.release.cluster;" ::: "memory");
        flag[0] = 0; flag[12] = 0; flag[13] = 0; flag[15] = 0;
    }
    if (w == CW) {
        asm volatile("cp.async.cg.shared.global [%0], [%1], 16;" :: "r"(sb + SM_SMALL + lane * 16), "l"(w_rad + lane * 8) : "memory");
        asm volatile("cp.async.cg.shared.global [%0], [%1], 16;" :: "r"(sb + SM_SMALL + 512 + lane * 16), "l"(w_rad + 256 + lane * 8) : "memory");
        if (lane < 8) asm volatile("cp.async.cg.shared.global [%0], [%1], 16;" :: "r"(sb + SM_SMALL + 1024 + lane * 16), "l"(cg + lane * 8) : "memory");
    }
    ((uint4*)hist)[tid] = make_uint4(0, 0, 0, 0);
    {
        const uint32_t dk = (80 + b % 22) * KN + (b & 31) * KB;
#pragma unroll
        for (int j = 0; j < 3; j++) if (tid + j * NT < NB * CELL / 4) ((uint4*)stage)[tid + j * NT] = make_uint4(dk, dk, dk, dk);
    }
    if (tid < 136) cnt[tid] = 0;
    if (tid == 0) { *(uint4*)(smem + SM_MISC + 1824 + 32) = make_uint4(0, 0, 0, 0); *(uint4*)(smem + SM_RECS + NB * CELL * 16) = make_uint4(0, 0, 0, 0); }
    if (tid < 80) { deg[tid] = 127 - tid; order[tid] = tid; }
    __syncthreads();
    TSTAMP(9);
    if (tid == 64) {
        __nanosleep(YDELAY);
        asm volatile("mbarrier.arrive.expect_tx.shared.b64 _, [%0], %1;" :: "r"(mbarR), "r"((c1 - c0) * 64) : "memory");
        asm volatile("cp.async.bulk.shared::cluster.global.mbarrier::complete_tx::bytes [%0], [%1], %2, [%3];"
                     :: "r"(sb + SM_RAWY), "l"(Y + 2 * c0), "r"((c1 - c0) * 32), "r"(mbarR) : "memory");
        asm volatile("cp.async.bulk.shared::cluster.global.mbarrier::complete_tx::bytes [%0], [%1], %2, [%3];"
                     :: "r"(sb + SM_RAWE), "l"(ef + 2 * c0), "r"((c1 - c0) * 32), "r"(mbarR) : "memory");
    }

    uint32_t bin[4] = {0, 0, 0, 0}, slot[4] = {0, 0, 0, 0};
    if (has4) {
        const uint32_t dd[4] = {(uint32_t)d4.x, (uint32_t)d4.y, (uint32_t)d4.z, (uint32_t)d4.w}, ss[4] = {(uint32_t)s4.x, (uint32_t)s4.y, (uint32_t)s4.z, (uint32_t)s4.w};
#pragma unroll
        for (int k = 0; k < 4; k++) { bin[k] = dd[k] / NPB; slot[k] = atomicAdd(&cnt[bin[k]], 1); }
#pragma unroll
        for (int k = 0; k < 4; k++) stage[bin[k] * CELL + min(slot[k], CELL - 1)] = (dd[k] - bin[k] * NPB) * KN + ss[k];
    }
    if (w == CW) {
        if (tid == NT - 1) { par = par >= NB; flag[14] = (par ^ 1) << 31; }
        asm volatile("cp.async.wait_all;" ::: "memory");
    }
    bar_sync(1, NT);
    TSTAMP(1);
    const uint32_t tag = flag[14];
#pragma unroll
    for (int j = 0; j < 2; j++) {
        const int i = tid + j * NT;
        if (i < NPIECE) {
            const uint2 sa = *(const uint2*)(stage + i * 6), sc = *(const uint2*)(stage + i * 6 + 2);
            uint2 se = *(const uint2*)(stage + i * 6 + 4);
            const uint32_t cf = cnt[i >> 3], cn = min(cf, 63u);
            if ((i & 7) == 7) {
                const uint32_t al = cf > CELL - 8 ? 7 : 0;
                uint32_t o;
                asm volatile("atom.shared.add.u32 %0, [%1], %2;" : "=r"(o) : "r"(sb + SM_MISC + 1824 + 60), "r"(cf + al) : "memory");
                se.y = (o + al) & ~al;
                cnt2[i >> 3] = se.y;
            }
            asm volatile("{.reg .b64 lo, hi; mov.b64 lo, {%1,%2}; mov.b64 hi, {%3,%4}; st.relaxed.gpu.global.v2.b64 [%0], {lo, hi};}"
                         :: "l"(gs->keys + ((i >> 3) * NB + b) * 8 + ((i ^ b) & 7)),
                            "r"(sa.x | (se.x << 20)), "r"(sa.y | ((se.x >> 12) << 20) | ((cn & 7) << 28) | tag),
                            "r"(sc.x | (se.y << 20)), "r"(sc.y | ((se.y >> 12) << 20) | ((cn >> 3) << 28) | tag) : "memory");
        }
    }
    bar_sync(1, NT);
    if (tid == NT - 1) {
        TSTAMPC(10);
        gbar_arrive(&gs->bar[0]);
        asm volatile("mbarrier.arrive.expect_tx.shared.b64 _, [%0], %1;" :: "r"(mbarK), "r"(NPIECE * 16) : "memory");
        unsigned v; int spins = 0;
        do { asm volatile("ld.relaxed.gpu.global.u32 %0, [%1];" : "=r"(v) : "l"(gs->bar) : "memory"); } while ((v >= NB) == par && ++spins < (1 << 22));
        TSTAMPC(13);
        asm volatile("fence.proxy.async.global;" ::: "memory");
        asm volatile("cp.async.bulk.shared::cluster.global.mbarrier::complete_tx::bytes [%0], [%1], %2, [%3];"
                 :: "r"(sb + SM_KEYS), "l"(gs->keys + b * NPIECE), "r"(NPIECE * 16), "r"(mbarK) : "memory");
    }
    __syncwarp();
    uint32_t at[4];
    {
        const int o = g & 3, f = 2 * (t & 1);
#pragma unroll
        for (int i = 0; i < 4; i++) {
            const uint16_t* cp = (const uint16_t*)(smem + SM_SMALL + 1024) + i * 16 + f * 4 + o;
            at[i] = (t >> 1) == (g >> 2) ? cp[0] | ((uint32_t)cp[4] << 16) : 0;
        }
    }

    const int q = lane >> 3, c = lane & 7;
    const uint32_t ring0 = sb + SM_RING + w * 2048;
    uint32_t wdst = ring0 + q * 128 + ((c + 2 * q) & 7) * 16;
    uint32_t rsrc = ring0 + t * 128 + ((g + 2 * t) & 7) * 16;
    uint32_t recl = sb + SM_META + w * (CAP * STEPB) + g * 16 + (t & 1) * 8, srcl = sb + SM_META + w * (CAP * STEPB) + 128 + q * 8 + (c >> 1) * STEPB + (c & 1) * 4;
    uint32_t flg = sb + SM_MISC + (136 + 104 + 80 + 136) * 4;
    asm volatile("" : "+r"(wdst), "+r"(rsrc), "+r"(recl), "+r"(srcl), "+r"(flg));
    auto setflag = [&]() { sts32(flg, 1); };
    uint32_t key[2][6], ha[2][6], rk[2][6], kidx[2], ka[2], kc[2];
    int nk[2];
#pragma unroll
    for (int j = 0; j < 2; j++) {
        const int i0 = j ? 2 * 608 - 1 - tid : tid, i = min(i0, NPIECE - 1), r = i / NB, cc = i - r * NB;
        ka[j] = sb + SM_KEYS + (cc * 8 + ((r ^ cc) & 7)) * 16;
        kidx[j] = (cc * CELL + r * 6) << 17;
        kc[j] = sb + SM_MISC + cc * 4;
        nk[j] = i0 < NPIECE && w < CW ? -6 * r : -1000;
    }
    asm volatile("" : "+r"(at[0]), "+r"(at[1]), "+r"(at[2]), "+r"(at[3]), "+r"(ka[0]), "+r"(ka[1]), "+r"(kidx[0]), "+r"(kidx[1]), "+r"(kc[0]), "+r"(kc[1]), "+r"(nk[0]), "+r"(nk[1]));
    if (w == CW) {
        __syncwarp();
        bar_sync(7, NT);
        if (tid == NT - 1) {
            TSTAMPC(11);
            asm volatile("cp.async.bulk.global.shared::cta.bulk_group [%0], [%1], %2;"
                         :: "l"(gs->recs + b * RCH), "r"(sb + SM_ROUT), "r"(((flag[15] + 1) & ~1u) * 16) : "memory");
            asm volatile("cp.async.bulk.commit_group;" ::: "memory");
            mbar_wait(mbarK, 0);
            unsigned long long tbase;
            asm volatile("mov.u64 %0, %%globaltimer;" : "=l"(tbase));
            tbase += POFF;
            flag[1] = (uint32_t)tbase; flag[4] = (uint32_t)tbase; flag[5] = (uint32_t)(tbase >> 32);
            asm volatile("red.max.relaxed.gpu.global.u64 [%0], %1;" :: "l"(&gs->t0), "l"(tbase) : "memory");
            if (b < 128) asm volatile("cp.async.bulk.prefetch.L2.global [%0], 256;" :: "l"(w_mix + b * 16));
            asm volatile("cp.async.bulk.wait_group 0;" ::: "memory");
            TSTAMPC(14);
            gbar_arrive(&gs->bar[1]);
            TSTAMPC(15);
        }
    } else {
        if (w < 8) {
            const uint32_t* wp = (const uint32_t*)(smem + SM_SMALL) + (t & 1) * 128 + 8 * w + g;
            const uint32_t wr0 = t < 2 ? wp[0] : 0, wr1 = t < 2 ? wp[64] : 0;
            *(uint2*)(smem + SM_AZ + (w >> 1) * 512 + lane * 16 + (w & 1) * 8) =
                make_uint2(pack2(0.5f * bf2f(wr0 & 0xFFFF), 0.5f * bf2f(wr1 & 0xFFFF)), pack2(0.5f * bf2f(wr0 >> 16), 0.5f * bf2f(wr1 >> 16)));
        }
        const bool sw = g & 1;
        uint32_t rp[4];
#pragma unroll
        for (int k = 0; k < 4; k++) rp[k] = cnt2[bin[k]] + slot[k];
        uint4* ro = (uint4*)(smem + SM_ROUT);
        uint4 *p0 = ro + (sw ? rp[2] : rp[0]), *p1 = ro + (sw ? rp[3] : rp[1]), *p2 = ro + (sw ? rp[0] : rp[2]), *p3 = ro + (sw ? rp[1] : rp[3]);
        const uint32_t ya = sb + SM_RAWY + tid * 32 + (sw ? 16 : 0);
        mbar_wait(mbarR, 0);
        TSTAMP(18);
        if (has4) {
            const uint4 y0 = lds128(ya), e0 = lds128(ya + (SM_RAWE - SM_RAWY)), y1 = lds128(ya ^ 16), e1 = lds128((ya ^ 16) + (SM_RAWE - SM_RAWY));
            *p0 = make_uint4(y0.x, e0.x, y0.y, e0.y); *p1 = make_uint4(y0.z, e0.z, y0.w, e0.w);
            *p2 = make_uint4(y1.x, e1.x, y1.y, e1.y); *p3 = make_uint4(y1.z, e1.z, y1.w, e1.w);
        }
        asm volatile("fence.proxy.async.shared::cta;" ::: "memory");
        bar_arrive(7, NT);
    }
    __syncwarp();
    TSTAMP(2);

    if (w < CW) {
        mbar_wait(mbarK, 0);
        TSTAMP(3);
        uint4 v[2] = {lds128(ka[0]), lds128(ka[1])};
        if ((int)((v[0].y ^ tag) | (v[0].w ^ tag) | (v[1].y ^ tag) | (v[1].w ^ tag)) < 0) {
#pragma unroll
            for (int j = 0; j < 2; j++) {
                int spins = 0;
#pragma unroll 1
                while ((int)((v[j].y ^ tag) | (v[j].w ^ tag)) < 0) {
                    asm volatile("{.reg .b64 lo, hi; ld.relaxed.gpu.global.v2.b64 {lo, hi}, [%4]; mov.b64 {%0,%1}, lo; mov.b64 {%2,%3}, hi;}"
                                 : "=r"(v[j].x), "=r"(v[j].y), "=r"(v[j].z), "=r"(v[j].w) : "l"((const unsigned char*)(gs->keys + b * NPIECE) + (ka[j] - sb - SM_KEYS)) : "memory");
                    if (++spins > (1 << 20)) { setflag(); break; }
                }
            }
        }
#pragma unroll
        for (int j = 0; j < 2; j++) {
            const uint32_t hc = ((v[j].y >> 28) & 7) | ((v[j].w >> 25) & 0x38);
            if (j == 1 && nk[j] == -42) {
                sts32(kc[j], hc | ((v[j].z >> 20) << 8));
                if (hc > CELL - 1) setflag();
                v[j].w |= ((80 * KN) >> 12) << 20;
            }
            nk[j] += hc;
            if (nk[j] > 0) {
                key[j][0] = v[j].x & 0xFFFFF; key[j][1] = v[j].y & 0xFFFFF; key[j][2] = v[j].z & 0xFFFFF; key[j][3] = v[j].w & 0xFFFFF;
                key[j][4] = (v[j].x >> 20) | ((v[j].y >> 8) & 0xFF000); key[j][5] = (v[j].z >> 20) | ((v[j].w >> 8) & 0xFF000);
#pragma unroll
                for (int u = 0; u < 6; u++) {
                    ha[j][u] = __umulhi(key[j][u], 0xFFFFFFFFu / KB + 1);
                    asm volatile("{.reg .u32 a, n; mad.lo.u32 a, %1, 4, %2; atom.shared.add.u32 %0, [a+%3], 1;\n"
                                 "shr.u32 n, %1, 5; mad.lo.u32 a, n, 4, %2; red.shared.add.u32 [a+%4], 128;}"
                                 : "=r"(rk[j][u]) : "r"(ha[j][u]), "r"(sb), "n"(SM_HIST), "n"(SM_MISC + 136 * 4) : "memory");
                }
            }
        }
        bar_sync(9, NT - 32);
        TSTAMP(20);
        const int n = tid >> 3, sub = tid & 7;
        const uint32_t me = deg[n];
        uint32_t r = 0, r2 = 0;
#pragma unroll
        for (int k = 0; k < 5; k++) { const uint2 dd = *(const uint2*)(deg + sub * 10 + 2 * k); r += (me - dd.x) >> 31; r2 += (me - dd.y) >> 31; }
        r += r2;
#pragma unroll
        for (int j = 0; j < 2; j++) kidx[j] += (lds32(kc[j]) & 0x700) << 9;
        r += __shfl_xor_sync(0xffffffff, r, 1); r += __shfl_xor_sync(0xffffffff, r, 2); r += __shfl_xor_sync(0xffffffff, r, 4);
        if (sub == 0) order[r] = n;
    }
    bar_sync(1, NT);
    TSTAMP(22);
    uint32_t len2;
    {
        const uint2 na = *(const uint2*)(order + 2 * w);
        uint2 nb = *(const uint2*)(order + 78 - 2 * w);
        const uint32_t hl = sb + SM_HIST + lane * 4;
        const uint32_t ha0 = lds32(hl + na.x * 128), ha1 = lds32(hl + na.y * 128), hb0 = lds32(hl + nb.y * 128), hb1 = lds32(hl + nb.x * 128);
        if (deg[na.x] >= (4 * CAP + 1) * 128) setflag();
        const uint32_t ca = ha0 + (ha1 << 16), c4 = ca + (hb0 << 8) + (hb1 << 24);
        uint32_t inc = c4;
#pragma unroll
        for (int o = 1; o < 32; o <<= 1)
            asm volatile("{.reg .pred p; .reg .u32 u; shfl.sync.up.b32 u|p, %0, %1, 0, 0xffffffff; @p add.u32 %0, %0, u;}" : "+r"(inc) : "r"(o));
        const int su = __reduce_add_sync(0xffffffff, (int)(ha0 - ha1) * (2 * lane - 31)), sv = __reduce_add_sync(0xffffffff, (int)(hb0 - hb1) * (2 * lane - 31));
        const bool swp = (su ^ sv) >= 0;
        if (swp) { nb = make_uint2(nb.y, nb.x); *(uint2*)(order + 78 - 2 * w) = nb; }
        const uint32_t sel = swp ? 0x4143 : 0x4341, ex = inc - c4;
        const uint32_t ea = (ex & 0x00FF00FF) + __byte_perm(ex, 0, sel), eb = ea + ca, base = sb + SM_LIST + w * 2048;
        uint2* pos = (uint2*)(smem + SM_POS) + lane;
        pos[na.x * 32] = make_uint2(base + (ea & 0xFFFF) * 8, na.x * (0u - 4 * KN));
        pos[nb.y * 32] = make_uint2(base + (eb & 0xFFFF) * 8, nb.y * (0u - 4 * KN) + 0x80000000u);
        pos[na.y * 32] = make_uint2(base + 4 + (ea >> 16) * 8, na.y * (0u - 4 * KN));
        pos[nb.x * 32] = make_uint2(base + 4 + (eb >> 16) * 8, nb.x * (0u - 4 * KN) + 0x80000000u);
        len2 = __shfl_sync(0xffffffff, (inc & 0x00FF00FF) + __byte_perm(inc, 0, sel), 31);
        if (max(len2 & 0xFFFF, len2 >> 16) > 4 * CAP) setflag();
    }
    uint32_t ci = cnt[min(w + NW * lane, NB)];
    ci = (((ci & 0xFF) + ((ci >> 8) & 7)) << 24) + min(w + NW * lane, NB) * (RCH / 8) + (ci >> 11);
    if (w == CW) {
        bar_arrive(9, NT);
        if (tid == NT - 1) {
            uint32_t v1, g0; int spins = 0;
            do {
                asm volatile("ld.relaxed.gpu.global.u32 %1, [%2+8]; ld.acquire.gpu.global.u32 %0, [%2+4];" : "=r"(v1), "=r"(g0) : "l"(gs->bar) : "memory");
            } while ((v1 >= NB) == par && ++spins < (1 << 22));
            if ((v1 >= NB) == par) *flag = 1;
            if (g0 - flag[1] < 30000) flag[1] = g0;
            TSTAMPC(17);
        }
        __syncwarp();
    } else {
        bar_sync(9, NT);
        TSTAMP(21);
        const uint32_t over = lds32(flg);
#pragma unroll
        for (int j = 0; j < 2; j++) {
            if (nk[j] > 0) {
                uint2 h[6];
#pragma unroll
                for (int u = 0; u < 6; u++) h[u] = lds64(sb + SM_POS + ha[j][u] * 8);
                if (over) nk[j] = 0;
#pragma unroll
                for (int u = 0; u < 6; u++)
                    asm volatile("{.reg .pred p; setp.gt.s32 p, %2, %3; @p st.shared.u32 [%0], %1;}"
                                 :: "r"(h[u].x + rk[j][u] * 8), "r"(key[j][u] * 4 + h[u].y + (kidx[j] + (u << 17))), "r"(nk[j]), "r"(u) : "memory");
            }
        }
    }
    bar_sync(1, NT);
    TSTAMP(4);
    if (*flag) {
        slow_path(smem, n0, nn, (const uint16_t*)x, (const int*)src4, (const int*)dst4, (const uint16_t*)Y, (const uint16_t*)ef, w_rad, cg,
                  (const uint16_t*)w_mix, (__nv_bfloat16*)out);
        return;
    }
    {
        const uint4* gp = gs->recs + lane;
        asm volatile("" : "+l"(gp));
        const uint32_t sp = sb + SM_RECS + (w * CELL + lane) * 16, lc = (lane << 24) | 0xFFFFFF;
#pragma unroll
        for (int j = 0; j < 7; j++)
            asm volatile("{.reg .pred p; .reg .u32 l; .reg .u64 a; setp.lt.u32 p, %2, %3; and.b32 l, %3, 0xFFFF; mad.wide.u32 a, l, 128, %1;\n"
                         "@p cp.async.cg.shared.global [%0], [a], 16;}"
                         :: "r"(sp + j * (NW * CELL * 16)), "l"(gp), "r"(lc), "r"(__shfl_sync(0xffffffff, ci, j)) : "memory");
        for (uint32_t m = __ballot_sync(0xffffffff, ci >= (33u << 24)); m; m &= m - 1) {
            const int j = __ffs(m) - 1;
            const uint32_t cj = __shfl_sync(0xffffffff, ci, j);
            if (lane + 32 < (cj >> 24))
                asm volatile("cp.async.cg.shared.global [%0], [%1], 16;" :: "r"(sp + j * (NW * CELL * 16) + 512), "l"(gp + (size_t)(cj & 0xFFFF) * 8 + 32) : "memory");
        }
        asm volatile("cp.async.commit_group;" ::: "memory");
    }
    const int S = __shfl_sync(0xffffffff, max((int)(max(len2 & 0xFFFF, len2 >> 16) + 3) >> 2, DS + 1), 0);
    const int mylen = (lane & 1) ? len2 >> 16 : len2 & 0xFFFF;
    constexpr int NRAW = (CAP + 3) / 4;
    uint32_t bits0 = 0, raw[NRAW];
    unsigned char* meta = smem + SM_META + w * (CAP * STEPB);
    const int la = sb + SM_LIST + w * 2048 + lane * 4, llast = la - (lane & ~1) * 4 + (mylen - 1) * 8;
#pragma unroll
    for (int k = 0; k < NRAW; k++) raw[k] = lds32(min(la + k * 128, llast));
    const uint32_t sv0 = min(raw[0] & 0xFFFC, 4 * (NN - 1));
    const unsigned char* pbase = x + c * 16;
    asm volatile("" : "+l"(pbase));
    auto cpa2 = [&](uint32_t dstp, uint32_t sv) {
        asm volatile("cp.async.cg.shared.global [%0], [%1], 16; cp.async.cg.shared.global [%0+1024], [%1+128], 16;"
                     :: "r"(dstp), "l"(pbase + (size_t)sv * 256) : "memory");
    };
    auto cpa2p = [&](uint32_t dstp, uint32_t sv) {
        asm volatile("{.reg .pred p; setp.ge.s32 p, %2, 0; @p cp.async.cg.shared.global [%0], [%1], 16; @p cp.async.cg.shared.global [%0+1024], [%1+128], 16;}"
                     :: "r"(dstp), "l"(pbase + (size_t)sv * 256), "r"(sv) : "memory");
    };
    auto wait_until = [&](uint32_t tt) {
        asm volatile("{.reg .pred p; .reg .u32 d;\n"
                     "PACE_LOOP: mov.u32 d, %%globaltimer_lo; sub.u32 d, %0, d; setp.lt.u32 p, d, 32768; @p nanosleep.u32 %1; @p bra.uni PACE_LOOP;}"
                     :: "r"(tt), "n"(PSLEEP) : "memory");
    };
    const uint32_t tfill = flag[1] - FOFF;
    auto fill = [&](int i) {
        wait_until(tfill + i * FDT);
        cpa2(wdst + i * SLOTB, __shfl_sync(0xffffffff, sv0, 8 * i + 2 * q)); cpa2(wdst + i * SLOTB + 512, __shfl_sync(0xffffffff, sv0, 8 * i + 2 * q + 1));
        asm volatile("cp.async.commit_group;" ::: "memory");
    };
    fill(0);
    TSTAMP(5);
    auto relay = [&]() {
        uint32_t g0, g1, b0, b1;
        asm volatile("ld.volatile.shared.v2.u32 {%0,%1}, [%4+40]; ld.volatile.shared.v2.u32 {%2,%3}, [%4+16];"
                     : "=r"(g0), "=r"(g1), "=r"(b0), "=r"(b1) : "r"(flg) : "memory");
        const unsigned long long dg = (((unsigned long long)g1 << 32) | g0) - (((unsigned long long)b1 << 32) | b0);
        asm volatile("{.reg .pred p, q; setp.eq.u32 p, %1, 0; setp.lt.u64 q, %2, 30000; @q st.shared.u32 [%3+4], %4;\n"
                     "@p cp.async.cg.shared.global [%3+32], [%0], 16;}"
                     :: "l"(gs->bar), "r"(lane), "l"(dg), "r"(flg), "r"(g0) : "memory");
    };
    auto report = [&](uint32_t cand) {
        uint32_t b0, b1;
        asm volatile("ld.volatile.shared.v2.u32 {%0,%1}, [%2+16];" : "=r"(b0), "=r"(b1) : "r"(flg) : "memory");
        asm volatile("{.reg .pred p; setp.eq.u32 p, %2, 0; @p red.max.relaxed.gpu.global.u64 [%0], %1;}"
                     :: "l"(&gs->t0), "l"((((unsigned long long)b1 << 32) | b0) + (cand - b0)), "r"(lane) : "memory");
    };
    uint32_t ra[NRAW];
#pragma unroll
    for (int k = NRAW - 1; k >= 0; k--) {
        const uint32_t m = (__ballot_sync(0xffffffff, (int)raw[k] < 0) >> g) & 0x01010101u;
        bits0 = __funnelshift_l(m * 0x10204080u, bits0, 4);
        const bool pad = la + k * 128 > llast;
        ra[k] = pad ? NB * CELL * 16 : (raw[k] >> 13) & 0x1FFF0;
        raw[k] = (raw[k] & 0xFFFF) | (pad ? F_PAD : 0);
    }
    if (t < 2) bits0 = ~bits0;
    asm volatile("" : "+r"(bits0), "+r"(ra[0]), "+r"(ra[1]), "+r"(ra[2]), "+r"(ra[3]), "+r"(ra[4]), "+r"(raw[0]), "+r"(raw[1]), "+r"(raw[2]), "+r"(raw[3]), "+r"(raw[4]));
    fill(1);
    asm volatile("cp.async.wait_group 2;" ::: "memory");
    bar_sync(1, NT);
    TSTAMP(19);
    if (w == CW) {
        uint32_t tn; asm volatile("mov.u32 %0, %%globaltimer_lo;" : "=r"(tn));
        if ((int)(tn + RDY - flag[1]) > 0) { report(tn + RDY); flag[1] = tn + RDY; }
    }
    {
        uint4 rv[NRAW];
#pragma unroll
        for (int k = 0; k < NRAW - 1; k++) rv[k] = lds128(ra[k] + (sb + SM_RECS));
        if ((NRAW - 1) * 4 < S) rv[NRAW - 1] = lds128(ra[NRAW - 1] + (sb + SM_RECS));
        fill(2);
        bar_sync(1, NT);
        TSTAMP(12);
        unsigned char* mr = meta + (q - 1) * STEPB + c * 16;
        unsigned char* ms = meta + (q - DS - 1) * STEPB + 128 + c * 4;
#pragma unroll
        for (int k = 0; k < NRAW; k++) {
            if (k == 0) {
                *(uint4*)(mr + (q == 0 ? S * STEPB : 0)) = rv[k];
                *(uint32_t*)(ms + S * STEPB) = raw[0] + F_WRAP;
            } else if (k * 4 + q < S) {
                *(uint4*)(mr + k * 4 * STEPB) = rv[k];
                *(uint32_t*)(ms + k * 4 * STEPB + (k == 1 && q == 0 ? S * STEPB : 0)) = raw[k];
            }
        }
    }
    __syncwarp();
    const uint32_t tphase = PACE / 4;
    uint32_t dreg;
    {
        const int ls = lane >= S ? min(lane - S, S - 1) : lane, st = ls == 0 ? S - 1 : ls - 1;
        const uint4 u0 = *(const uint4*)(meta + st * STEPB + 128), u1 = *(const uint4*)(meta + st * STEPB + 144);
        int pos = (u0.x + u0.y + u0.z + u0.w + u1.x + u1.y + u1.z + u1.w) << 1 >> 6;
        pos += ((u0.x & F_WRAP) ? NN : 0) + (lane >= S ? NN : 0) - NN * (2 * DS + 1) / 32;
        dreg = pos * (int)tphase / NN;
    }
    fill(3);
    TSTAMP(6);

    uint32_t* stash = (uint32_t*)(gs->stash + (b * NW + w) * 256) + lane;
    asm volatile("" : "+l"(stash));
    float acc[4][4];
#pragma unroll
    for (int i = 0; i < 16; i++) acc[i / 4][i % 4] = 0.f;
    uint4 az = *(const uint4*)(smem + SM_AZ + lane * 16);
    uint32_t dcur = dreg, dl = 0, now = flag[1], tcur = 0;
    uint32_t mp = 0, smask = 1, didx = 2, nowe = 0;
    uint32_t mend = S * STEPB;
    uint2 r = lds64(mend - STEPB + recl);
    uint2 s0 = lds64(sb + SM_META + w * (CAP * STEPB) + 128 + q * 8 + mend - STEPB);
    float zn[4], yn[4];
    auto zpre = [&]() {
        mma1688zv(zn, az.x, az.y, r.y);
        mma1688zv(yn, az.z, az.w, r.y);
    };
    zpre();
    uint32_t s4r = 0;
    auto step = [&](const uint32_t off, const int mode, const bool pc = true) {
        const uint2 rc = r;
        const uint2 sc = s0;
        if (mode != 4) r = lds64(mp + recl);
        if (mode == 0 && off == 0) s4r = lds32(mp + srcl);
        asm volatile("cp.async.wait_group %0;" :: "n"(DS - 1) : "memory");
        const uint4 xa = lds128(rsrc + off), xb = lds128(rsrc + off + 512), xc = lds128(rsrc + off + 1024), xd = lds128(rsrc + off + 1536);
        float z[4], y[4], t1[4], t2[4];
        for (int i = 0; i < 4; i++) { z[i] = zn[i]; y[i] = yn[i]; }
        uint32_t bt;
        asm("{.reg .pred p; .reg .b32 m; and.b32 m, %2, %3; setp.ne.u32 p, m, 0; selp.b32 %0, %1, 0, p;}" : "=r"(bt) : "r"(rc.x), "r"(bits0), "r"(smask));
        mma1688z(t1, at[0], at[1], bt);
        mma1688z(t2, at[2], at[3], bt);
        const uint32_t T0 = pack2(t1[0], t1[2]), T1 = pack2(t2[0], t2[2]), T2 = pack2(t1[1], t1[3]), T3 = pack2(t2[1], t2[3]);
        uint32_t R[8];
#pragma unroll
        for (int i = 0; i < 4; i++) { R[i] = __float_as_uint(silu_h(z[i])); R[4 + i] = __float_as_uint(silu_h(y[i])); }
        auto tick = [&]() {
            if (mode == 0) {
                unsigned long long n64; asm volatile("mov.u64 %0, %%globaltimer;" : "=l"(n64));
                if (pc) now = (uint32_t)n64; else nowe = (uint32_t)n64;
            }
        };
        if (MO == 0) {
        mma16816(acc[0], mul_hi(xa.x, R[0]), mul_hi(xa.z, R[2]), mul_hi(xa.y, R[0]), mul_hi(xa.w, R[2]), T0, T1);
        mma16816(acc[1], mul_hi(xb.x, R[1]), mul_hi(xb.z, R[3]), mul_hi(xb.y, R[1]), mul_hi(xb.w, R[3]), T2, T3);
        if (BP == 2) tick();
        mma16816(acc[2], mul_hi(xc.x, R[4]), mul_hi(xc.z, R[6]), mul_hi(xc.y, R[4]), mul_hi(xc.w, R[6]), T0, T1);
        } else {
        mma16816(acc[0], mul_hi(xa.x, R[0]), mul_hi(xa.z, R[2]), mul_hi(xa.y, R[0]), mul_hi(xa.w, R[2]), T0, T1);
        mma16816(acc[2], mul_hi(xc.x, R[4]), mul_hi(xc.z, R[6]), mul_hi(xc.y, R[4]), mul_hi(xc.w, R[6]), T0, T1);
        if (BP == 2) tick();
        mma16816(acc[1], mul_hi(xb.x, R[1]), mul_hi(xb.z, R[3]), mul_hi(xb.y, R[1]), mul_hi(xb.w, R[3]), T2, T3);
        }
        if (BP == 3) tick();
        const uint32_t y0 = mul_hi(xd.x, R[5]), y1 = mul_hi(xd.z, R[7]), y2 = mul_hi(xd.y, R[5]), y3 = mul_hi(xd.w, R[7]);
        if (BP == 5) tick();
        mma16816(acc[3], y0, y1, y2, y3, T2, T3);
        if (mode != 4 && mode != 0) zpre();
        if (mode == 0) {
            if (BP == 4) tick();
            zpre();
            s0.x = __shfl_sync(0xffffffff, s4r, off / SLOTB * 2, 8); s0.y = __shfl_sync(0xffffffff, s4r, off / SLOTB * 2 + 1, 8);
            if (pc) { dl = __shfl_sync(0xffffffff, dcur, didx); didx += 2; }
            cpa2p(wdst + off, sc.x); cpa2p(wdst + off + 512, sc.y);
        }
        if (mode == 1 && w < 16) {
            const int lane = tid & 31, q = lane >> 3, c = lane & 7;
            const uint32_t ring0 = sb + SM_RING + w * 2048;
#pragma unroll
            for (int j = 0; j < 4; j++) {
                const int kk = 4 * j + q, ch = 16 * (w & 7) + 2 * (kk & 7) + (kk >> 3);
                asm volatile("cp.async.cg.shared.global [%0], [%1], 16;" :: "r"(ring0 + kk * 128 + ((c ^ (kk & 7)) << 4)), "l"(w_mix + ch * 16 + (w >> 3) * 8 + c) : "memory");
            }
            asm volatile("cp.async.mbarrier.arrive.noinc.shared.b64 [%0];" :: "r"(mbarW) : "memory");
        }
        if (mode == 2 || mode == 3) {
            const int lane = tid & 31;
            const uint32_t ring0 = sb + SM_RING + w * 2048;
#pragma unroll
            for (int j = 0; j < 4; j += mode - 1)
                asm volatile("cp.async.cg.shared.global [%0], [%1], 16;" :: "r"(ring0 + off + j * 512 + lane * 16), "l"(stash + (mode - 2) * 512 + j * 128 + lane * 3) : "memory");
        }
        if (mode < 4) asm volatile("cp.async.commit_group;" ::: "memory");
        mp += STEPB; smask <<= 1;
    };
    auto putacc = [&](uint32_t* p) {
        p[0] = pack2(acc[0][0], acc[0][1]); p[32] = pack2(acc[0][2], acc[0][3]); p[64] = pack2(acc[2][0], acc[2][1]); p[96] = pack2(acc[2][2], acc[2][3]);
        p[256] = pack2(acc[1][0], acc[1][1]); p[288] = pack2(acc[1][2], acc[1][3]); p[320] = pack2(acc[3][0], acc[3][1]); p[352] = pack2(acc[3][2], acc[3][3]);
    };
    int ph = 0;
    auto phase_end = [&](const int k) {
        az = lds128(sb + SM_AZ + (ph + 1) * 512 + lane * 16);
        putacc(stash + ph * ph * 128);
#pragma unroll
        for (int i = 0; i < 16; i++) acc[i / 4][i % 4] = 0.f;
        pbase += 256; mp = 0; smask = 1; ph++;
        zpre();
        if (k < 3) s4r = lds32(srcl - (k + 1) * STEPB);
        dcur += tphase; didx = 1 + (k & 1);
        if (ph == 3) {
            mend -= DS * STEPB;
            dcur += (int)(dcur - __shfl_sync(0xffffffff, dcur, 0)) * (((w >> 2) - 2) * FAN) >> 8;
        }
        WSTAMP(ph - 1);
    };
    uint32_t t0 = now;
    if (w == PW) {
        asm volatile("mov.u32 %0, %%globaltimer_lo;" : "=r"(now));
        now += PTOL - PTOL0;
    }
    const uint32_t bias = w == RW ? 1u << 20 : 0;
    if (w == RW) relay();
    dcur += bias;
    auto body = [&](const int k) -> bool {
        if (k == 2) asm volatile("ld.volatile.shared.u32 %0, [%1+4];" : "=r"(t0) : "r"(flg));
        const bool pc = k & 1;
        step(k * SLOTB, 0, pc);
        if (!pc) {
            if (mp == mend) phase_end(k);
        } else if (mp == mend || now < dl) {
            if (mp == mend) {
                if (k == 3 && ph == 3) return true;
                phase_end(k);
            }
            if (w == RW) dl -= 1u << 20;
            if (w == RW) {
                relay();
                {
                    const int lane = tid & 31, n0 = cta_now() * NPB, nn = min(NPB, NN - n0);
                    const int row = (mp / (2 * STEPB)) * (16 * XPF) + (lane >> 1);
#pragma unroll
                    for (int u = 0; u < XPF; u++)
                        asm volatile("{.reg .pred p; setp.lt.s32 p, %1, %2; @p prefetch.global.L2 [%0];}"
                                     :: "l"(x + (size_t)(n0 + row + 16 * u) * 1024 + (ph + 1) * 256 + (lane & 1) * 128), "r"(row + 16 * u), "r"(ph < 3 ? nn : 0));
                }
            }
            wait_until(nowe == 12345 ? dl + 1 : dl);
        }
        return false;
    };
    if (w >= 4 && w < 9) {
        const int i = tid_now() - 128;
        if ((i >> 1) < nn && b >= XPF0) asm volatile("prefetch.global.L2 [%0];" :: "l"(x + (size_t)(n0 + (i >> 1)) * 1024 + (i & 1) * 128));
    }
    {
        const uint32_t d0 = __shfl_sync(0xffffffff, dreg, 0);
        if (w == RW) {
            uint32_t g0, tn; int spins = 0;
            do {
                asm volatile("ld.relaxed.gpu.global.u32 %0, [%2]; mov.u32 %1, %%globaltimer_lo;" : "=r"(g0), "=r"(tn) : "l"(&gs->t0) : "memory");
                if (g0 - t0 < 30000) { t0 = g0; flag[1] = g0; }
            } while (__shfl_sync(0xffffffff, t0 - tn, 0) < 32768 && ++spins < 64);
        }
        asm volatile("{.reg .pred p; .reg .u32 d;\n"
                     "PACE_LOOP: ld.volatile.shared.u32 %0, [%2+4]; mov.u32 d, %%globaltimer_lo; sub.u32 d, %1, d; add.u32 d, d, %0;\n"
                     "setp.lt.u32 p, d, 32768; @p nanosleep.u32 32; @p bra.uni PACE_LOOP;}"
                     : "=&r"(t0) : "r"(d0), "r"(flg) : "memory");
    }
    while (true) {
        if (w == PW) {
            const uint32_t cand = now - dl + tcur - PTOL;
            if ((int)(cand - t0) > 0) report(cand);
        }
        dcur += t0 - tcur; tcur = t0;
        body(0); body(1); body(2);
        if (body(3)) break;
    }
    __syncwarp();
    step(0, 1);
    { uint32_t tn; asm volatile("mov.u32 %0, %%globaltimer_lo;" : "=r"(tn)); wait_until(tn + (w >> 2) * TDEL); }
    step(SLOTB, 2); step(2 * SLOTB, 3); step(3 * SLOTB, 4);
    WSTAMP(3); ESTAMP(0);

    {
        const int tid = tid_now(), lane = tid & 31, g = lane >> 2, t = lane & 3, n0 = cta_now() * NPB, nn = min(NPB, NN - n0);
        putacc((uint32_t*)(smem + SM_RING + 2 * SLOTB + w * 2048 + 512) + lane);
        const int wg = w >> 2, w4 = w & 3;
        int nd[8];
#pragma unroll
        for (int j = 0; j < 8; j++) { const int l = wg * 8 + j; nd[j] = order[(t >> 1) ? 79 - l : l]; asm volatile("" : "+r"(nd[j])); }
        const bool odd = t & 1;
        uint2* ob = (uint2*)out + (size_t)n0 * 128 + w4 * 16 + g + (odd ? 8 : 0);
        asm volatile("cp.async.wait_all;" ::: "memory");
        mbar_wait(mbarW, 0);
        asm volatile("fence.proxy.async.shared::cta;" ::: "memory");
        ESTAMP(1);
        bar_sync(2 + wg, 128);
        uint32_t ticket = 0;
        if ((tid & 127) == 0) {
            asm volatile("atom.shared.add.u32 %0, [%1+48], 1;" : "=r"(ticket) : "r"(flg) : "memory");
            int spins = 0;
            while (flag[13] < ticket && ++spins < (1 << 16)) __nanosleep(40);
        }
        bar_sync(2 + wg, 128);
        const uint64_t descA0 = (uint64_t)(((sb + SM_RING) & 0x3FFFF) >> 4) | ((uint64_t)1 << 16) | ((uint64_t)(1024 >> 4) << 32) | ((uint64_t)1 << 62);
        const uint64_t descB0 = (uint64_t)(((sb + SM_RING + SLOTB + wg * 8192) & 0x3FFFF) >> 4) | ((uint64_t)(128 >> 4) << 16) | ((uint64_t)(1024 >> 4) << 32);
        float d[2][32];
        asm volatile("wgmma.fence.sync.aligned;" ::: "memory");
        ESTAMP(2);
#pragma unroll
        for (int mt = 0; mt < 2; mt++) {
#pragma unroll
            for (int ks = 0; ks < 8; ks++) {
                if (mt * 8 + ks == RELK)
                    asm volatile("{.reg .pred p; setp.eq.u32 p, %1, 0; @p st.volatile.shared.u32 [%0+52], %2;}" :: "r"(flg), "r"(tid & 127), "r"(ticket + 1) : "memory");
                const uint64_t da = descA0 + (uint64_t)((ks * 2048 + mt * 16384) >> 4), db = descB0 + (uint64_t)(((ks & 3) * 256 + (ks >> 2) * SLOTB) >> 4);
                asm volatile("{.reg .pred p; setp.ne.b32 p, %34, 0;\n"
                    "wgmma.mma_async.sync.aligned.m64n64k16.f32.bf16.bf16 "
                    "{%0,%1,%2,%3,%4,%5,%6,%7,%8,%9,%10,%11,%12,%13,%14,%15,%16,%17,%18,%19,%20,%21,%22,%23,%24,%25,%26,%27,%28,%29,%30,%31}, %32, %33, p, 1, 1, 1, 1;}"
                    : "+f"(d[mt][0]), "+f"(d[mt][1]), "+f"(d[mt][2]), "+f"(d[mt][3]), "+f"(d[mt][4]), "+f"(d[mt][5]), "+f"(d[mt][6]), "+f"(d[mt][7]),
                      "+f"(d[mt][8]), "+f"(d[mt][9]), "+f"(d[mt][10]), "+f"(d[mt][11]), "+f"(d[mt][12]), "+f"(d[mt][13]), "+f"(d[mt][14]), "+f"(d[mt][15]),
                      "+f"(d[mt][16]), "+f"(d[mt][17]), "+f"(d[mt][18]), "+f"(d[mt][19]), "+f"(d[mt][20]), "+f"(d[mt][21]), "+f"(d[mt][22]), "+f"(d[mt][23]),
                      "+f"(d[mt][24]), "+f"(d[mt][25]), "+f"(d[mt][26]), "+f"(d[mt][27]), "+f"(d[mt][28]), "+f"(d[mt][29]), "+f"(d[mt][30]), "+f"(d[mt][31])
                    : "l"(da), "l"(db), "r"(ks));
            }
            asm volatile("wgmma.commit_group.sync.aligned;" ::: "memory");
        }
#pragma unroll
        for (int mt = 0; mt < 2; mt++) {
            if (mt == 0) asm volatile("wgmma.wait_group.sync.aligned 1;" ::: "memory");
            else asm volatile("wgmma.wait_group.sync.aligned 0;" ::: "memory");
            ESTAMP(3 + mt);
#pragma unroll
            for (int i = 0; i < 32; i++) asm volatile("" : "+f"(d[mt][i]) :: "memory");
#pragma unroll
            for (int j = 0; j < 8; j++) {
                const uint32_t v0 = pack2(d[mt][4 * j], d[mt][4 * j + 1]), v1 = pack2(d[mt][4 * j + 2], d[mt][4 * j + 3]);
                const uint32_t rv = __shfl_xor_sync(0xffffffff, odd ? v0 : v1, 1);
                if (nd[j] < nn) ob[nd[j] * 128 + mt * 64] = odd ? make_uint2(rv, v1) : make_uint2(v0, rv);
            }
        }
    }
    TSTAMP(8); ESTAMP(5);
}

__global__ void __launch_bounds__(NT, 1)
tfn_fallback(const uint16_t* x, const int* src, const int* dst, const uint16_t* Y, const uint16_t* ef, const uint16_t* w_rad,
             const uint16_t* cg, const uint16_t* w_mix, __nv_bfloat16* out) {
    extern __shared__ __align__(1024) unsigned char smem[];
    const int n0 = blockIdx.x * NPB;
    slow_path(smem, n0, min(NPB, NN - n0), x, src, dst, Y, ef, w_rad, cg, w_mix, out);
}

}

extern "C" void kernel_launch(void* const* d_in, const int* in_sizes, int n_in, void* d_out, int out_size) {
    (void)in_sizes; (void)n_in; (void)out_size;
    cudaFuncSetAttribute(tfn_kernel, cudaFuncAttributeMaxDynamicSharedMemorySize, SM_TOTAL);
    int dev = 0, sms = 0;
    cudaGetDevice(&dev);
    cudaDeviceGetAttribute(&sms, cudaDevAttrMultiProcessorCount, dev);
    if (sms < NB) {
        cudaFuncSetAttribute(tfn_fallback, cudaFuncAttributeMaxDynamicSharedMemorySize, NPB * 2048);
        tfn_fallback<<<NB, NT, NPB * 2048, cudaStreamPerThread>>>((const uint16_t*)d_in[0], (const int*)d_in[1], (const int*)d_in[2], (const uint16_t*)d_in[3],
            (const uint16_t*)d_in[4], (const uint16_t*)d_in[5], (const uint16_t*)d_in[6], (const uint16_t*)d_in[7], (__nv_bfloat16*)d_out);
        return;
    }
    Scratch* gs = nullptr;
    cudaGetSymbolAddress((void**)&gs, g_scratch);
    cudaLaunchConfig_t cfg = {};
    cfg.gridDim = dim3(NB); cfg.blockDim = dim3(NT); cfg.dynamicSmemBytes = SM_TOTAL; cfg.stream = cudaStreamPerThread;
    cudaLaunchAttribute at[1];
    at[0].id = cudaLaunchAttributeCooperative; at[0].val.cooperative = 1;
    cfg.attrs = at; cfg.numAttrs = 1;
    cudaLaunchKernelEx(&cfg, tfn_kernel, (const unsigned char*)d_in[0], (const int4*)d_in[1], (const int4*)d_in[2],
                       (const uint4*)d_in[3], (const uint4*)d_in[4], (const uint16_t*)d_in[5], (const uint16_t*)d_in[6],
                       (const uint4*)d_in[7], (uint32_t*)d_out, gs);
}
```
